```python
import torch

def _softmax(x, axis=-1):
    return torch.softmax(x, dim=axis)
def _gelu(x):
    return torch.nn.functional.gelu(x, approximate="tanh")
def _silu(x):
    return torch.nn.functional.silu(x)
def _sigmoid(x):
    return torch.sigmoid(x)
def _layernorm(x, axis=-1, eps=1e-5):
    m = x.mean(dim=axis, keepdim=True)
    v = x.var(dim=axis, keepdim=True, unbiased=False)
    return (x - m) / torch.sqrt(v + eps)
def _scatter_add(tgt, idx, src, axis=0):
    return tgt.clone().index_add_(axis, idx, src)
def _segment_sum(src, seg, n):
    out = torch.zeros((n,) + src.shape[1:], dtype=src.dtype)
    return out.index_add_(0, seg, src)
def _pad(x, pw):
    flat = tuple(v for pair in reversed(pw) for v in pair)
    return torch.nn.functional.pad(x, flat)

kernel_name = 'gated_mix__sliding_local_dilated__moe_arch_mod__prompt'

def setup_inputs():

    _w = (lambda a: (lambda t: t.to(torch.bfloat16) if t.is_floating_point() else t)(torch.as_tensor(a)))
    def _A_setup():
        B, S, D = 1, 2048, 640
        return {
            "x": _w((lambda *s: torch.randn(*s, dtype=torch.bfloat16) * 0.05)(B, S, D)),
            "wqkv": _w((lambda *s: torch.randn(*s, dtype=torch.bfloat16) * 0.8)(D, 3 * D)),
            "wo": _w((lambda *s: torch.randn(*s, dtype=torch.bfloat16) * 0.05)(D, D)),
        }
    _A_in = _A_setup()

    def _B_setup():
        B, S, D, F, C = 1, 2048, 640, 1728, 2
        return {
            "x": _w((lambda *s: torch.randn(*s, dtype=torch.bfloat16) * 0.05)(B, S, D)),
            "w_r": _w((lambda *s: torch.randn(*s, dtype=torch.bfloat16) * 1.6)(D)),
            "w_gate": _w((lambda *s: torch.randn(*s, dtype=torch.bfloat16) * 0.4)(D, F)),
            "w_up": _w((lambda *s: torch.randn(*s, dtype=torch.bfloat16) * 0.4)(D, F)),
            "w_down": _w((lambda *s: torch.randn(*s, dtype=torch.bfloat16) * 0.4)(F, D)),
        }
    _B_in = _B_setup()

    return {
        "A_x": _A_in["x"],
        "A_wqkv": _A_in["wqkv"],
        "A_wo": _A_in["wo"],
        "B_x": _B_in["x"],
        "B_w_r": _B_in["w_r"],
        "B_w_gate": _B_in["w_gate"],
        "B_w_up": _B_in["w_up"],
        "B_w_down": _B_in["w_down"],
        "gate_w": _w((lambda *s: torch.randn(*s, dtype=torch.bfloat16) * 0.05)(640) * 16.0),
    }

def reference(A_x, A_wqkv, A_wo, B_x, B_w_r, B_w_gate, B_w_up, B_w_down, gate_w):
    def _A_ref(x, wqkv, wo):
        B, S, D = x.shape
        H = 32; Dh = D // H
        W, dil = 8, 2
        qkv = (lambda x, *d: x.permute(*d))((x @ wqkv).reshape(B, S, 3, H, Dh), 2, 0, 3, 1, 4)
        q, k, v = qkv[0], qkv[1], qkv[2]
        scale = Dh ** -0.5
        pos = torch.arange(S)
        off = torch.arange(W) * dil
        idx = pos[:, None] - off[None, :]
        mask = idx >= 0
        idx_c = torch.where(mask, idx, 0).reshape(-1)
        kg = k[:, :, idx_c, :].reshape(B, H, S, W, Dh)
        vg = v[:, :, idx_c, :].reshape(B, H, S, W, Dh)
        logits = torch.einsum("bhsd,bhswd->bhsw", q, kg) * scale
        logits = torch.where(mask[None, None, :, :], logits, -1e9)
        attn = _softmax(logits, axis=-1)
        o = torch.einsum("bhsw,bhswd->bhsd", attn, vg)
        return (lambda x, *d: x.permute(*d))(o, 0, 2, 1, 3).reshape(B, S, D) @ wo

    def _B_ref(x, w_r, w_gate, w_up, w_down):
        B, S, D = x.shape
        C = 2
        r = x @ w_r
        idx = torch.argsort(-r, axis=-1)[:, :C]
        idx_e = (lambda x, n, axis: torch.repeat_interleave(x, n, dim=axis))(idx.reshape(B, C, 1), D, axis=2)
        x_sel = (lambda x, i, axis: torch.take_along_dim(x, i, dim=axis))(x, idx_e, axis=1)
        g = _silu(x_sel @ w_gate)
        u = x_sel @ w_up
        y = (g * u) @ w_down
        r_sel = _sigmoid((lambda x, i, axis: torch.take_along_dim(x, i, dim=axis))(r, idx, axis=1))
        y = y * r_sel.reshape(B, C, 1)
        b_off = (torch.arange(B) * S).reshape(B, 1)
        flat_idx = (idx + b_off).reshape(B * C)
        zero = (x * 0.0).reshape(B * S, D)
        upd = _scatter_add(zero, flat_idx, y.reshape(B * C, D), axis=0)
        return x + upd.reshape(B, S, D)

    x = A_x
    g = _sigmoid((x * gate_w).sum(-1, keepdims=True))
    a = _A_ref(x, A_wqkv, A_wo)
    b = _B_ref(x, B_w_r, B_w_gate, B_w_up, B_w_down)
    return g * a + (1 - g) * b
```

```cpp
#include <cuda_runtime.h>
#include <cuda_bf16.h>
#include <cuda.h>
#include <stdint.h>

namespace {

constexpr int NCTA = 128;
constexpr int NFFN = 108;
constexpr uint32_t SENT = 0xFFFFFFFFu;

constexpr uint32_t SB = 1024;
constexpr uint32_t SM_W = SB;
constexpr uint32_t SM_X = SB + 122880;
constexpr uint32_t SM_F = SB + 188416;
constexpr uint32_t SM_HALO = SB + 212992;
constexpr uint32_t SM_BAR = SB + 223232;
constexpr uint32_t SM_PROF = SB + 223744;
constexpr uint32_t SM_KEY = SB + 224000;
constexpr uint32_t SM_RED = SB + 224128;
constexpr uint32_t SM_XS = SB + 226688;
constexpr uint32_t SM_SENT = SB + 227328;
constexpr uint32_t SM_U = SM_RED + 1920;
constexpr uint32_t SM_GATE = SM_RED;
constexpr uint32_t SM_TOTAL = 232448;
constexpr uint32_t SM_HALO1 = SM_X + 32768;
constexpr uint32_t SM_UP = SM_W + 61440;
constexpr uint32_t SM_OUT = SM_W + 61440;

constexpr uint32_t B_XL0 = SM_BAR, B_FULL = SM_BAR + 8, B_GT = SM_BAR + 72, B_RG = SM_BAR + 80, B_RG2 = SM_BAR + 88,
                   B_XS = SM_BAR + 96, B_EMPTY = SM_BAR + 128, B_DONE = SM_BAR + 192, B_XE = SM_BAR + 200,
                   B_GUD = SM_BAR + 224, B_OE = SM_BAR + 232, B_OT = SM_BAR + 264, B_MOD = SM_BAR + 296,
                   B_GU = SM_BAR + 104, B_ALL = SM_BAR + 112, B_UP = SM_BAR + 120, B_DN = SM_BAR + 304, B_RS = SM_BAR + 312, B_INIT = SM_BAR + 320,
                   B_RE = SM_BAR + 328, B_G2 = SM_BAR + 336;

struct Params {
    CUtensorMap x, x2, w, wr, woa, wob, xg, gate, up, down;
    __nv_bfloat16* op;
    const __nv_bfloat16 *xp, *wp, *upp, *wop, *dp, *w_r, *gate_w;
    uint32_t zero;
};

constexpr int SC_O = 0;
constexpr int SC_HALO = 1280;
constexpr int SC_GU = 1440;
constexpr int SC_Y = 1504;
constexpr int SC_SIZE = 1600;
__device__ __align__(128) uint4 g_sc[NCTA * SC_SIZE];
__device__ __align__(128) uint4 g_cand[NCTA];
__device__ __align__(16) uint32_t g_gate[2048];
__device__ __align__(128) unsigned g_cnt[64];
#define TS(i) do { } while (0)
#define TS2(i) do { } while (0)
#define TSX(i) do { } while (0)

__device__ __forceinline__ uint32_t smem_u32(const void* p) { return (uint32_t)__cvta_generic_to_shared(p); }
__device__ __forceinline__ void fault() { asm volatile("st.shared.u32 [%0], %0;" ::"r"(0x100001) : "memory"); }
__device__ __forceinline__ void mbar_init(uint32_t bar, uint32_t cnt) {
    asm volatile("mbarrier.init.shared::cta.b64 [%0], %1;" ::"r"(bar), "r"(cnt) : "memory");
}
__device__ __forceinline__ void mbar_expect_tx(uint32_t bar, uint32_t bytes) {
    asm volatile("mbarrier.arrive.expect_tx.shared::cta.b64 _, [%0], %1;" ::"r"(bar), "r"(bytes) : "memory");
}
__device__ __forceinline__ void mbar_arrive(uint32_t bar) {
    asm volatile("mbarrier.arrive.shared::cta.b64 _, [%0];" ::"r"(bar) : "memory");
}
__device__ __forceinline__ bool mbar_try(uint32_t bar, uint32_t parity) {
    uint32_t ok;
    asm volatile("{\n.reg .pred p;\nmbarrier.try_wait.parity.shared::cta.b64 p, [%1], %2;\nselp.u32 %0, 1, 0, p;\n}"
                 : "=r"(ok) : "r"(bar), "r"(parity) : "memory");
    return ok;
}
__device__ __forceinline__ void mbar_wait(uint32_t bar, uint32_t parity) {
    asm volatile("{\n.reg .pred p;\nAGAIN:\nmbarrier.try_wait.parity.shared::cta.b64 p, [%0], %1;\n@!p bra AGAIN;\n}"
                 ::"r"(bar), "r"(parity) : "memory");
}
__device__ __forceinline__ void tma_2d(uint32_t dst, const CUtensorMap* m, uint32_t bar, int c0, int c1) {
    asm volatile("cp.async.bulk.tensor.2d.shared::cluster.global.mbarrier::complete_tx::bytes [%0], [%1, {%3, %4}], [%2];"
                 ::"r"(dst), "l"(m), "r"(bar), "r"(c0), "r"(c1) : "memory");
}
__device__ __forceinline__ void bulk_load(uint32_t dst, const void* src, uint32_t bytes, uint32_t bar) {
    asm volatile("cp.async.bulk.shared::cluster.global.mbarrier::complete_tx::bytes [%0], [%1], %2, [%3];"
                 ::"r"(dst), "l"(src), "r"(bytes), "r"(bar) : "memory");
}
__device__ __forceinline__ void bulk_store(void* dst, uint32_t src, uint32_t bytes) {
    asm volatile("cp.async.bulk.global.shared::cta.bulk_group [%0], [%1], %2;" ::"l"(dst), "r"(src), "r"(bytes) : "memory");
}
__device__ __forceinline__ void tma_3d(uint32_t dst, const CUtensorMap* m, uint32_t bar, int c0, int c1, int c2) {
    asm volatile("cp.async.bulk.tensor.3d.shared::cluster.global.mbarrier::complete_tx::bytes [%0], [%1, {%3, %4, %5}], [%2];"
                 ::"r"(dst), "l"(m), "r"(bar), "r"(c0), "r"(c1), "r"(c2) : "memory");
}
__device__ __forceinline__ void fence_async_smem() { asm volatile("fence.proxy.async.shared::cta;" ::: "memory"); }
__device__ __forceinline__ void wg_fence() { asm volatile("wgmma.fence.sync.aligned;" ::: "memory"); }
__device__ __forceinline__ void wg_commit() { asm volatile("wgmma.commit_group.sync.aligned;" ::: "memory"); }
template <int N> __device__ __forceinline__ void wg_wait() { asm volatile("wgmma.wait_group.sync.aligned %0;" ::"n"(N) : "memory"); }
__device__ __forceinline__ void bar_sync(int id, int n) { asm volatile("bar.cta.sync %0, %1;" ::"r"(id), "r"(n) : "memory"); }
__device__ __forceinline__ void bar_arrive(int id, int n) { asm volatile("bar.cta.arrive %0, %1;" ::"r"(id), "r"(n) : "memory"); }

__device__ constexpr uint32_t desc_lo(uint32_t addr, uint32_t lbo) { return (addr >> 4) | ((lbo >> 4) << 16); }
__device__ __forceinline__ bool elect_one() {
    uint32_t p;
    asm volatile("{\n.reg .pred p;\nelect.sync _|p, 0xffffffff;\nselp.u32 %0, 1, 0, p;\n}" : "=r"(p));
    return p;
}
__device__ __forceinline__ uint32_t ld_relaxed4(const void* p) {
    uint32_t v;
    asm volatile("ld.relaxed.gpu.global.u32 %0, [%1];" : "=r"(v) : "l"(p) : "memory");
    return v;
}
__device__ __forceinline__ void st_relaxed4(void* p, uint32_t v) {
    asm volatile("st.relaxed.gpu.global.u32 [%0], %1;" ::"l"(p), "r"(v) : "memory");
}
__device__ __forceinline__ void red_inc(unsigned* p, unsigned after) {
    asm volatile("red.relaxed.gpu.global.add.u32 [%0], 1;" ::"l"(p), "r"(after) : "memory");
}
__device__ __forceinline__ uint32_t lds4(uint32_t a) {
    uint32_t v;
    asm volatile("ld.shared.u32 %0, [%1];" : "=r"(v) : "r"(a) : "memory");
    return v;
}
__device__ __forceinline__ float2 lds8f(uint32_t a) {
    float2 v;
    asm volatile("ld.shared.v2.f32 {%0, %1}, [%2];" : "=f"(v.x), "=f"(v.y) : "r"(a) : "memory");
    return v;
}
__device__ __forceinline__ void sts4(uint32_t a, uint32_t v) { asm volatile("st.shared.u32 [%0], %1;" ::"r"(a), "r"(v) : "memory"); }
__device__ __forceinline__ uint32_t hmul2(uint32_t a, uint32_t b) {
    uint32_t d;
    asm("mul.rn.bf16x2 %0, %1, %2;" : "=r"(d) : "r"(a), "r"(b));
    return d;
}
__device__ __forceinline__ uint32_t hadd2(uint32_t a, uint32_t b) {
    uint32_t d;
    asm("add.rn.bf16x2 %0, %1, %2;" : "=r"(d) : "r"(a), "r"(b));
    return d;
}
__device__ __forceinline__ uint32_t hfma2(uint32_t a, uint32_t b, uint32_t c) {
    uint32_t d;
    asm("fma.rn.bf16x2 %0, %1, %2, %3;" : "=r"(d) : "r"(a), "r"(b), "r"(c));
    return d;
}
__device__ __forceinline__ uint4 ld_relaxed16(const void* p) {
    uint4 v;
    asm volatile("{\n.reg .b128 t;\n.reg .b64 lo, hi;\nld.relaxed.gpu.global.b128 t, [%4];\nmov.b128 {lo, hi}, t;\n"
                 "mov.b64 {%0, %1}, lo;\nmov.b64 {%2, %3}, hi;\n}" : "=r"(v.x), "=r"(v.y), "=r"(v.z), "=r"(v.w) : "l"(p) : "memory");
    return v;
}
__device__ __forceinline__ void st_relaxed16(void* p, uint32_t a, uint32_t b, uint32_t c, uint32_t d) {
    uint64_t lo = (uint64_t)a | ((uint64_t)b << 32), hi = (uint64_t)c | ((uint64_t)d << 32);
    asm volatile("{\n.reg .b128 t;\nmov.b128 t, {%1, %2};\nst.relaxed.gpu.global.b128 [%0], t;\n}" ::"l"(p), "l"(lo), "l"(hi) : "memory");
}
__device__ __forceinline__ uint4 ld_nc16(const void* p) {
    uint4 v;
    asm volatile("ld.global.nc.L1::no_allocate.v4.u32 {%0, %1, %2, %3}, [%4];" : "=r"(v.x), "=r"(v.y), "=r"(v.z), "=r"(v.w) : "l"(p));
    return v;
}
__device__ __forceinline__ uint2 ld_nc8(const void* p) {
    uint2 v;
    asm volatile("ld.global.nc.L1::no_allocate.v2.u32 {%0, %1}, [%2];" : "=r"(v.x), "=r"(v.y) : "l"(p));
    return v;
}
__device__ __forceinline__ uint4 lds16(uint32_t a) {
    uint4 v;
    asm volatile("ld.shared.v4.u32 {%0, %1, %2, %3}, [%4];" : "=r"(v.x), "=r"(v.y), "=r"(v.z), "=r"(v.w) : "r"(a) : "memory");
    return v;
}
__device__ __forceinline__ void sts16(uint32_t a, uint32_t x, uint32_t y, uint32_t z, uint32_t w) {
    asm volatile("st.shared.v4.u32 [%0], {%1, %2, %3, %4};" ::"r"(a), "r"(x), "r"(y), "r"(z), "r"(w) : "memory");
}
__device__ __forceinline__ uint32_t pack2(float lo, float hi) {
    uint32_t r;
    asm("cvt.rn.bf16x2.f32 %0, %1, %2;" : "=r"(r) : "f"(hi), "f"(lo));
    return r;
}
__device__ __forceinline__ uint32_t pack2v(float lo, float hi) {
    uint32_t r;
    asm volatile("cvt.rn.bf16x2.f32 %0, %1, %2;" : "=r"(r) : "f"(hi), "f"(lo));
    return r;
}
__device__ __forceinline__ float bf_lo(uint32_t u) { return __uint_as_float(u << 16); }
__device__ __forceinline__ float bf_hi(uint32_t u) { return __uint_as_float(u & 0xFFFF0000u); }
__device__ __forceinline__ float up_lo(uint32_t u, uint32_t z) { return __uint_as_float(__byte_perm(u, z, 0x1044)); }
__device__ __forceinline__ float up_hi(uint32_t u, uint32_t z) { return __uint_as_float(__byte_perm(u, z, 0x3244)); }
__device__ __forceinline__ float bf_round(float f) { return __bfloat162float(__float2bfloat16_rn(f)); }
__device__ __forceinline__ uint32_t movm(uint32_t a) {
    uint32_t d;
    asm volatile("movmatrix.sync.aligned.m8n8.trans.b16 %0, %1;" : "=r"(d) : "r"(a));
    return d;
}
__device__ __forceinline__ void mma16(float (&c)[4], uint32_t a0, uint32_t a1, uint32_t a2, uint32_t a3, uint32_t b0, uint32_t b1) {
    asm volatile("mma.sync.aligned.m16n8k16.row.col.f32.bf16.bf16.f32 {%0,%1,%2,%3}, {%4,%5,%6,%7}, {%8,%9}, {%0,%1,%2,%3};"
                 : "+f"(c[0]), "+f"(c[1]), "+f"(c[2]), "+f"(c[3]) : "r"(a0), "r"(a1), "r"(a2), "r"(a3), "r"(b0), "r"(b1));
}
__device__ __forceinline__ void mma8(float (&c)[4], uint32_t a0, uint32_t a1, uint32_t b0) {
    asm volatile("mma.sync.aligned.m16n8k8.row.col.f32.bf16.bf16.f32 {%0,%1,%2,%3}, {%4,%5}, {%6}, {%0,%1,%2,%3};"
                 : "+f"(c[0]), "+f"(c[1]), "+f"(c[2]), "+f"(c[3]) : "r"(a0), "r"(a1), "r"(b0));
}
__device__ __forceinline__ float ex2(float x) { float y; asm("ex2.approx.ftz.f32 %0, %1;" : "=f"(y) : "f"(x)); return y; }
__device__ __forceinline__ float rcp(float x) { float y; asm("rcp.approx.ftz.f32 %0, %1;" : "=f"(y) : "f"(x)); return y; }
__device__ __forceinline__ float sigmoidf(float z) { return rcp(1.0f + ex2(z * -1.4426950408889634f)); }
__device__ __forceinline__ float u2f(uint32_t u) { return __uint_as_float(u); }
__device__ __forceinline__ uint32_t f2u(float f) { return __float_as_uint(f); }

__device__ __forceinline__ void wgmma_main(float (&d)[96], uint32_t a, uint32_t b, int scale_d) {
    asm volatile("{\n.reg .pred p;\n.reg .b64 da, db;\nsetp.ne.b32 p, %98, 0;\n"
        "mov.b64 da, {%96, 0x40000040};\nmov.b64 db, {%97, 0x40000040};\n"
        "wgmma.mma_async.sync.aligned.m64n192k16.f32.bf16.bf16 "
        "{%0, %1, %2, %3, %4, %5, %6, %7, %8, %9, %10, %11, %12, %13, %14, %15, "
        "%16, %17, %18, %19, %20, %21, %22, %23, %24, %25, %26, %27, %28, %29, %30, %31, "
        "%32, %33, %34, %35, %36, %37, %38, %39, %40, %41, %42, %43, %44, %45, %46, %47, "
        "%48, %49, %50, %51, %52, %53, %54, %55, %56, %57, %58, %59, %60, %61, %62, %63, "
        "%64, %65, %66, %67, %68, %69, %70, %71, %72, %73, %74, %75, %76, %77, %78, %79, "
        "%80, %81, %82, %83, %84, %85, %86, %87, %88, %89, %90, %91, %92, %93, %94, %95}, "
        "da, db, p, 1, 1, 0, 1;\n}\n"
        : "+f"(d[0]), "+f"(d[1]), "+f"(d[2]), "+f"(d[3]), "+f"(d[4]), "+f"(d[5]), "+f"(d[6]), "+f"(d[7]),
          "+f"(d[8]), "+f"(d[9]), "+f"(d[10]), "+f"(d[11]), "+f"(d[12]), "+f"(d[13]), "+f"(d[14]), "+f"(d[15]),
          "+f"(d[16]), "+f"(d[17]), "+f"(d[18]), "+f"(d[19]), "+f"(d[20]), "+f"(d[21]), "+f"(d[22]), "+f"(d[23]),
          "+f"(d[24]), "+f"(d[25]), "+f"(d[26]), "+f"(d[27]), "+f"(d[28]), "+f"(d[29]), "+f"(d[30]), "+f"(d[31]),
          "+f"(d[32]), "+f"(d[33]), "+f"(d[34]), "+f"(d[35]), "+f"(d[36]), "+f"(d[37]), "+f"(d[38]), "+f"(d[39]),
          "+f"(d[40]), "+f"(d[41]), "+f"(d[42]), "+f"(d[43]), "+f"(d[44]), "+f"(d[45]), "+f"(d[46]), "+f"(d[47]),
          "+f"(d[48]), "+f"(d[49]), "+f"(d[50]), "+f"(d[51]), "+f"(d[52]), "+f"(d[53]), "+f"(d[54]), "+f"(d[55]),
          "+f"(d[56]), "+f"(d[57]), "+f"(d[58]), "+f"(d[59]), "+f"(d[60]), "+f"(d[61]), "+f"(d[62]), "+f"(d[63]),
          "+f"(d[64]), "+f"(d[65]), "+f"(d[66]), "+f"(d[67]), "+f"(d[68]), "+f"(d[69]), "+f"(d[70]), "+f"(d[71]),
          "+f"(d[72]), "+f"(d[73]), "+f"(d[74]), "+f"(d[75]), "+f"(d[76]), "+f"(d[77]), "+f"(d[78]), "+f"(d[79]),
          "+f"(d[80]), "+f"(d[81]), "+f"(d[82]), "+f"(d[83]), "+f"(d[84]), "+f"(d[85]), "+f"(d[86]), "+f"(d[87]),
          "+f"(d[88]), "+f"(d[89]), "+f"(d[90]), "+f"(d[91]), "+f"(d[92]), "+f"(d[93]), "+f"(d[94]), "+f"(d[95])
        : "r"(a), "r"(b), "r"(scale_d));
}

__device__ __forceinline__ void wgmma_rem(float (&d)[24], uint32_t a, uint32_t b, int scale_d) {
    asm volatile("{\n.reg .pred p;\n.reg .b64 da, db;\nsetp.ne.b32 p, %26, 0;\n"
        "mov.b64 da, {%24, 0x40000040};\nmov.b64 db, {%25, 0xC0000010};\n"
        "wgmma.mma_async.sync.aligned.m64n48k16.f32.bf16.bf16 "
        "{%0, %1, %2, %3, %4, %5, %6, %7, %8, %9, %10, %11, %12, %13, %14, %15, "
        "%16, %17, %18, %19, %20, %21, %22, %23}, "
        "da, db, p, 1, 1, 0, 1;\n}\n"
        : "+f"(d[0]), "+f"(d[1]), "+f"(d[2]), "+f"(d[3]), "+f"(d[4]), "+f"(d[5]), "+f"(d[6]), "+f"(d[7]),
          "+f"(d[8]), "+f"(d[9]), "+f"(d[10]), "+f"(d[11]), "+f"(d[12]), "+f"(d[13]), "+f"(d[14]), "+f"(d[15]),
          "+f"(d[16]), "+f"(d[17]), "+f"(d[18]), "+f"(d[19]), "+f"(d[20]), "+f"(d[21]), "+f"(d[22]), "+f"(d[23])
        : "r"(a), "r"(b), "r"(scale_d));
}

__device__ __forceinline__ void wgmma_out(float (&d)[80], uint32_t a, uint32_t b, int scale_d) {
    asm volatile("{\n.reg .pred p;\n.reg .b64 da, db;\nsetp.ne.b32 p, %82, 0;\n"
        "mov.b64 da, {%80, 0x50};\nmov.b64 db, {%81, 0x40000040};\n"
        "wgmma.mma_async.sync.aligned.m64n160k16.f32.bf16.bf16 "
        "{%0, %1, %2, %3, %4, %5, %6, %7, %8, %9, %10, %11, %12, %13, %14, %15, "
        "%16, %17, %18, %19, %20, %21, %22, %23, %24, %25, %26, %27, %28, %29, %30, %31, "
        "%32, %33, %34, %35, %36, %37, %38, %39, %40, %41, %42, %43, %44, %45, %46, %47, "
        "%48, %49, %50, %51, %52, %53, %54, %55, %56, %57, %58, %59, %60, %61, %62, %63, "
        "%64, %65, %66, %67, %68, %69, %70, %71, %72, %73, %74, %75, %76, %77, %78, %79}, "
        "da, db, p, 1, 1, 0, 1;\n}\n"
        : "+f"(d[0]), "+f"(d[1]), "+f"(d[2]), "+f"(d[3]), "+f"(d[4]), "+f"(d[5]), "+f"(d[6]), "+f"(d[7]),
          "+f"(d[8]), "+f"(d[9]), "+f"(d[10]), "+f"(d[11]), "+f"(d[12]), "+f"(d[13]), "+f"(d[14]), "+f"(d[15]),
          "+f"(d[16]), "+f"(d[17]), "+f"(d[18]), "+f"(d[19]), "+f"(d[20]), "+f"(d[21]), "+f"(d[22]), "+f"(d[23]),
          "+f"(d[24]), "+f"(d[25]), "+f"(d[26]), "+f"(d[27]), "+f"(d[28]), "+f"(d[29]), "+f"(d[30]), "+f"(d[31]),
          "+f"(d[32]), "+f"(d[33]), "+f"(d[34]), "+f"(d[35]), "+f"(d[36]), "+f"(d[37]), "+f"(d[38]), "+f"(d[39]),
          "+f"(d[40]), "+f"(d[41]), "+f"(d[42]), "+f"(d[43]), "+f"(d[44]), "+f"(d[45]), "+f"(d[46]), "+f"(d[47]),
          "+f"(d[48]), "+f"(d[49]), "+f"(d[50]), "+f"(d[51]), "+f"(d[52]), "+f"(d[53]), "+f"(d[54]), "+f"(d[55]),
          "+f"(d[56]), "+f"(d[57]), "+f"(d[58]), "+f"(d[59]), "+f"(d[60]), "+f"(d[61]), "+f"(d[62]), "+f"(d[63]),
          "+f"(d[64]), "+f"(d[65]), "+f"(d[66]), "+f"(d[67]), "+f"(d[68]), "+f"(d[69]), "+f"(d[70]), "+f"(d[71]),
          "+f"(d[72]), "+f"(d[73]), "+f"(d[74]), "+f"(d[75]), "+f"(d[76]), "+f"(d[77]), "+f"(d[78]), "+f"(d[79])
        : "r"(a), "r"(b), "r"(scale_d));
}

__device__ __forceinline__ void wgmma_own(float (&d)[80], uint32_t a0, uint32_t a1, uint32_t a2, uint32_t a3, uint32_t b, int scale_d) {
    asm volatile("{\n.reg .pred p;\n.reg .b64 db;\nsetp.ne.b32 p, %85, 0;\nmov.b64 db, {%84, 0x40000040};\n"
        "wgmma.mma_async.sync.aligned.m64n160k16.f32.bf16.bf16 "
        "{%0, %1, %2, %3, %4, %5, %6, %7, %8, %9, %10, %11, %12, %13, %14, %15, "
        "%16, %17, %18, %19, %20, %21, %22, %23, %24, %25, %26, %27, %28, %29, %30, %31, "
        "%32, %33, %34, %35, %36, %37, %38, %39, %40, %41, %42, %43, %44, %45, %46, %47, "
        "%48, %49, %50, %51, %52, %53, %54, %55, %56, %57, %58, %59, %60, %61, %62, %63, "
        "%64, %65, %66, %67, %68, %69, %70, %71, %72, %73, %74, %75, %76, %77, %78, %79}, "
        "{%80, %81, %82, %83}, db, p, 1, 1, 1;\n}\n"
        : "+f"(d[0]), "+f"(d[1]), "+f"(d[2]), "+f"(d[3]), "+f"(d[4]), "+f"(d[5]), "+f"(d[6]), "+f"(d[7]),
          "+f"(d[8]), "+f"(d[9]), "+f"(d[10]), "+f"(d[11]), "+f"(d[12]), "+f"(d[13]), "+f"(d[14]), "+f"(d[15]),
          "+f"(d[16]), "+f"(d[17]), "+f"(d[18]), "+f"(d[19]), "+f"(d[20]), "+f"(d[21]), "+f"(d[22]), "+f"(d[23]),
          "+f"(d[24]), "+f"(d[25]), "+f"(d[26]), "+f"(d[27]), "+f"(d[28]), "+f"(d[29]), "+f"(d[30]), "+f"(d[31]),
          "+f"(d[32]), "+f"(d[33]), "+f"(d[34]), "+f"(d[35]), "+f"(d[36]), "+f"(d[37]), "+f"(d[38]), "+f"(d[39]),
          "+f"(d[40]), "+f"(d[41]), "+f"(d[42]), "+f"(d[43]), "+f"(d[44]), "+f"(d[45]), "+f"(d[46]), "+f"(d[47]),
          "+f"(d[48]), "+f"(d[49]), "+f"(d[50]), "+f"(d[51]), "+f"(d[52]), "+f"(d[53]), "+f"(d[54]), "+f"(d[55]),
          "+f"(d[56]), "+f"(d[57]), "+f"(d[58]), "+f"(d[59]), "+f"(d[60]), "+f"(d[61]), "+f"(d[62]), "+f"(d[63]),
          "+f"(d[64]), "+f"(d[65]), "+f"(d[66]), "+f"(d[67]), "+f"(d[68]), "+f"(d[69]), "+f"(d[70]), "+f"(d[71]),
          "+f"(d[72]), "+f"(d[73]), "+f"(d[74]), "+f"(d[75]), "+f"(d[76]), "+f"(d[77]), "+f"(d[78]), "+f"(d[79])
        : "r"(a0), "r"(a1), "r"(a2), "r"(a3), "r"(b), "r"(scale_d));
}

#define TSA(i) do { } while (0)
#define MAP_TILE(b) (((b) & 3) | (((b) >> 5) << 2))
#define MAP_HG(b) ((((b) >> 2) & 7) ^ (((b) & 32) ? 6 : 0))
#define SKEW 4
#define PACE 500
#define PACE_W0 (-600)
#define PACE_A 250
#define PACE_B 450
#define RG_T0 3800
#define RG_DT 500
#define RG_ORDER 0x24130
#define GU_N 8
#define GU_T0 3600
#define GU_DT 300
#define RS_T0 10000
#define RS_DT 200
#define EXCH_FIRST 1
#define HALO_D 300
#define PF_UP 4200
#define O_D 0
#define O_DT 300
#define PF_DN 4200
#define PF_DT 450
#define GX_NS 200
#define NRS 2
#define C5_D 600
#define C6_D 100
#define GU_LATE 1
#define RF_T 2500
#define RW_T 1400
#define RG_CH 3
#define PF_N 10
#define PF_0 4
#define EPF_N 15
#define EPF_M 15
#define EPF_T 900
#define PF_ST 0
#define GU_ST 0
#define RG_V 1
#define RG1_T0 1700
#define RG1_DT 200
#define RW1_T 0
#define CAND_T 9000

__device__ __forceinline__ uint32_t keep(uint32_t v) { return __shfl_sync(0xffffffffu, v, threadIdx.x); }
__device__ __forceinline__ uint32_t ukeep(uint32_t v) { return __shfl_sync(0xffffffffu, v, 0); }
__device__ __forceinline__ void ldsm2(uint32_t* d, uint32_t a) {
    asm volatile("ldmatrix.sync.aligned.m8n8.x4.shared.b16 {%0,%1,%2,%3}, [%8];\nldmatrix.sync.aligned.m8n8.x4.shared.b16 {%4,%5,%6,%7}, [%9];"
                 : "=r"(d[0]), "=r"(d[1]), "=r"(d[2]), "=r"(d[3]), "=r"(d[4]), "=r"(d[5]), "=r"(d[6]), "=r"(d[7])
                 : "r"(a), "r"(a ^ 32) : "memory");
}
template <bool SWP, int SEG, int E>
__device__ __forceinline__ void pack_blocks(uint32_t (&d)[10], const float (&am)[96], const float (&ar)[24]) {
#pragma unroll
    for (int t = 0; t < 10; t++) {
        const float* p = (SWP ? t < 2 : t >= 8) ? ar + (SEG * 2 + (t & 1)) * 4 + E : am + (SEG * 8 + t - (SWP ? 2 : 0)) * 4 + E;
        d[t] = pack2v(p[0], p[1]);
    }
}
__device__ __forceinline__ int src_of(int i, int hg) { return i == 0 ? hg : i - (i <= hg); }

__device__ constexpr uint32_t o_buf(int i) { return ((0x99ADA3D1u >> ((i - NRS) & 3) * 8) & 255) << 10; }
__device__ constexpr uint32_t wo_buf(int i) { return SM_W + ((0x10342103u >> i * 4) & 7) * 30720; }

template <int N>
__device__ __forceinline__ void poll(uint4 (&a)[N], const uint4* p, int stride) {
    bool bad;
    do {
        bad = false;
#pragma unroll
        for (int s = 0; s < N; s++) a[s] = ld_relaxed16(p + s * stride);
#pragma unroll
        for (int s = 0; s < N; s++) bad |= a[s].w == SENT;
    } while (__any_sync(0xffffffffu, bad));
}
__device__ __forceinline__ void pace(unsigned t0, int t) {
    asm volatile("{\n.reg .pred p;\n.reg .s32 d;\nAGAIN:\nmov.u32 d, %%clock;\nsub.s32 d, d, %0;\nsetp.lt.s32 p, d, 0;\n"
                 "@p nanosleep.u32 20;\n@p bra AGAIN;\n}" ::"r"(t0 + t) : "memory");
}
__device__ __forceinline__ void l2_prefetch(const void* p) { asm volatile("prefetch.global.L2 [%0];" ::"l"(p) : "memory"); }

template <int ROW>
__device__ __forceinline__ void wgmma_vec(float (&d)[8], uint32_t a, uint32_t b, int scale_d) {
    asm volatile("{\n.reg .pred p;\n.reg .b64 da, db;\nsetp.ne.b32 p, %10, 0;\nmov.b64 da, {%8, 0x40000040};\nmov.b64 db, {%9, %11};\n"
                 "wgmma.mma_async.sync.aligned.m64n16k16.f32.bf16.bf16 {%0, %1, %2, %3, %4, %5, %6, %7}, da, db, p, 1, 1, 1, 0;\n}"
                 : "+f"(d[0]), "+f"(d[1]), "+f"(d[2]), "+f"(d[3]), "+f"(d[4]), "+f"(d[5]), "+f"(d[6]), "+f"(d[7])
                 : "r"(a), "r"(b), "r"(scale_d), "n"(ROW / 16));
}

__global__ void __launch_bounds__(512, 1) fused_kernel(const __grid_constant__ Params P) {
    extern __shared__ __align__(1024) uint8_t smem_raw[];
    const unsigned t_start = clock();
    const int tid = threadIdx.x, lane = tid & 31;
    const int warp = __shfl_sync(0xffffffffu, tid >> 5, 0);
    const int tile = MAP_TILE(blockIdx.x), hg = MAP_HG(blockIdx.x);
    const int cid = tile * 8 + hg;
    const int par = tile & 1, p0 = (tile >> 1) * 128;
    uint4* const sc = g_sc + cid * SC_SIZE;
    const bool swp = (hg & 3) == 3;
    const int wcm = hg * 80 + (swp ? 16 : 0), wcr = hg * 80 + (swp ? 0 : 64);
    if (EPF_N && warp == 15 && lane < EPF_N) l2_prefetch(P.wp + (lane * 128 + blockIdx.x) * 64);
    if (warp < 7 && elect_one()) {
#pragma unroll
        for (int i = 0; i < 4; i++) mbar_init(SM_BAR + warp * 32 + i * 8, warp < 4 ? 1 : warp < 6 ? 2 : 4);
        asm volatile("fence.mbarrier_init.release.cluster;" ::: "memory");
        if (warp == 0) {
            mbar_expect_tx(B_FULL, 15360 + 8192);
            tma_3d(SM_X + 8192, &P.x, B_FULL, 0, par, p0 + 64);
            tma_3d(SM_W, &P.w, B_FULL, wcm, 0, 0);
            tma_3d(SM_W + 12288, &P.wr, B_FULL, wcr, 0, 0);
            TS(40);
            mbar_expect_tx(B_XL0, 8192);
            tma_3d(SM_X, &P.x, B_XL0, 0, par, p0);
        }
    }
    __syncthreads();

    if (warp >= 12) {
        asm volatile("setmaxnreg.dec.sync.aligned.u32 32;");
        if (warp == 12) {
            if (elect_one()) {
#pragma unroll 1
                for (int s = 1; s < 20; s++) {
                    const uint32_t fb = B_FULL + (s & 7) * 8, dst = SM_W + (s & 7) * 15360;
                    mbar_wait(fb + (B_EMPTY - B_FULL), ~(s >> 3) & 1);
                    pace(t_start, max(PACE_A + s * PACE_B, PACE_W0 + s * PACE));
                    mbar_expect_tx(fb, (s & 1) ? 15360 : 15360 + 16384);
                    tma_3d(dst, &P.w, fb, wcm, s * 32, 0);
                    tma_3d(dst + 12288, &P.wr, fb, wcr, s * 32, 0);
                    TS2(20 + s);
                    if (s == 1) TS(41);
                }
                mbar_wait(B_RG2, 0);
                if (cid < NFFN) {
                    mbar_wait(B_EMPTY + 5 * 8, 1);
                    mbar_expect_tx(B_UP, 20480);
                    TS(46);
                    tma_2d(SM_UP, &P.up, B_UP, (cid >> 2) * 64, (cid & 3) * 160);
                }
                const int cb = hg >> 1, ca = (cb * 5 + 1) >> 1, cr = cb * 160 + ((cb & 1) ? 0 : 128);
#pragma unroll 1
                for (int j = 0; j < 8; j++) {
                    const int i = j ^ (j == 3 || j == 4 ? 7 : 0);
                    if (j != 3) mbar_wait(j < 3 ? B_EMPTY + ((2 * j + 7) & 7) * 8 : B_GUD + (j - 4) * 8, j == 0);
                    if (j >= 5) pace(clock(), j == 5 ? C5_D : C6_D);
                    const uint32_t dst = wo_buf(i), gb = B_G2 + i * 8;
                    mbar_expect_tx(gb, 25600);
                    tma_3d(dst, &P.woa, gb, 0, src_of(i, hg) * 80, ca);
                    tma_2d(dst + 20480, &P.wob, gb, cr, src_of(i, hg) * 80);
                }
            }
        } else if (warp == 14) {
            if (elect_one()) {
#pragma unroll 1
                for (int kb = 1; kb < 10; kb++) {
                    const uint32_t fb = B_FULL + (kb & 3) * 16, dst = SM_X + (kb & 3) * 16384;
                    mbar_wait(fb + (B_EMPTY - B_FULL + 8), ~(kb >> 2) & 1);
                    if (kb >= 4) mbar_wait(B_XE + (kb - 4 >> 1) * 8, 0);
                    pace(t_start, max(PACE_A - PACE_B / 2 + 2 * kb * PACE_B, PACE_W0 - 50 + (2 * kb + 1) * PACE));
                    tma_3d(dst, &P.x2, fb, kb * 64, par, p0);
                }
            }
            __syncwarp();
            mbar_wait(B_ALL, 0);
            bar_sync(12, 64);
            pace(clock(), HALO_D);
            uint4 hv[5];
            poll<5>(hv, sc + (SC_HALO - (tile < 2 ? 0 : 16 * SC_SIZE) + lane), 32);
#pragma unroll
            for (int s = 0; s < 5; s++) sts16(SM_HALO + s * 512 + lane * 16, hv[s].x, hv[s].y, hv[s].z, hv[s].w);
            bar_arrive(8, 64);
            TS(25);
        } else if (warp == 15) {
            if (EPF_M) {
                pace(t_start, EPF_T);
                if (lane < EPF_M) l2_prefetch(P.wp + ((lane + EPF_N) * 128 + blockIdx.x) * 64);
            }
#pragma unroll 1
            for (int i = PF_0; i < PF_N; i++) {
                pace(t_start, (i < 6 ? PF_UP : PF_DN) + i * PF_DT + (cid * 5 & 15) * PF_ST);
                const int ln = (i * 128 + cid) * 32 + lane;
                l2_prefetch((ln < 17280 ? P.upp : ln < 23680 ? P.wop - 17280 * 64 : P.dp - 23680 * 64) + ln * 64);
            }
            int it = smem_u32(smem_raw) == SB ? 0 : 1 << 20;
            while (!mbar_try(B_DONE, 0) || !mbar_try(B_MOD, 0))
                if (++it > (1 << 20)) fault();
        } else {
#pragma unroll 1
            for (int i = 0; i < 10; i++) sts16(SM_SENT + i * 512 + lane * 16, SENT, SENT, SENT, SENT);
            fence_async_smem();
            __syncwarp();
            if (elect_one()) {
                mbar_expect_tx(B_RG, 2560);
                mbar_expect_tx(B_GU, 20480);
                asm volatile("mbarrier.expect_tx.relaxed.cta.shared::cta.b64 [%0], 10240;" ::"r"(B_RG2) : "memory");
                pace(t_start, RW1_T);
                bulk_load(SM_RED, P.w_r, 1280, B_RG);
                bulk_load(SM_RED + 1280, P.gate_w, 1280, B_RG);
#pragma unroll 1
                for (int i = 0; i < 5; i++) {
                    pace(t_start, RG1_T0 + i * RG1_DT);
                    tma_3d(SM_HALO + i * 2048, &P.xg, B_RG2, 320 + i * 64, par, p0 + hg * 16);
                }
#pragma unroll
                for (int i = 0; i < 22; i++) mbar_init(B_GUD + i * 8, i < 15 + NRS ? 1 : 2);
                bulk_store(sc + SC_HALO, SM_SENT, 5120);
                asm volatile("cp.async.bulk.commit_group;\ncp.async.bulk.wait_group 0;" ::: "memory");
                mbar_arrive(B_RG2);
                TS(43);
                const unsigned goal = (ld_relaxed4(g_cnt + 32) | (NCTA - 1)) + 1;
#pragma unroll 1
                for (int i = 0; i < (cid < NFFN ? GU_N : 0); i++) {
                    pace(t_start, GU_T0 + i * GU_DT + (cid * 5 & 15) * GU_ST);
                    tma_2d(SM_F + i * (20480 / GU_N), &P.gate, B_GU, (cid >> 2) * 64, (cid & 3) * 160 + i * (160 / GU_N));
                }
#pragma unroll 1
                for (int i = 0; i < 4; i++) {
                    pace(t_start, RS_T0 + i * RS_DT);
                    bulk_store(sc + i * 320, SM_SENT, 5120);
                }
                asm volatile("cp.async.bulk.commit_group;\ncp.async.bulk.wait_group 0;" ::: "memory");
                red_inc(g_cnt + 32, goal);
                mbar_arrive(B_RS);
                TS(44);
                while (ld_relaxed4(g_cnt + 32) - goal > 0x80000000u) {}
                mbar_arrive(B_INIT);
                TS(45);
            }
        }
    } else if (warp >= 8) {
        asm volatile("setmaxnreg.dec.sync.aligned.u32 96;");
        const int t = tid - 256;
        unsigned epoch = ld_relaxed4(g_cnt);
        float gv = 0.f;
        int grow = hg * 16 + (t >> 3);
        mbar_wait(B_RG, 0);
        TS(warp == 8 ? 48 : 63);
        {
            float r0 = 0.f, r1 = 0.f, g0 = 0.f, g1 = 0.f;
            const uint32_t sw = (t >> 4) * 128 + (((t ^ (t >> 4)) & 7) << 4), hi = (t >> 3) & 1;
            mbar_wait(B_XL0, 0);
#pragma unroll 1
            for (int i = 0; i < 5; i++) {
                const int p = (RG_ORDER >> (i * 4)) & 7, kb = 2 * p + hi;
                mbar_wait(p < 3 ? B_FULL + (p & 1) * 32 : B_RG2, p == 2);
                if (p < 2) mbar_wait(B_FULL + p * 32 + 16, 0);
                const uint32_t xa = sw + (kb < 5 ? SM_X + (kb & 3) * 16384 + hg * 2048 : SM_HALO - 5 * 2048 + kb * 2048);
                const uint4 a = lds16(xa), b = lds16(xa + 1024);
                const uint4 w = lds16(SM_RED + p * 256 + (t & 15) * 16), v = lds16(SM_RED + 1280 + p * 256 + (t & 15) * 16);
                if (__ballot_sync(0xffffffffu, lane == 0 || a.w == b.w) && lane == 0 && p < 3) mbar_arrive(B_XE + p * 8);
                const uint32_t as[4] = {a.x, a.y, a.z, a.w}, bs[4] = {b.x, b.y, b.z, b.w};
                const uint32_t ws[4] = {w.x, w.y, w.z, w.w}, vs[4] = {v.x, v.y, v.z, v.w};
#pragma unroll
                for (int e = 0; e < 4; e++) {
                    r0 = fmaf(bf_lo(as[e]), bf_lo(ws[e]), r0);
                    r1 = fmaf(bf_lo(bs[e]), bf_lo(ws[e]), r1);
                    g0 = fmaf(bf_lo(as[e]), bf_lo(vs[e]), g0);
                    g1 = fmaf(bf_lo(bs[e]), bf_lo(vs[e]), g1);
                    r0 = fmaf(bf_hi(as[e]), bf_hi(ws[e]), r0);
                    r1 = fmaf(bf_hi(bs[e]), bf_hi(ws[e]), r1);
                    g0 = fmaf(bf_hi(as[e]), bf_hi(vs[e]), g0);
                    g1 = fmaf(bf_hi(bs[e]), bf_hi(vs[e]), g1);
                }
            }
            const bool up = lane & 4;
            r0 = (hi ? r1 : r0) + __shfl_xor_sync(0xffffffffu, hi ? r0 : r1, 8);
            g0 = (hi ? g1 : g0) + __shfl_xor_sync(0xffffffffu, hi ? g0 : g1, 8);
            float r = (up ? g0 : r0) + __shfl_xor_sync(0xffffffffu, up ? r0 : g0, 4);
            r += __shfl_xor_sync(0xffffffffu, r, 2);
            r = bf_round(r + __shfl_xor_sync(0xffffffffu, r, 1));
            const int row = hg * 16 + (t >> 4) + hi * 8;
            const uint32_t u = f2u(r);
            if (!up) sts4(SM_KEY + (t >> 3) * 4, (((int)u < 0 ? ~u : u | 0x80000000u) & 0xFFFF0000u) | (2047 - (p0 + row) * 2 - par));
            gv = r;
            grow = row;
        }
        TS(warp == 8 ? 61 : 63);
        mbar_wait(B_RG2, 0);
        bar_sync(4, 128);
        asm volatile("bfe.u32 %0, %0, 7, 25;\nadd.u32 %0, %0, 1;" : "+r"(epoch));
        if (warp == 8) {
            const uint32_t key = lds4(SM_KEY + (lane & 15) * 4);
            uint32_t k1 = __reduce_max_sync(0xffffffffu, key);
            uint32_t k2 = __reduce_max_sync(0xffffffffu, key == k1 ? 0u : key);
            if (elect_one()) {
                st_relaxed16(g_cand + cid, k1, k2, epoch, epoch);
                red_inc(g_cnt, epoch);
            }
            TS(49);
        }
        if ((lane & 7) == 4) st_relaxed4(g_gate + tile * 128 + grow, f2u(bf_round(sigmoidf(gv))) | (epoch & 0xFFFFu));
        pace(t_start, CAND_T);
        if (warp == 9) {
            uint4 v;
            do {
                asm volatile("ld.relaxed.gpu.global.v4.u32 {%0, %1, %2, %3}, [%4];"
                             : "=r"(v.x), "=r"(v.y), "=r"(v.z), "=r"(v.w) : "l"(g_gate + tile * 128 + lane * 4) : "memory");
            } while (__any_sync(0xffffffffu, ((v.x ^ epoch) | (v.y ^ epoch) | (v.z ^ epoch) | (v.w ^ epoch)) & 0xFFFFu));
            sts16(SM_GATE + lane * 16, v.x, v.y, v.z, v.w);
            __syncwarp();
            if (lane == 0) mbar_arrive(B_GT);
            TS(47);
        }
        if (warp == 8) {
            uint4 cd[4];
            do {
#pragma unroll
                for (int j = 0; j < 4; j++) cd[j] = ld_relaxed16(g_cand + lane + 32 * j);
            } while (!__all_sync(0xffffffffu, cd[0].z == epoch && cd[1].z == epoch && cd[2].z == epoch && cd[3].z == epoch));
            uint32_t l1 = 0, l2 = 0;
#pragma unroll
            for (int j = 0; j < 4; j++) {
                l2 = max(max(l2, cd[j].y), min(l1, cd[j].x));
                l1 = max(l1, cd[j].x);
            }
            const uint32_t k1 = __reduce_max_sync(0xffffffffu, l1);
            const uint32_t k2 = __reduce_max_sync(0xffffffffu, l1 == k1 ? l2 : l1);
            if (elect_one()) {
                bulk_load(SM_XS, P.xp + (~k1 & 2047) * 640 + (cid & 3) * 160, 320, B_XS);
                bulk_load(SM_XS + 320, P.xp + (~k2 & 2047) * 640 + (cid & 3) * 160, 320, B_XS);
                sts16(SM_KEY + 16 * 4, k1, k2, 0, 0);
                mbar_expect_tx(B_XS, 640);
                mbar_arrive(B_ALL);
                TS(56);
            }
        }
        mbar_wait(B_XS, 0);
        TS(warp == 8 ? 50 : 63);
        const int cq = lane & 3, q = cid & 3;
        if (cid < NFFN) {
            float ga[8], ua[8];
            mbar_wait(B_GU, 0);
            mbar_wait(B_UP, 0);
            bar_sync(13, 256);
            TS(warp == 8 ? 53 : 63);
            wg_fence();
#pragma unroll
            for (int i = 0; i < 10; i++) {
                wgmma_vec<320>(ga, desc_lo(SM_F, 16) + i * 128, desc_lo(SM_XS, 16) + i * 2, i);
                wgmma_vec<320>(ua, desc_lo(SM_UP, 16) + i * 128, desc_lo(SM_XS, 16) + i * 2, i);
            }
            wg_commit();
            wg_wait<0>();
            TS(warp == 8 ? 54 : 63);
            if (cq == 0) {
                st_relaxed16(sc + SC_GU + (t >> 2), f2u(ga[0]), f2u(ga[2]), f2u(ga[4]), f2u(ga[6]));
                st_relaxed16(sc + SC_GU + 32 + (t >> 2), f2u(ua[0]), f2u(ua[2]), f2u(ua[4]), f2u(ua[6]));
            }
            if (warp == 9 && elect_one()) {
                mbar_arrive(B_GUD);
                mbar_expect_tx(B_DN, 24576);
                tma_3d(SM_F, &P.down, B_DN, 0, (cid >> 2) * 64, q * 3 - (q == 3));
            }
            uint4 pq[2];
            __nanosleep(GX_NS);
            poll<2>(pq, sc + (cq - q) * SC_SIZE + SC_GU + (t >> 2), 32);
            TS(warp == 8 ? 55 : 63);
            const bool tk = cq & 2, c8 = cq & 1;
            float v[4];
#pragma unroll
            for (int m = 0; m < 2; m++) {
                v[2 * m] = u2f(tk ? pq[m].z : pq[m].x) + __shfl_xor_sync(0xffffffffu, u2f(tk ? pq[m].x : pq[m].z), 2);
                v[2 * m + 1] = u2f(tk ? pq[m].w : pq[m].y) + __shfl_xor_sync(0xffffffffu, u2f(tk ? pq[m].y : pq[m].w), 2);
                v[m] = bf_round((c8 ? v[2 * m + 1] : v[2 * m]) + __shfl_xor_sync(0xffffffffu, c8 ? v[2 * m] : v[2 * m + 1], 1));
            }
            const uint32_t h = pack2(bf_round(v[0] * sigmoidf(v[0])) * v[1], 0.f);
            asm volatile("st.shared.u16 [%0], %1;" ::"r"(SM_XS + (cq >> 1) * 128 + ((t >> 5) * 16 + (cq & 1) * 8 + (lane >> 2)) * 2),
                         "h"((uint16_t)h) : "memory");
            fence_async_smem();
            bar_sync(4, 128);
            TS(warp == 8 ? 57 : 63);
            mbar_wait(B_DN, 0);
            TS(warp == 8 ? 59 : 63);
            float y[3][8];
#pragma unroll 1
            for (int i = 0; i < 4; i++) {
                wg_fence();
#pragma unroll
                for (int m = 0; m < 3; m++) wgmma_vec<128>(y[m], desc_lo(SM_F + m * 8192, 16) + i * 128, desc_lo(SM_XS, 16) + i * 2, i);
                wg_commit();
            }
            wg_wait<0>();
            if (cq == 0) {
#pragma unroll
                for (int m = 0; m < 6; m++)
                    asm volatile("st.relaxed.gpu.global.v2.f32 [%0], {%1, %2};"
                                 ::"l"(reinterpret_cast<float2*>(sc + SC_Y) + (m & 1) * 96 + (m >> 1) * 32 + (t >> 2)),
                                   "f"(y[m >> 1][(m & 1) * 4]), "f"(y[m >> 1][(m & 1) * 4 + 2]) : "memory");
            }
        } else if (t == 0) {
            mbar_arrive(B_GUD);
        }
        TS(warp == 8 ? 51 : 63);
        const uint32_t k1 = lds4(SM_KEY + 16 * 4), k2 = lds4(SM_KEY + 17 * 4);
        const uint32_t mine = (tile >> 1) * 256 + (hg & 1) * 128 + par;
        const bool own1 = (~k1 & 0x781) == mine, own2 = (~k2 & 0x781) == mine;
        if ((own1 || own2) && NFFN) {
            const int rg = min(t / 40, 2), c40 = t % 40, un = (hg >> 1) * 40 + c40, src = un < 48 ? 0 : un < 96 ? 1 : un < 128 ? 2 : 3;
            TS(warp == 8 ? 60 : 63);
#pragma unroll 1
            for (int j = !own1; j <= own2; j++) {
                const uint4* p = g_sc + (rg * 4 + src) * SC_SIZE + SC_Y + j * 48 + un - (src * 3 - (src == 3)) * 16;
                float y[4];
                bool bad;
                do {
                    uint4 yp[9];
#pragma unroll
                    for (int i = 0; i < 9; i++) yp[i] = ld_relaxed16(p + i * 12 * SC_SIZE);
                    y[0] = y[1] = y[2] = y[3] = 0.f;
                    bad = false;
#pragma unroll
                    for (int i = 0; i < 9; i++) {
                        y[0] += u2f(yp[i].x); y[1] += u2f(yp[i].y); y[2] += u2f(yp[i].z); y[3] += u2f(yp[i].w);
                        bad |= max(max(yp[i].x, yp[i].y), max(yp[i].z, yp[i].w)) == SENT;
                    }
                } while (__any_sync(0xffffffffu, bad));
                TS(warp == 8 ? 62 : 63);
                sts16(SM_F + j * 2048 + t * 16, f2u(y[0]), f2u(y[1]), f2u(y[2]), f2u(y[3]));
                bar_sync(4, 128);
                if (t < 80) {
                    const uint32_t key = j ? k2 : k1, ya = SM_F + j * 2048 + (t >> 1) * 16 + (t & 1) * 4;
                    const float rs = bf_round(sigmoidf(u2f(((int)key < 0 ? key & 0x7FFFFFFFu : ~key) & 0xFFFF0000u)));
                    const float y0 = u2f(lds4(ya)) + u2f(lds4(ya + 640)) + u2f(lds4(ya + 1280));
                    const float y1 = u2f(lds4(ya + 8)) + u2f(lds4(ya + 648)) + u2f(lds4(ya + 1288));
                    sts4(SM_U + j * 320 + (t >> 3) * 32 + (t & 1) * 16 + (t & 6) * 2, pack2(bf_round(y0) * rs, bf_round(y1) * rs));
                }
            }
            bar_sync(4, 128);
        }
        if (t == 0) mbar_arrive(B_MOD);
        TS(warp == 8 ? 52 : 63);
    } else {
        asm volatile("setmaxnreg.inc.sync.aligned.u32 192;");
        const int wg = warp >> 2;
        const bool leader = (tid & 127) == 0;
        float am[96], ar[24];
        if (wg == 0) mbar_wait(B_XL0, 0);
        bool rel = false;
        uint32_t nb[40];
        const int odd = (hg >> 1) & 1, kba = ukeep(((hg >> 1) * 5 + 1) >> 1), kbr = ukeep(kba + 2 - odd * 3);
        const int kbs = wg ? -1 : (20 - SKEW) / 2;
        const uint32_t xrow = keep(SM_X + (warp * 16 + (lane & 15)) * 128 + (((lane >> 4) ^ (lane & 7)) << 4));
#pragma unroll 1
        for (int kb = 0; kb < 10; kb++) {
            const uint32_t fb = B_FULL + (kb & 3) * 16, wo = (kb & 3) * 1920, ph = (kb >> 2) & 1;
            const uint32_t xo = desc_lo(SM_X, 16) + wg * 512 + (kb & 3) * 1024;
#pragma unroll
            for (int h = 0; h < 2; h++) {
                mbar_wait(fb + h * 8, ph);
                if (kb == 0 && h == 0) TS(warp == 0 ? 0 : warp == 4 ? 16 : 63);
                TS2(warp == 4 ? kb * 2 + h : 63);
                if (h == 0) {
                    const uint32_t xa = xrow + (kb & 3) * 16384;
                    if (kb == kba) { ldsm2(nb, xa); ldsm2(nb + 8, xa ^ 64); }
                    if (kb == kba + 1) { ldsm2(nb + 16, xa); ldsm2(nb + 24, xa ^ 64); }
                    if (kb == kbr) ldsm2(nb + 32, xa ^ (odd * 64));
                }
                wg_wait<1>();
                if (rel) mbar_arrive(B_EMPTY + ((kb * 16 - 16) & 48) + h * 8);
                if (h == (SKEW & 1) && kb == kbs) bar_sync(5, 256);
                wg_fence();
                wgmma_main(am, xo + h * 4, desc_lo(SM_W + h * 15360, 4096) + wo, h || kb);
                wgmma_rem(ar, xo + h * 4, desc_lo(SM_W + h * 15360 + 12288, 1024) + wo, h || kb);
                wgmma_main(am, xo + h * 4 + 2, desc_lo(SM_W + h * 15360 + 2048, 4096) + wo, 1);
                wgmma_rem(ar, xo + h * 4 + 2, desc_lo(SM_W + h * 15360 + 12288 + 512, 1024) + wo, 1);
                wg_commit();
            }
            rel = leader;
        }
        if (wg == 1) bar_arrive(5, 256);
        else if (cid < NFFN) bar_arrive(13, 256);
        mbar_wait(B_XE + 16, 0);
        mbar_wait(B_RG2, 0);
        mbar_wait(B_EMPTY + 5 * 8, 1);
        wg_wait<0>();
        if (leader) mbar_arrive(B_EMPTY + 3 * 8);
        TS(warp == 0 ? 2 : warp == 4 ? 18 : 63);
        TS2(warp == 0 ? 41 : warp == 4 ? 40 : 63);

        uint32_t kl[10], kh[10], vl[10], vh[10], ql[10], qh[10], kp[10], vp[10];
        if (swp) {
            pack_blocks<true, 1, 2>(kh, am, ar);
            pack_blocks<true, 2, 2>(vh, am, ar);
        } else {
            pack_blocks<false, 1, 2>(kh, am, ar);
            pack_blocks<false, 2, 2>(vh, am, ar);
        }
        const int w4 = warp & 3;
        const uint32_t pbuf = (wg ? SM_HALO1 : SM_HALO) + w4 * 2560 + lane * 16;
        const uint32_t hbuf = warp == 3 ? SM_HALO1 + lane * 16 : pbuf + 2560;
        {
            const uint32_t ex[20] = {kh[0], kh[1], kh[3], kh[4], kh[5], kh[6], kh[8], kh[9], kh[2], kh[7],
                                     vh[0], vh[1], vh[2], vh[3], vh[4], vh[5], vh[6], vh[7], vh[8], vh[9]};
            if (warp == 7) {
                uint4* const hp = sc + SC_HALO + lane;
#pragma unroll
                for (int s = 0; s < 5; s++) st_relaxed16(hp + s * 32, ex[4 * s], ex[4 * s + 1], ex[4 * s + 2], ex[4 * s + 3]);
                bar_arrive(12, 64);
            } else {
#pragma unroll
                for (int s = 0; s < 5; s++) sts16(hbuf + s * 512, ex[4 * s], ex[4 * s + 1], ex[4 * s + 2], ex[4 * s + 3]);
            }
        }
        TSA(warp == 7 ? 22 : warp == 3 ? 23 : 63);
        if (warp == 3) bar_arrive(11, 64);
        if (swp) {
            pack_blocks<true, 2, 0>(vl, am, ar);
            pack_blocks<true, 0, 0>(ql, am, ar);
            pack_blocks<true, 0, 2>(qh, am, ar);
            pack_blocks<true, 1, 0>(kl, am, ar);
        } else {
            pack_blocks<false, 2, 0>(vl, am, ar);
            pack_blocks<false, 0, 0>(ql, am, ar);
            pack_blocks<false, 0, 2>(qh, am, ar);
            pack_blocks<false, 1, 0>(kl, am, ar);
        }
#pragma unroll
        for (int t = 0; t < 10; t++) { vl[t] = movm(vl[t]); vh[t] = movm(vh[t]); }
        mbar_wait(B_RS, 0);
        mbar_wait(B_GT, 0);
        const float g0 = bf_hi(lds4(SM_GATE + warp * 64 + (lane & 28))), g1 = bf_hi(lds4(SM_GATE + 32 + warp * 64 + (lane & 28)));

        const int r = lane >> 2, cq = lane & 3;
        const bool no_prev = warp == 0 && tile < 2, low = cq < 2;
        const bool le0 = 2 * cq <= r, le1 = 2 * cq + 1 <= r;
        const uint32_t mle = (le0 ? 0xFFFFu : 0u) | (le1 ? 0xFFFF0000u : 0u);
        const float scl = 0.22360679774997896f * 1.4426950408889634f;
        uint32_t pl[4], ph[4];
        {
            float sl[4][4], sh[4][4], sp[4][4];
            auto exchange = [&]() {
            TSA(warp == 1 ? 26 : 63);
            bar_sync(6 + wg, 128);
            if (w4 == 0) bar_sync(8 + wg * 3, 64);
            {
                const uint4 a = lds16(pbuf), b = lds16(pbuf + 512), c = lds16(pbuf + 1024), d = lds16(pbuf + 1536), e = lds16(pbuf + 2048);
                kp[0] = a.x; kp[1] = a.y; kp[3] = a.z; kp[4] = a.w; kp[5] = b.x; kp[6] = b.y; kp[8] = b.z; kp[9] = b.w;
                kp[2] = c.x; kp[7] = c.y; vp[0] = c.z; vp[1] = c.w; vp[2] = d.x; vp[3] = d.y; vp[4] = d.z; vp[5] = d.w;
                vp[6] = e.x; vp[7] = e.y; vp[8] = e.z; vp[9] = e.w;
            }
            TSA(warp == 0 ? 3 : warp == 4 ? 19 : warp == 5 ? 27 : 63);
            };
            if (EXCH_FIRST) exchange();
#pragma unroll
            for (int h = 0; h < 4; h++) {
                const int ta = (h >> 1) * 5 + (h & 1) * 3, tc = (h >> 1) * 5 + 2;
                const uint32_t ml = low != (h & 1) ? ql[tc] : 0u, mh = low != (h & 1) ? qh[tc] : 0u;
#pragma unroll
                for (int e = 0; e < 4; e++) sl[h][e] = sh[h][e] = sp[h][e] = 0.f;
                mma16(sl[h], ql[ta], qh[ta], ql[ta + 1], qh[ta + 1], kl[ta], kl[ta + 1]);
                mma16(sh[h], ql[ta], qh[ta], ql[ta + 1], qh[ta + 1], kh[ta], kh[ta + 1]);
                mma8(sl[h], ml, mh, kl[tc]);
                mma8(sh[h], ml, mh, kh[tc]);
            }
            if (!EXCH_FIRST) exchange();
#pragma unroll
            for (int h = 0; h < 4; h++) {
                const int ta = (h >> 1) * 5 + (h & 1) * 3, tc = (h >> 1) * 5 + 2;
                mma16(sp[h], ql[ta], qh[ta], ql[ta + 1], qh[ta + 1], kp[ta], kp[ta + 1]);
                mma8(sp[h], low != (h & 1) ? ql[tc] : 0u, low != (h & 1) ? qh[tc] : 0u, kp[tc]);
            }
#pragma unroll
            for (int t = 0; t < 10; t++) vp[t] = movm(vp[t]);
#pragma unroll
            for (int h = 0; h < 4; h++) {
                if (no_prev) sp[h][0] = sp[h][1] = -1e9f / 0.22360679774997896f;
                const float a0 = le0 ? sl[h][0] : sp[h][0], a1 = le1 ? sl[h][1] : sp[h][1];
                const float b0 = le0 ? sh[h][2] : sl[h][2], b1 = le1 ? sh[h][3] : sl[h][3];
                float ma = fmaxf(a0, a1), mb = fmaxf(b0, b1);
                ma = fmaxf(ma, __shfl_xor_sync(0xffffffffu, ma, 1));
                mb = fmaxf(mb, __shfl_xor_sync(0xffffffffu, mb, 1));
                ma = fmaxf(ma, __shfl_xor_sync(0xffffffffu, ma, 2)) * -scl;
                mb = fmaxf(mb, __shfl_xor_sync(0xffffffffu, mb, 2)) * -scl;
                pl[h] = pack2(ex2(fmaf(a0, scl, ma)), ex2(fmaf(a1, scl, ma)));
                ph[h] = pack2(ex2(fmaf(b0, scl, mb)), ex2(fmaf(b1, scl, mb)));
            }
        }
        TSA(warp == 0 ? 4 : warp == 4 ? 20 : warp == 5 ? 28 : 63);
        uint32_t ol[10], oh[10];
        {
            uint32_t* const po = reinterpret_cast<uint32_t*>(sc + SC_O + warp * 160) + lane;
            const uint32_t ONES = 0x3F803F80u;
            float o[12][4];
#pragma unroll
            for (int hp = 0; hp < 2; hp++) {
#pragma unroll
                for (int h = hp * 2; h < hp * 2 + 2; h++) {
                    const int ta = (h >> 1) * 5 + (h & 1) * 3, tc = (h >> 1) * 5 + 2;
                    const bool mine = (lane < 16) != (h & 1);
                    const uint32_t a0 = pl[h] & mle, a1 = ph[h] & ~mle, a3 = ph[h] & mle, ap = pl[h] & ~mle;
#pragma unroll
                    for (int i = 0; i < 3; i++) o[h * 3 + i][0] = o[h * 3 + i][1] = o[h * 3 + i][2] = o[h * 3 + i][3] = 0.f;
                    mma16(o[h * 3 + 2], a0, a1, 0u, a3, mine ? vl[tc] : ONES, mine ? vh[tc] : ONES);
                    mma16(o[h * 3], a0, a1, 0u, a3, vl[ta], vh[ta]);
                    mma16(o[h * 3 + 1], a0, a1, 0u, a3, vl[ta + 1], vh[ta + 1]);
                    mma8(o[h * 3 + 2], ap, 0u, mine ? vp[tc] : ONES);
                    mma8(o[h * 3], ap, 0u, vp[ta]);
                    mma8(o[h * 3 + 1], ap, 0u, vp[ta + 1]);
                }
                if (hp && wg != (hg & 1)) bar_arrive(2, 256);
                const float (&oa)[4] = o[hp * 6 + 2], (&ob)[4] = o[hp * 6 + 5];
                const float hl = rcp(low ? ob[0] : oa[0]) * g0, hh = rcp(low ? ob[2] : oa[2]) * g1;
                const float gl = __shfl_xor_sync(0xffffffffu, hl, 2), gh = __shfl_xor_sync(0xffffffffu, hh, 2);
                const float ial = low ? gl : hl, iah = low ? gh : hh, ibl = low ? hl : gl, ibh = low ? hh : gh;
#pragma unroll
                for (int i = 0; i < 2; i++) {
                    ol[hp * 5 + i] = pack2(o[hp * 6 + i][0] * ial, o[hp * 6 + i][1] * ial);
                    oh[hp * 5 + i] = pack2(o[hp * 6 + i][2] * iah, o[hp * 6 + i][3] * iah);
                    ol[hp * 5 + 3 + i] = pack2(o[hp * 6 + 3 + i][0] * ibl, o[hp * 6 + 3 + i][1] * ibl);
                    oh[hp * 5 + 3 + i] = pack2(o[hp * 6 + 3 + i][2] * ibh, o[hp * 6 + 3 + i][3] * ibh);
                }
                ol[hp * 5 + 2] = pack2((low ? oa[0] : ob[0]) * gl, (low ? oa[1] : ob[1]) * gl);
                oh[hp * 5 + 2] = pack2((low ? oa[2] : ob[2]) * gh, (low ? oa[3] : ob[3]) * gh);
#pragma unroll
                for (int t = hp * 5; t < hp * 5 + 5; t++) {
                    st_relaxed4(po + t * 32, ol[t]);
                    st_relaxed4(po + 320 + t * 32, oh[t]);
                }
            }
        }
        TS(warp == 0 ? 5 : warp == 4 ? 21 : warp == 5 ? 29 : warp == 1 ? 31 : 63);
        const uint4* ow = sc + (SC_O + (hg & 1) * 640 - hg * SC_SIZE);
        if (wg != (hg & 1)) {
            mbar_wait(B_INIT, 0);
            mbar_wait(B_EMPTY + 3 * 8, 0);
            if (w4 < 2) bar_arrive(9, 256); else bar_sync(9, 256);
            if (w4 == 0) TS(wg ? 26 : 27);
            uint32_t ph = 0;
#pragma unroll 1
            for (int i = w4 + 1 + NRS; i < 8; i += 4) {
                const uint4* src = ow + src_of(i, hg) * SC_SIZE;
                const uint32_t buf = o_buf(i), chk = buf + lane * 132;
                if (i < 5 + NRS) {
                    while (__any_sync(0xffffffffu, ld_relaxed4(&src[(lane & 3) * 160 + 159].w) == SENT)) {}
                    if (w4) pace(clock(), w4 * O_DT - O_D);
                } else {
                    mbar_wait(B_OE + (i - 4) * 8, 0);
                }
                if (i == 1 + NRS) TS(wg ? 3 : 4);
                uint32_t c;
                do {
                    if (elect_one()) {
                        mbar_expect_tx(B_OT + w4 * 8, 10240);
                        bulk_load(buf, src, 10240, B_OT + w4 * 8);
                    }
                    mbar_wait(B_OT + w4 * 8, ph);
                    if (i == 1 + NRS && !ph) TS(wg ? 19 : 20);
                    ph ^= 1;
                    c = max(max(lds4(chk), lds4(chk + 4096)), lds4(chk + 6144));
                } while (__any_sync(0xffffffffu, c == SENT));
                if (lane == 0) mbar_arrive(B_G2 + i * 8);
                TS(32 + i);
            }
            return;
        }

        float oc[80];
        bar_arrive(9, 256);
        bar_sync(2, 256);
        mbar_wait(B_G2, 0);
        TS(w4 == 0 ? 6 : 63);
        wg_fence();
#pragma unroll
        for (int s = 0; s < 5; s++)
            wgmma_own(oc, ol[2 * s], oh[2 * s], ol[2 * s + 1], oh[2 * s + 1], desc_lo(wo_buf(0), 10240) + s * 128, s);
        wg_commit();
        mbar_wait(B_XS, 0);
        const int orow = p0 + wg * 64 + w4 * 16;
        const uint32_t tk1 = ~lds4(SM_KEY + 16 * 4) & 2047, tk2 = ~lds4(SM_KEY + 17 * 4) & 2047;
        const uint32_t sel1 = (tk1 & 1) == par ? (tk1 >> 1) - orow : 99, sel2 = (tk2 & 1) == par ? (tk2 >> 1) - orow : 99;
        const uint32_t n0 = pack2(1.f - g0, 1.f - g0), n1 = pack2(1.f - g1, 1.f - g1);
        const uint32_t stg = SM_OUT + w4 * 5120;
        const uint32_t m128 = keep(stg + (lane & 15) * 128 + (((lane >> 4) ^ (lane & 7)) << 4));
        const uint32_t m64 = keep(stg + 4096 + (lane & 15) * 64 + (((lane >> 4) ^ ((lane >> 1) & 3)) << 4));
        const uint32_t l128 = keep(stg + (lane >> 3) * 128 + (((lane & 7) ^ (lane >> 3)) << 4));
        const uint32_t l64 = keep(stg + 4096 + r * 64 + ((cq ^ (lane >> 3)) << 4));
        char* const o128 = reinterpret_cast<char*>(P.op) + keep(((orow + (lane >> 3)) * 2 + par) * 1280 + kba * 128 + (lane & 7) * 16);
        char* const o64 = reinterpret_cast<char*>(P.op) + keep(((orow + r) * 2 + par) * 1280 + kbr * 128 + odd * 64 + cq * 16);
        mbar_wait(B_INIT, 0);
        wg_wait<0>();
        if (leader) mbar_arrive(B_OE);
        {
            uint32_t af[NRS][20];
            uint32_t m;
            do {
#pragma unroll
                for (int i = 0; i < NRS; i++) {
                    const uint32_t* p = reinterpret_cast<const uint32_t*>(ow + src_of(i + 1, hg) * SC_SIZE + w4 * 160) + lane;
#pragma unroll
                    for (int t = 0; t < 20; t++) af[i][t] = ld_relaxed4(p + t * 32);
                }
                m = 0;
#pragma unroll
                for (int i = 0; i < NRS; i++)
#pragma unroll
                    for (int t = 0; t < 20; t++) m = max(m, af[i][t]);
            } while (__any_sync(0xffffffffu, m == SENT));
#pragma unroll
            for (int i = 0; i < NRS; i++) {
                mbar_wait(B_G2 + 8 + i * 8, 0);
                TS(w4 == 0 ? (i ? 11 : 7) : 63);
                wg_fence();
#pragma unroll
                for (int s = 0; s < 5; s++)
                    wgmma_own(oc, af[i][2 * s], af[i][10 + 2 * s], af[i][2 * s + 1], af[i][11 + 2 * s], desc_lo(wo_buf(i + 1), 10240) + s * 128, 1);
                wg_commit();
            }
            if (NRS == 2) {
                wg_wait<1>();
                if (leader) mbar_arrive(B_OE + 8);
            }
        }
#pragma unroll 1
        for (int i = 1 + NRS; i < 8; i++) {
            const uint32_t ao = desc_lo(0, 128) + (o_buf(i) >> 4), wo = desc_lo(0, 10240) + (wo_buf(i) >> 4);
            mbar_wait(B_G2 + i * 8, 0);
            TS(w4 == 0 ? (i < 2 ? 6 + i : i < 7 ? 9 + i : 17) : 63);
            wg_fence();
#pragma unroll
            for (int s = 0; s < 5; s++) wgmma_out(oc, ao + s * 16, wo + s * 128, 1);
            wg_commit();
            if (i < 5) {
                wg_wait<1>();
                if (i > 1 && leader) mbar_arrive(B_OE - 8 + i * 8);
            }
        }
        TS(w4 == 0 ? 8 : 63);

        if (min(sel1, sel2) < 16) {
            mbar_wait(B_MOD, 0);
#pragma unroll 1
            for (int j = 0; j < 2; j++) {
                const uint32_t sel = j ? sel2 : sel1;
#pragma unroll
                for (int t = 0; t < 20; t++) {
                    const uint32_t u = lds4(SM_U + j * 320 + cq * 4 + (t < 16 ? odd * 64 + t * 16 : (odd ? 0 : 256) + (t - 16) * 16));
                    if (sel == r) nb[2 * t] = hadd2(nb[2 * t], u);
                    if (sel == r + 8) nb[2 * t + 1] = hadd2(nb[2 * t + 1], u);
                }
            }
        }
        wg_wait<0>();
        TS(w4 == 0 ? 9 : 63);
        const bool nan = oc[0] != oc[0] || oc[2] != oc[2];
#pragma unroll
        for (int part = 0; part < 3; part++) {
            const int s0 = part ? part * 4 - 4 : 8, ns = part ? 4 : 2;
#pragma unroll
            for (int i = 0; i < 4; i++) {
                if (i >= ns) break;
                const int s = s0 + i;
                const uint32_t y0 = hfma2(n0, nb[s * 4], pack2(oc[s * 8 + 0], oc[s * 8 + 1]));
                const uint32_t y1 = hfma2(n1, nb[s * 4 + 1], pack2(oc[s * 8 + 2], oc[s * 8 + 3]));
                const uint32_t y2 = hfma2(n0, nb[s * 4 + 2], pack2(oc[s * 8 + 4], oc[s * 8 + 5]));
                const uint32_t y3 = hfma2(n1, nb[s * 4 + 3], pack2(oc[s * 8 + 6], oc[s * 8 + 7]));
                asm volatile("stmatrix.sync.aligned.m8n8.x4.shared.b16 [%0], {%1,%2,%3,%4};"
                             ::"r"(((s < 8 ? m128 : m64) ^ ((s & 3) * 32)) + (s & 4) * 512), "r"(y0), "r"(y1), "r"(y2), "r"(y3) : "memory");
            }
            __syncwarp();
            uint4 v[4];
#pragma unroll
            for (int i = 0; i < 4; i++)
                if (i < ns) v[i] = lds16(!part ? l64 + i * 512 : (l128 ^ ((i & 1) * 64)) + i * 512 + s0 * 512);
#pragma unroll
            for (int i = 0; i < 4; i++)
                if (i < ns) *reinterpret_cast<uint4*>(!part ? o64 + i * 8 * 2560 : o128 + i * 4 * 2560 + s0 * 32) = v[i];
            if (part == 0) TS(w4 == 0 ? 1 : 63);
        }
        TS(w4 == 0 ? 10 : 63);
        if (lane == 0) mbar_arrive(B_DONE);
        uint32_t redo;
        asm volatile("{\n.reg .pred p, q;\nsetp.ne.u32 p, %1, 0;\nbar.cta.red.or.pred q, 10, 128, p;\nselp.u32 %0, 1, 0, q;\n}"
                     : "=r"(redo) : "r"((uint32_t)nan) : "memory");
        if (redo) {
            const int cb = hg >> 1;
#pragma unroll 1
            for (int i = 0; i < 8; i++) {
                if (leader) {
                    mbar_expect_tx(B_RE, 25600);
                    tma_3d(SM_W, &P.woa, B_RE, 0, i * 80, (cb * 5 + 1) >> 1);
                    tma_2d(SM_W + 20480, &P.wob, B_RE, cb * 160 + ((cb & 1) ? 0 : 128), i * 80);
                }
#pragma unroll 1
                for (int s = 0; s < 20; s++) {
                    const int w = w4 * 640 + s * 32 + lane;
                    uint32_t v, it = 0;
                    do {
                        v = ld_relaxed4(reinterpret_cast<const uint32_t*>(ow + i * SC_SIZE) + w);
                        if (++it > (1u << 22)) fault();
                    } while ((v >> 16) == 0xFFFFu || (v & 0xFFFFu) == 0xFFFFu);
                    sts4(SM_X + w * 4, v);
                }
                fence_async_smem();
                __syncwarp();
                bar_sync(10, 128);
                mbar_wait(B_RE, i & 1);
                wg_fence();
#pragma unroll
                for (int s = 0; s < 5; s++) wgmma_out(oc, desc_lo(SM_X, 128) + s * 16, desc_lo(SM_W, 10240) + s * 128, s || i);
                wg_commit();
                wg_wait<0>();
                bar_sync(10, 128);
            }
#pragma unroll
            for (int t = 0; t < 40; t++) {
                const int col = (t < 32 ? kba * 64 + (t >> 1) * 8 : kbr * 64 + odd * 32 + ((t - 32) >> 1) * 8) + cq * 2;
                *reinterpret_cast<uint32_t*>(P.op + ((orow + r + (t & 1) * 8) * 2 + par) * 640 + col) =
                    hfma2((t & 1) ? n1 : n0, nb[t], pack2(oc[2 * t], oc[2 * t + 1]));
            }
        }
    }
}

typedef CUresult (*EncodeFn)(CUtensorMap*, CUtensorMapDataType, cuuint32_t, void*, const cuuint64_t*, const cuuint64_t*,
                             const cuuint32_t*, const cuuint32_t*, CUtensorMapInterleave, CUtensorMapSwizzle,
                             CUtensorMapL2promotion, CUtensorMapFloatOOBfill);

void encode(EncodeFn fn, CUtensorMap* m, const void* ptr, int rank, const cuuint64_t* dims, const cuuint64_t* strides,
            const cuuint32_t* box, CUtensorMapSwizzle swz) {
    const cuuint32_t es[4] = {1, 1, 1, 1};
    fn(m, CU_TENSOR_MAP_DATA_TYPE_BFLOAT16, rank, const_cast<void*>(ptr), dims, strides, box, es,
       CU_TENSOR_MAP_INTERLEAVE_NONE, swz, CU_TENSOR_MAP_L2_PROMOTION_L2_128B, CU_TENSOR_MAP_FLOAT_OOB_FILL_NONE);
}

}

extern "C" void kernel_launch(void* const* d_in, const int* in_sizes, int n_in, void* d_out, int out_size) {
    (void)in_sizes; (void)n_in; (void)out_size;
    Params P;
    P.xp = (const __nv_bfloat16*)d_in[0];
    P.wp = (const __nv_bfloat16*)d_in[1];
    P.wop = (const __nv_bfloat16*)d_in[2];
    P.dp = (const __nv_bfloat16*)d_in[7];
    P.upp = (const __nv_bfloat16*)d_in[6];
    P.op = (__nv_bfloat16*)d_out;
    P.w_r = (const __nv_bfloat16*)d_in[4];
    P.gate_w = (const __nv_bfloat16*)d_in[8];
    P.zero = 0;

    void* fp = nullptr;
    cudaDriverEntryPointQueryResult st;
    cudaGetDriverEntryPoint("cuTensorMapEncodeTiled", &fp, cudaEnableDefault, &st);
    EncodeFn fn = (EncodeFn)fp;
    const cuuint64_t xd[3] = {640, 2, 1024}, xs[2] = {1280, 2560};
    const cuuint32_t bx[3] = {64, 1, 64}, bx2[3] = {64, 1, 128};
    encode(fn, &P.x2, d_in[0], 3, xd, xs, bx2, CU_TENSOR_MAP_SWIZZLE_128B);
    encode(fn, &P.x, d_in[0], 3, xd, xs, bx, CU_TENSOR_MAP_SWIZZLE_128B);
    const cuuint64_t wd[3] = {640, 640, 3}, ws[2] = {3840, 1280};
    const cuuint32_t bw[3] = {64, 32, 3}, bwr[3] = {16, 32, 3};
    encode(fn, &P.w, d_in[1], 3, wd, ws, bw, CU_TENSOR_MAP_SWIZZLE_128B);
    encode(fn, &P.wr, d_in[1], 3, wd, ws, bwr, CU_TENSOR_MAP_SWIZZLE_32B);
    const cuuint64_t ad[3] = {64, 640, 10}, as[2] = {1280, 128}, bd[2] = {640, 640};
    const cuuint32_t ba[3] = {64, 80, 2}, bb[2] = {32, 80};
    encode(fn, &P.woa, d_in[2], 3, ad, as, ba, CU_TENSOR_MAP_SWIZZLE_128B);
    encode(fn, &P.wob, d_in[2], 2, bd, as, bb, CU_TENSOR_MAP_SWIZZLE_128B);
    const cuuint64_t gd[2] = {1728, 640}, gs[1] = {3456}, dd[3] = {64, 1728, 10};
    const cuuint32_t bg[2] = {64, 160 / GU_N}, bu[2] = {64, 160}, bdn[3] = {64, 64, 3}, bxg[3] = {64, 1, 16};
    encode(fn, &P.xg, d_in[0], 3, xd, xs, bxg, CU_TENSOR_MAP_SWIZZLE_128B);
    encode(fn, &P.gate, d_in[5], 2, gd, gs, bg, CU_TENSOR_MAP_SWIZZLE_128B);
    encode(fn, &P.up, d_in[6], 2, gd, gs, bu, CU_TENSOR_MAP_SWIZZLE_128B);
    encode(fn, &P.down, d_in[7], 3, dd, as, bdn, CU_TENSOR_MAP_SWIZZLE_128B);

    cudaFuncSetAttribute(fused_kernel, cudaFuncAttributeMaxDynamicSharedMemorySize, SM_TOTAL);
    fused_kernel<<<NCTA, 512, SM_TOTAL, cudaStreamPerThread>>>(P);
}
```

```cpp
#include <cuda_runtime.h>
#include <cuda_bf16.h>
#include <cuda.h>
#include <stdint.h>

namespace {

constexpr int NCTA = 128, NEXTRA = 4;
constexpr int NFFN = 108;
constexpr uint32_t SENT = 0xFFFFFFFFu;

constexpr uint32_t SB = 1024;
constexpr uint32_t SM_W = SB;
constexpr uint32_t SM_X = SB + 122880;
constexpr uint32_t SM_F = SB + 192512;
constexpr uint32_t SM_HALO = SB + 212992;
constexpr uint32_t SM_BAR = SB + 223232;
constexpr uint32_t SM_PROF = SB + 223744;
constexpr uint32_t SM_KEY = SB + 224000;
constexpr uint32_t SM_RED = SB + 224128;
constexpr uint32_t SM_XS = SB + 226688;
constexpr uint32_t SM_SENT = SB + 227328;
constexpr uint32_t SM_U = SM_RED + 1920;
constexpr uint32_t SM_H = SM_RED + 1536;
constexpr uint32_t SM_GATE = SM_RED;
constexpr uint32_t SM_TOTAL = 232448;
constexpr uint32_t SM_HALO1 = SM_X + 32768;
constexpr uint32_t SM_UP = SM_W + 61440;
constexpr uint32_t SM_OUT = SM_W + 61440;

constexpr uint32_t B_XL0 = SM_BAR, B_FULL = SM_BAR + 8, B_GT = SM_BAR + 72, B_RG = SM_BAR + 80, B_RG2 = SM_BAR + 88,
                   B_XS = SM_BAR + 96, B_EMPTY = SM_BAR + 128, B_DONE = SM_BAR + 192, B_XE = SM_BAR + 200,
                   B_GUD = SM_BAR + 224, B_OE = SM_BAR + 232, B_OT = SM_BAR + 264, B_MOD = SM_BAR + 296,
                   B_GU = SM_BAR + 104, B_UP = SM_BAR + 112, B_RS = SM_BAR + 312, B_INIT = SM_BAR + 320,
                   B_RE = SM_BAR + 328, B_G2 = SM_BAR + 336, B_DF = SM_BAR + 400;

struct Params {
    CUtensorMap x, x2, w, wr, woa, wob, xg, gate, up, down;
    __nv_bfloat16* op;
    const __nv_bfloat16 *xp, *wp, *dp, *upp, *wop, *w_r, *gate_w;
};

constexpr int SC_O = 0;
constexpr int SC_HALO = 1280;
constexpr int SC_GU = 1440;
constexpr int SC_Y = 1504;
constexpr int SC_SIZE = 1600;
__device__ __align__(128) uint4 g_sc[NCTA * SC_SIZE];
__device__ __align__(128) uint2 g_cand[NCTA];
__device__ __align__(16) uint32_t g_gate[2048];
__device__ __align__(128) unsigned g_cnt[64];
#define TS(i) do { } while (0)
#define TS2(i) do { } while (0)
#define TSX(i) do { } while (0)

__device__ __forceinline__ uint32_t smem_u32(const void* p) { return (uint32_t)__cvta_generic_to_shared(p); }
__device__ __forceinline__ void fault() { asm volatile("st.shared.u32 [%0], %0;" ::"r"(0x100001) : "memory"); }
__device__ __forceinline__ void mbar_init(uint32_t bar, uint32_t cnt) {
    asm volatile("mbarrier.init.shared::cta.b64 [%0], %1;" ::"r"(bar), "r"(cnt) : "memory");
}
__device__ __forceinline__ void mbar_expect_tx(uint32_t bar, uint32_t bytes) {
    asm volatile("mbarrier.arrive.expect_tx.shared::cta.b64 _, [%0], %1;" ::"r"(bar), "r"(bytes) : "memory");
}
__device__ __forceinline__ void mbar_arrive(uint32_t bar) {
    asm volatile("mbarrier.arrive.shared::cta.b64 _, [%0];" ::"r"(bar) : "memory");
}
__device__ __forceinline__ bool mbar_try(uint32_t bar, uint32_t parity) {
    uint32_t ok;
    asm volatile("{\n.reg .pred p;\nmbarrier.try_wait.parity.shared::cta.b64 p, [%1], %2;\nselp.u32 %0, 1, 0, p;\n}"
                 : "=r"(ok) : "r"(bar), "r"(parity) : "memory");
    return ok;
}
__device__ __forceinline__ void mbar_wait(uint32_t bar, uint32_t parity) {
    asm volatile("{\n.reg .pred p;\nAGAIN:\nmbarrier.try_wait.parity.shared::cta.b64 p, [%0], %1;\n@!p bra AGAIN;\n}"
                 ::"r"(bar), "r"(parity) : "memory");
}
__device__ __forceinline__ void tma_2d(uint32_t dst, const CUtensorMap* m, uint32_t bar, int c0, int c1) {
    asm volatile("cp.async.bulk.tensor.2d.shared::cluster.global.mbarrier::complete_tx::bytes [%0], [%1, {%3, %4}], [%2];"
                 ::"r"(dst), "l"(m), "r"(bar), "r"(c0), "r"(c1) : "memory");
}
__device__ __forceinline__ void bulk_load(uint32_t dst, const void* src, uint32_t bytes, uint32_t bar) {
    asm volatile("cp.async.bulk.shared::cluster.global.mbarrier::complete_tx::bytes [%0], [%1], %2, [%3];"
                 ::"r"(dst), "l"(src), "r"(bytes), "r"(bar) : "memory");
}
__device__ __forceinline__ void bulk_store(void* dst, uint32_t src, uint32_t bytes) {
    asm volatile("cp.async.bulk.global.shared::cta.bulk_group [%0], [%1], %2;" ::"l"(dst), "r"(src), "r"(bytes) : "memory");
}
__device__ __forceinline__ void tma_3d(uint32_t dst, const CUtensorMap* m, uint32_t bar, int c0, int c1, int c2) {
    asm volatile("cp.async.bulk.tensor.3d.shared::cluster.global.mbarrier::complete_tx::bytes [%0], [%1, {%3, %4, %5}], [%2];"
                 ::"r"(dst), "l"(m), "r"(bar), "r"(c0), "r"(c1), "r"(c2) : "memory");
}
__device__ __forceinline__ void fence_async_smem() { asm volatile("fence.proxy.async.shared::cta;" ::: "memory"); }
__device__ __forceinline__ void wg_fence() { asm volatile("wgmma.fence.sync.aligned;" ::: "memory"); }
__device__ __forceinline__ void wg_commit() { asm volatile("wgmma.commit_group.sync.aligned;" ::: "memory"); }
template <int N> __device__ __forceinline__ void wg_wait() { asm volatile("wgmma.wait_group.sync.aligned %0;" ::"n"(N) : "memory"); }
__device__ __forceinline__ void bar_sync(int id, int n) { asm volatile("bar.cta.sync %0, %1;" ::"r"(id), "r"(n) : "memory"); }
__device__ __forceinline__ void bar_arrive(int id, int n) { asm volatile("bar.cta.arrive %0, %1;" ::"r"(id), "r"(n) : "memory"); }

__device__ constexpr uint32_t desc_lo(uint32_t addr, uint32_t lbo) { return (addr >> 4) | ((lbo >> 4) << 16); }
__device__ __forceinline__ bool elect_one() {
    uint32_t p;
    asm volatile("{\n.reg .pred p;\nelect.sync _|p, 0xffffffff;\nselp.u32 %0, 1, 0, p;\n}" : "=r"(p));
    return p;
}
__device__ __forceinline__ uint32_t ld_relaxed4(const void* p) {
    uint32_t v;
    asm volatile("ld.relaxed.gpu.global.u32 %0, [%1];" : "=r"(v) : "l"(p) : "memory");
    return v;
}
__device__ __forceinline__ void st_relaxed4(void* p, uint32_t v) {
    asm volatile("st.relaxed.gpu.global.u32 [%0], %1;" ::"l"(p), "r"(v) : "memory");
}
template <int N = 1>
__device__ __forceinline__ void red_inc(unsigned* p, unsigned after) {
    asm volatile("red.relaxed.gpu.global.add.u32 [%0], %2;" ::"l"(p), "r"(after), "n"(N) : "memory");
}
__device__ __forceinline__ uint32_t lds4(uint32_t a) {
    uint32_t v;
    asm volatile("ld.shared.u32 %0, [%1];" : "=r"(v) : "r"(a) : "memory");
    return v;
}
__device__ __forceinline__ float2 lds8f(uint32_t a) {
    float2 v;
    asm volatile("ld.shared.v2.f32 {%0, %1}, [%2];" : "=f"(v.x), "=f"(v.y) : "r"(a) : "memory");
    return v;
}
__device__ __forceinline__ void sts4(uint32_t a, uint32_t v) { asm volatile("st.shared.u32 [%0], %1;" ::"r"(a), "r"(v) : "memory"); }
__device__ __forceinline__ uint32_t hmul2(uint32_t a, uint32_t b) {
    uint32_t d;
    asm("mul.rn.bf16x2 %0, %1, %2;" : "=r"(d) : "r"(a), "r"(b));
    return d;
}
__device__ __forceinline__ uint32_t hadd2(uint32_t a, uint32_t b) {
    uint32_t d;
    asm("add.rn.bf16x2 %0, %1, %2;" : "=r"(d) : "r"(a), "r"(b));
    return d;
}
__device__ __forceinline__ uint32_t hfma2(uint32_t a, uint32_t b, uint32_t c) {
    uint32_t d;
    asm("fma.rn.bf16x2 %0, %1, %2, %3;" : "=r"(d) : "r"(a), "r"(b), "r"(c));
    return d;
}
__device__ __forceinline__ uint4 ld_relaxed16(const void* p) {
    uint4 v;
    asm volatile("{\n.reg .b128 t;\n.reg .b64 lo, hi;\nld.relaxed.gpu.global.b128 t, [%4];\nmov.b128 {lo, hi}, t;\n"
                 "mov.b64 {%0, %1}, lo;\nmov.b64 {%2, %3}, hi;\n}" : "=r"(v.x), "=r"(v.y), "=r"(v.z), "=r"(v.w) : "l"(p) : "memory");
    return v;
}
__device__ __forceinline__ void st_relaxed16(void* p, uint32_t a, uint32_t b, uint32_t c, uint32_t d) {
    uint64_t lo = (uint64_t)a | ((uint64_t)b << 32), hi = (uint64_t)c | ((uint64_t)d << 32);
    asm volatile("{\n.reg .b128 t;\nmov.b128 t, {%1, %2};\nst.relaxed.gpu.global.b128 [%0], t;\n}" ::"l"(p), "l"(lo), "l"(hi) : "memory");
}
__device__ __forceinline__ void st_relaxed8(void* p, uint32_t a, uint32_t b) {
    asm volatile("{\n.reg .b64 t;\nmov.b64 t, {%1, %2};\nst.relaxed.gpu.global.b64 [%0], t;\n}" ::"l"(p), "r"(a), "r"(b) : "memory");
}
__device__ __forceinline__ uint4 ld_nc16(const void* p) {
    uint4 v;
    asm volatile("ld.global.L1::no_allocate.v4.u32 {%0, %1, %2, %3}, [%4];" : "=r"(v.x), "=r"(v.y), "=r"(v.z), "=r"(v.w) : "l"(p) : "memory");
    return v;
}
__device__ __forceinline__ uint2 ld_nc8(const void* p) {
    uint2 v;
    asm volatile("ld.global.nc.L1::no_allocate.v2.u32 {%0, %1}, [%2];" : "=r"(v.x), "=r"(v.y) : "l"(p));
    return v;
}
__device__ __forceinline__ uint4 lds16(uint32_t a) {
    uint4 v;
    asm volatile("ld.shared.v4.u32 {%0, %1, %2, %3}, [%4];" : "=r"(v.x), "=r"(v.y), "=r"(v.z), "=r"(v.w) : "r"(a) : "memory");
    return v;
}
__device__ __forceinline__ void sts16(uint32_t a, uint32_t x, uint32_t y, uint32_t z, uint32_t w) {
    asm volatile("st.shared.v4.u32 [%0], {%1, %2, %3, %4};" ::"r"(a), "r"(x), "r"(y), "r"(z), "r"(w) : "memory");
}
__device__ __forceinline__ uint32_t pack2(float lo, float hi) {
    uint32_t r;
    asm("cvt.rn.bf16x2.f32 %0, %1, %2;" : "=r"(r) : "f"(hi), "f"(lo));
    return r;
}
__device__ __forceinline__ uint32_t pack2v(float lo, float hi) {
    uint32_t r;
    asm volatile("cvt.rn.bf16x2.f32 %0, %1, %2;" : "=r"(r) : "f"(hi), "f"(lo));
    return r;
}
__device__ __forceinline__ float bf_lo(uint32_t u) { return __uint_as_float(u << 16); }
__device__ __forceinline__ float bf_hi(uint32_t u) { return __uint_as_float(u & 0xFFFF0000u); }
__device__ __forceinline__ float bf_round(float f) { return __bfloat162float(__float2bfloat16_rn(f)); }
__device__ __forceinline__ uint32_t prmt(uint32_t a, uint32_t sel) {
    uint32_t d;
    asm("prmt.b32 %0, %1, 0, %2;" : "=r"(d) : "r"(a), "r"(sel));
    return d;
}
__device__ __forceinline__ uint32_t movm(uint32_t a) {
    uint32_t d;
    asm volatile("movmatrix.sync.aligned.m8n8.trans.b16 %0, %1;" : "=r"(d) : "r"(a));
    return d;
}
__device__ __forceinline__ void mma16(float (&c)[4], uint32_t a0, uint32_t a1, uint32_t a2, uint32_t a3, uint32_t b0, uint32_t b1) {
    asm volatile("mma.sync.aligned.m16n8k16.row.col.f32.bf16.bf16.f32 {%0,%1,%2,%3}, {%4,%5,%6,%7}, {%8,%9}, {%0,%1,%2,%3};"
                 : "+f"(c[0]), "+f"(c[1]), "+f"(c[2]), "+f"(c[3]) : "r"(a0), "r"(a1), "r"(a2), "r"(a3), "r"(b0), "r"(b1));
}
__device__ __forceinline__ void mma8(float (&c)[4], uint32_t a0, uint32_t a1, uint32_t b0) {
    asm volatile("mma.sync.aligned.m16n8k8.row.col.f32.bf16.bf16.f32 {%0,%1,%2,%3}, {%4,%5}, {%6}, {%0,%1,%2,%3};"
                 : "+f"(c[0]), "+f"(c[1]), "+f"(c[2]), "+f"(c[3]) : "r"(a0), "r"(a1), "r"(b0));
}
__device__ __forceinline__ float ex2(float x) { float y; asm("ex2.approx.ftz.f32 %0, %1;" : "=f"(y) : "f"(x)); return y; }
__device__ __forceinline__ float rcp(float x) { float y; asm("rcp.approx.ftz.f32 %0, %1;" : "=f"(y) : "f"(x)); return y; }
__device__ __forceinline__ float sigmoidf(float z) { return rcp(1.0f + ex2(z * -1.4426950408889634f)); }
__device__ __forceinline__ float u2f(uint32_t u) { return __uint_as_float(u); }
__device__ __forceinline__ uint32_t f2u(float f) { return __float_as_uint(f); }

__device__ __forceinline__ void wgmma_main(float (&d)[96], uint32_t a, uint32_t b, int scale_d) {
    asm volatile("{\n.reg .pred p;\n.reg .b64 da, db;\nsetp.ne.b32 p, %98, 0;\n"
        "mov.b64 da, {%96, 0x40000040};\nmov.b64 db, {%97, 0x40000040};\n"
        "wgmma.mma_async.sync.aligned.m64n192k16.f32.bf16.bf16 "
        "{%0, %1, %2, %3, %4, %5, %6, %7, %8, %9, %10, %11, %12, %13, %14, %15, "
        "%16, %17, %18, %19, %20, %21, %22, %23, %24, %25, %26, %27, %28, %29, %30, %31, "
        "%32, %33, %34, %35, %36, %37, %38, %39, %40, %41, %42, %43, %44, %45, %46, %47, "
        "%48, %49, %50, %51, %52, %53, %54, %55, %56, %57, %58, %59, %60, %61, %62, %63, "
        "%64, %65, %66, %67, %68, %69, %70, %71, %72, %73, %74, %75, %76, %77, %78, %79, "
        "%80, %81, %82, %83, %84, %85, %86, %87, %88, %89, %90, %91, %92, %93, %94, %95}, "
        "da, db, p, 1, 1, 0, 1;\n}\n"
        : "+f"(d[0]), "+f"(d[1]), "+f"(d[2]), "+f"(d[3]), "+f"(d[4]), "+f"(d[5]), "+f"(d[6]), "+f"(d[7]),
          "+f"(d[8]), "+f"(d[9]), "+f"(d[10]), "+f"(d[11]), "+f"(d[12]), "+f"(d[13]), "+f"(d[14]), "+f"(d[15]),
          "+f"(d[16]), "+f"(d[17]), "+f"(d[18]), "+f"(d[19]), "+f"(d[20]), "+f"(d[21]), "+f"(d[22]), "+f"(d[23]),
          "+f"(d[24]), "+f"(d[25]), "+f"(d[26]), "+f"(d[27]), "+f"(d[28]), "+f"(d[29]), "+f"(d[30]), "+f"(d[31]),
          "+f"(d[32]), "+f"(d[33]), "+f"(d[34]), "+f"(d[35]), "+f"(d[36]), "+f"(d[37]), "+f"(d[38]), "+f"(d[39]),
          "+f"(d[40]), "+f"(d[41]), "+f"(d[42]), "+f"(d[43]), "+f"(d[44]), "+f"(d[45]), "+f"(d[46]), "+f"(d[47]),
          "+f"(d[48]), "+f"(d[49]), "+f"(d[50]), "+f"(d[51]), "+f"(d[52]), "+f"(d[53]), "+f"(d[54]), "+f"(d[55]),
          "+f"(d[56]), "+f"(d[57]), "+f"(d[58]), "+f"(d[59]), "+f"(d[60]), "+f"(d[61]), "+f"(d[62]), "+f"(d[63]),
          "+f"(d[64]), "+f"(d[65]), "+f"(d[66]), "+f"(d[67]), "+f"(d[68]), "+f"(d[69]), "+f"(d[70]), "+f"(d[71]),
          "+f"(d[72]), "+f"(d[73]), "+f"(d[74]), "+f"(d[75]), "+f"(d[76]), "+f"(d[77]), "+f"(d[78]), "+f"(d[79]),
          "+f"(d[80]), "+f"(d[81]), "+f"(d[82]), "+f"(d[83]), "+f"(d[84]), "+f"(d[85]), "+f"(d[86]), "+f"(d[87]),
          "+f"(d[88]), "+f"(d[89]), "+f"(d[90]), "+f"(d[91]), "+f"(d[92]), "+f"(d[93]), "+f"(d[94]), "+f"(d[95])
        : "r"(a), "r"(b), "r"(scale_d));
}

__device__ __forceinline__ void wgmma_rem(float (&d)[24], uint32_t a, uint32_t b, int scale_d) {
    asm volatile("{\n.reg .pred p;\n.reg .b64 da, db;\nsetp.ne.b32 p, %26, 0;\n"
        "mov.b64 da, {%24, 0x40000040};\nmov.b64 db, {%25, 0xC0000010};\n"
        "wgmma.mma_async.sync.aligned.m64n48k16.f32.bf16.bf16 "
        "{%0, %1, %2, %3, %4, %5, %6, %7, %8, %9, %10, %11, %12, %13, %14, %15, "
        "%16, %17, %18, %19, %20, %21, %22, %23}, "
        "da, db, p, 1, 1, 0, 1;\n}\n"
        : "+f"(d[0]), "+f"(d[1]), "+f"(d[2]), "+f"(d[3]), "+f"(d[4]), "+f"(d[5]), "+f"(d[6]), "+f"(d[7]),
          "+f"(d[8]), "+f"(d[9]), "+f"(d[10]), "+f"(d[11]), "+f"(d[12]), "+f"(d[13]), "+f"(d[14]), "+f"(d[15]),
          "+f"(d[16]), "+f"(d[17]), "+f"(d[18]), "+f"(d[19]), "+f"(d[20]), "+f"(d[21]), "+f"(d[22]), "+f"(d[23])
        : "r"(a), "r"(b), "r"(scale_d));
}

__device__ __forceinline__ void wgmma_out(float (&d)[80], uint32_t a, uint32_t b, int scale_d) {
    asm volatile("{\n.reg .pred p;\n.reg .b64 da, db;\nsetp.ne.b32 p, %82, 0;\n"
        "mov.b64 da, {%80, 0x50};\nmov.b64 db, {%81, 0x40000040};\n"
        "wgmma.mma_async.sync.aligned.m64n160k16.f32.bf16.bf16 "
        "{%0, %1, %2, %3, %4, %5, %6, %7, %8, %9, %10, %11, %12, %13, %14, %15, "
        "%16, %17, %18, %19, %20, %21, %22, %23, %24, %25, %26, %27, %28, %29, %30, %31, "
        "%32, %33, %34, %35, %36, %37, %38, %39, %40, %41, %42, %43, %44, %45, %46, %47, "
        "%48, %49, %50, %51, %52, %53, %54, %55, %56, %57, %58, %59, %60, %61, %62, %63, "
        "%64, %65, %66, %67, %68, %69, %70, %71, %72, %73, %74, %75, %76, %77, %78, %79}, "
        "da, db, p, 1, 1, 0, 1;\n}\n"
        : "+f"(d[0]), "+f"(d[1]), "+f"(d[2]), "+f"(d[3]), "+f"(d[4]), "+f"(d[5]), "+f"(d[6]), "+f"(d[7]),
          "+f"(d[8]), "+f"(d[9]), "+f"(d[10]), "+f"(d[11]), "+f"(d[12]), "+f"(d[13]), "+f"(d[14]), "+f"(d[15]),
          "+f"(d[16]), "+f"(d[17]), "+f"(d[18]), "+f"(d[19]), "+f"(d[20]), "+f"(d[21]), "+f"(d[22]), "+f"(d[23]),
          "+f"(d[24]), "+f"(d[25]), "+f"(d[26]), "+f"(d[27]), "+f"(d[28]), "+f"(d[29]), "+f"(d[30]), "+f"(d[31]),
          "+f"(d[32]), "+f"(d[33]), "+f"(d[34]), "+f"(d[35]), "+f"(d[36]), "+f"(d[37]), "+f"(d[38]), "+f"(d[39]),
          "+f"(d[40]), "+f"(d[41]), "+f"(d[42]), "+f"(d[43]), "+f"(d[44]), "+f"(d[45]), "+f"(d[46]), "+f"(d[47]),
          "+f"(d[48]), "+f"(d[49]), "+f"(d[50]), "+f"(d[51]), "+f"(d[52]), "+f"(d[53]), "+f"(d[54]), "+f"(d[55]),
          "+f"(d[56]), "+f"(d[57]), "+f"(d[58]), "+f"(d[59]), "+f"(d[60]), "+f"(d[61]), "+f"(d[62]), "+f"(d[63]),
          "+f"(d[64]), "+f"(d[65]), "+f"(d[66]), "+f"(d[67]), "+f"(d[68]), "+f"(d[69]), "+f"(d[70]), "+f"(d[71]),
          "+f"(d[72]), "+f"(d[73]), "+f"(d[74]), "+f"(d[75]), "+f"(d[76]), "+f"(d[77]), "+f"(d[78]), "+f"(d[79])
        : "r"(a), "r"(b), "r"(scale_d));
}

__device__ __forceinline__ void wgmma_own(float (&d)[80], uint32_t a0, uint32_t a1, uint32_t a2, uint32_t a3, uint32_t b, int scale_d) {
    asm volatile("{\n.reg .pred p;\n.reg .b64 db;\nsetp.ne.b32 p, %85, 0;\nmov.b64 db, {%84, 0x40000040};\n"
        "wgmma.mma_async.sync.aligned.m64n160k16.f32.bf16.bf16 "
        "{%0, %1, %2, %3, %4, %5, %6, %7, %8, %9, %10, %11, %12, %13, %14, %15, "
        "%16, %17, %18, %19, %20, %21, %22, %23, %24, %25, %26, %27, %28, %29, %30, %31, "
        "%32, %33, %34, %35, %36, %37, %38, %39, %40, %41, %42, %43, %44, %45, %46, %47, "
        "%48, %49, %50, %51, %52, %53, %54, %55, %56, %57, %58, %59, %60, %61, %62, %63, "
        "%64, %65, %66, %67, %68, %69, %70, %71, %72, %73, %74, %75, %76, %77, %78, %79}, "
        "{%80, %81, %82, %83}, db, p, 1, 1, 1;\n}\n"
        : "+f"(d[0]), "+f"(d[1]), "+f"(d[2]), "+f"(d[3]), "+f"(d[4]), "+f"(d[5]), "+f"(d[6]), "+f"(d[7]),
          "+f"(d[8]), "+f"(d[9]), "+f"(d[10]), "+f"(d[11]), "+f"(d[12]), "+f"(d[13]), "+f"(d[14]), "+f"(d[15]),
          "+f"(d[16]), "+f"(d[17]), "+f"(d[18]), "+f"(d[19]), "+f"(d[20]), "+f"(d[21]), "+f"(d[22]), "+f"(d[23]),
          "+f"(d[24]), "+f"(d[25]), "+f"(d[26]), "+f"(d[27]), "+f"(d[28]), "+f"(d[29]), "+f"(d[30]), "+f"(d[31]),
          "+f"(d[32]), "+f"(d[33]), "+f"(d[34]), "+f"(d[35]), "+f"(d[36]), "+f"(d[37]), "+f"(d[38]), "+f"(d[39]),
          "+f"(d[40]), "+f"(d[41]), "+f"(d[42]), "+f"(d[43]), "+f"(d[44]), "+f"(d[45]), "+f"(d[46]), "+f"(d[47]),
          "+f"(d[48]), "+f"(d[49]), "+f"(d[50]), "+f"(d[51]), "+f"(d[52]), "+f"(d[53]), "+f"(d[54]), "+f"(d[55]),
          "+f"(d[56]), "+f"(d[57]), "+f"(d[58]), "+f"(d[59]), "+f"(d[60]), "+f"(d[61]), "+f"(d[62]), "+f"(d[63]),
          "+f"(d[64]), "+f"(d[65]), "+f"(d[66]), "+f"(d[67]), "+f"(d[68]), "+f"(d[69]), "+f"(d[70]), "+f"(d[71]),
          "+f"(d[72]), "+f"(d[73]), "+f"(d[74]), "+f"(d[75]), "+f"(d[76]), "+f"(d[77]), "+f"(d[78]), "+f"(d[79])
        : "r"(a0), "r"(a1), "r"(a2), "r"(a3), "r"(b), "r"(scale_d));
}

#define TSA(i) do { } while (0)
#define MAP_TILE(b) (((b) & 3) | (((b) >> 5) << 2))
#define MAP_HG(b) ((((b) >> 2) & 7) ^ (((b) & 32) ? 6 : 0))
#define B_OFF 0
#define W_S0 2
#define E_V 0
#define SKEW 4
#define PACE 500
#define PACE_W0 (-600)
#define PACE_A 250
#define PACE_B 450
#define RG_ORDER 0x24130
#define GU_T0 3600
#define GU_DT 300
#define RS_T0 10000
#define RS_DT 200
#define EXCH_FIRST 1
#define HALO_D 300
#define PF_UP 4200
#define O_D 0
#define O_DT 300
#define PF_DN 4200
#define PF_DT 450
#define GX_NS 200
#define NRS 2
#define C5_D 600
#define C6_D 100
#define PF_N 4
#define PF_0 4
#define EPF_N 15
#define EPF_M 15
#define EPF_T 900
#define RG1_T0 1700
#define RG1_DT 200
#define RW1_T 0
#define Y_T 16500
#define GL_T 0
#define DN_T0 500
#define DN_DT 68
#define DN_T1 100000
#define DN_D1 45
#define DN_R 5
#define H_T 13500
#define HS_T 13500
#define GL_N 16
#define C1_T 0
#define C0_T 0
#define RS_N 4
#define CAND_T 9000

__device__ __forceinline__ uint32_t keep(uint32_t v) { return __shfl_xor_sync(0xffffffffu, v, 0); }
__device__ __forceinline__ uint32_t ukeep(uint32_t v) { return __shfl_sync(0xffffffffu, v, 0); }
__device__ __forceinline__ void ldsm2(uint32_t* d, uint32_t a) {
    asm volatile("ldmatrix.sync.aligned.m8n8.x4.shared.b16 {%0,%1,%2,%3}, [%8];\nldmatrix.sync.aligned.m8n8.x4.shared.b16 {%4,%5,%6,%7}, [%9];"
                 : "=r"(d[0]), "=r"(d[1]), "=r"(d[2]), "=r"(d[3]), "=r"(d[4]), "=r"(d[5]), "=r"(d[6]), "=r"(d[7])
                 : "r"(a), "r"(a ^ 32) : "memory");
}
__device__ __forceinline__ void ldsm_t(uint32_t (&d)[4], uint32_t a) {
    asm volatile("ldmatrix.sync.aligned.m8n8.x4.trans.shared.b16 {%0,%1,%2,%3}, [%4];"
                 : "=r"(d[0]), "=r"(d[1]), "=r"(d[2]), "=r"(d[3]) : "r"(a) : "memory");
}
template <bool SWP, int SEG, int E>
__device__ __forceinline__ void pack_blocks(uint32_t (&d)[10], const float (&am)[96], const float (&ar)[24]) {
#pragma unroll
    for (int t = 0; t < 10; t++) {
        const float* p = (SWP ? t < 2 : t >= 8) ? ar + (SEG * 2 + (t & 1)) * 4 + E : am + (SEG * 8 + t - (SWP ? 2 : 0)) * 4 + E;
        d[t] = pack2v(p[0], p[1]);
    }
}
__device__ __forceinline__ int src_of(int i, int hg) { return i == 0 ? hg : i - (i <= hg); }

__device__ constexpr uint32_t o_buf(int i) { return ((0x99ADA3D1u >> ((i - NRS) & 3) * 8) & 255) << 10; }
__device__ constexpr uint32_t wo_buf(int i) { return SM_W + ((0x10342103u >> i * 4) & 7) * 30720; }

template <int N>
__device__ __forceinline__ void poll(uint4 (&a)[N], const uint4* p, int stride) {
    bool bad;
    do {
        bad = false;
#pragma unroll
        for (int s = 0; s < N; s++) a[s] = ld_relaxed16(p + s * stride);
#pragma unroll
        for (int s = 0; s < N; s++) bad |= a[s].w == SENT;
    } while (__any_sync(0xffffffffu, bad));
}
__device__ __forceinline__ void pace(unsigned t0, int t) {
    asm volatile("{\n.reg .pred p;\n.reg .s32 d;\nAGAIN:\nmov.u32 d, %%clock;\nsub.s32 d, d, %0;\nsetp.lt.s32 p, d, 0;\n"
                 "@p nanosleep.u32 20;\n@p bra AGAIN;\n}" ::"r"(t0 + t) : "memory");
}
__device__ __forceinline__ void l2_prefetch(const void* p) { asm volatile("prefetch.global.L2 [%0];" ::"l"(p) : "memory"); }

template <int N>
__device__ __forceinline__ bool landed(const uint4* w, int lane) {
    uint32_t a = 0;
#pragma unroll
    for (int i = 0; i < N; i++) a ^= w[i].w;
    return __ballot_sync(0xffffffffu, lane == 0 || a == 0) && lane == 0;
}
template <int N>
__device__ __forceinline__ float4 vec_mma(const uint4 (&w)[N], const uint32_t* x, uint32_t sel) {
    float c[4][4] = {};
    const uint32_t s[4] = {sel, sel >> 16, sel + ((sel & 0x10101010u) >> 3) * 17, (sel + ((sel & 0x10101010u) >> 3) * 17) >> 16};
#pragma unroll
    for (int i = 0; i < N; i++)
        mma16(c[i & 3], w[i].x, w[i].y, w[i].z, w[i].w, prmt(x[i >> 1], s[(i & 1) * 2]), prmt(x[i >> 1], s[(i & 1) * 2 + 1]));
    return make_float4((c[0][0] + c[1][0]) + (c[2][0] + c[3][0]), (c[0][1] + c[1][1]) + (c[2][1] + c[3][1]),
                       (c[0][2] + c[1][2]) + (c[2][2] + c[3][2]), (c[0][3] + c[1][3]) + (c[2][3] + c[3][3]));
}

__global__ void __launch_bounds__(512, 1) fused_kernel(const __grid_constant__ Params P) {
    extern __shared__ __align__(1024) uint8_t smem_raw[];
    const unsigned t_start = clock();
    const int tid = threadIdx.x, lane = tid & 31;
    const int warp = __shfl_sync(0xffffffffu, threadIdx.x >> 5, 0);
    const int role = (blockIdx.x & ~6) == 0 ? -1 : warp;
    const unsigned bid = ((blockIdx.x < 8 ? 4 + blockIdx.x / 2 : blockIdx.x) - B_OFF) & (NCTA - 1);
    const int tile = MAP_TILE(bid), hg = MAP_HG(bid);
    const int cid = tile * 8 + hg;
    const int par = tile & 1, p0 = (tile >> 1) * 128;
    uint4* const sc = g_sc + cid * SC_SIZE;
    const bool swp = (hg & 3) == 3;
    const int wcm = hg * 80 + (swp ? 16 : 0), wcr = hg * 80 + (swp ? 0 : 64);
    if (EPF_N && warp == 15 && lane < EPF_N) l2_prefetch(P.wp + (lane * 128 + bid) * 64);
    if (warp < 7 && elect_one()) {
#pragma unroll
        for (int i = 0; i < 4; i++) mbar_init(SM_BAR + warp * 32 + i * 8, warp < 4 ? 1 : warp < 6 ? 2 : 4);
        asm volatile("fence.mbarrier_init.release.cluster;" ::: "memory");
        if (role == 0) {
            mbar_expect_tx(B_FULL, 15360 + 8192);
            tma_3d(SM_X + 8192, &P.x, B_FULL, 0, par, p0 + 64);
            tma_3d(SM_W, &P.w, B_FULL, wcm, 0, 0);
            tma_3d(SM_W + 12288, &P.wr, B_FULL, wcr, 0, 0);
            TS(40);
            if (E_V < 2) {
                mbar_expect_tx(B_XL0, 8192);
                tma_3d(SM_X, &P.x, B_XL0, 0, par, p0);
            }
            if (W_S0 > 1 && E_V < 1) {
                mbar_expect_tx(B_FULL + 8, 15360);
                tma_3d(SM_W + 15360, &P.w, B_FULL + 8, wcm, 32, 0);
                tma_3d(SM_W + 15360 + 12288, &P.wr, B_FULL + 8, wcr, 32, 0);
            }
        }
    }
    __syncthreads();

    if (role >= 12) {
        asm volatile("setmaxnreg.dec.sync.aligned.u32 32;");
        if (warp == 12) {
            if (elect_one()) {
#pragma unroll 1
                for (int s = W_S0; s < 20; s++) {
                    const uint32_t fb = B_FULL + (s & 7) * 8, dst = SM_W + (s & 7) * 15360;
                    mbar_wait(fb + (B_EMPTY - B_FULL), ~(s >> 3) & 1);
                    pace(t_start, max(PACE_A + s * PACE_B, PACE_W0 + s * PACE));
                    mbar_expect_tx(fb, (s & 1) ? 15360 : 15360 + 16384);
                    tma_3d(dst, &P.w, fb, wcm, s * 32, 0);
                    tma_3d(dst + 12288, &P.wr, fb, wcr, s * 32, 0);
                    TS2(20 + s);
                    if (s == W_S0) TS(41);
                }
                mbar_wait(B_RG2, 0);
                if (NFFN) {
                    mbar_wait(B_EMPTY + 5 * 8, 1);
                    mbar_expect_tx(B_UP, cid < NFFN ? 20480 : 16384);
                    TS(46);
                    if (cid < NFFN) tma_2d(SM_UP, &P.up, B_UP, (cid >> 2) * 64, (cid & 3) * 160);
                    else
#pragma unroll 1
                        for (int i = 0; i < 8; i++) tma_2d(SM_UP + i * 2048, &P.down, B_UP, i * 64, cid * 32 - 2352);
                }
                const int cb = hg >> 1, ca = (cb * 5 + 1) >> 1, cr = cb * 160 + ((cb & 1) ? 0 : 128);
#pragma unroll 1
                for (int j = 0; j < 8; j++) {
                    const int i = j ^ (j == 3 || j == 4 ? 7 : 0);
                    if (j != 3) mbar_wait(j < 3 ? B_EMPTY + ((2 * j + 7) & 7) * 8 : B_GUD + (j - 4) * 8, j == 0);
                    if (j >= 5) pace(clock(), j == 5 ? C5_D : C6_D);
                    if (C1_T && j == 1) pace(t_start, C1_T);
                    if (C0_T && j == 0) pace(t_start, C0_T);
                    const uint32_t dst = wo_buf(i), gb = B_G2 + i * 8;
                    mbar_expect_tx(gb, 25600);
                    tma_3d(dst, &P.woa, gb, 0, src_of(i, hg) * 80, ca);
                    tma_2d(dst + 20480, &P.wob, gb, cr, src_of(i, hg) * 80);
                }
            }
        } else if (warp == 14) {
            if (elect_one()) {
#pragma unroll 1
                for (int kb = 1; kb < 10; kb++) {
                    const uint32_t fb = B_FULL + (kb & 3) * 16, dst = SM_X + (kb & 3) * 16384;
                    mbar_wait(fb + (B_EMPTY - B_FULL + 8), ~(kb >> 2) & 1);
                    if (kb >= 4) mbar_wait(B_XE + (kb - 4 >> 1) * 8, 0);
                    pace(t_start, max(PACE_A - PACE_B / 2 + 2 * kb * PACE_B, PACE_W0 - 50 + (2 * kb + 1) * PACE));
                    tma_3d(dst, &P.x2, fb, kb * 64, par, p0);
                }
            }
            __syncwarp();
            pace(t_start, CAND_T);
            {
                const uint32_t tag = lds4(SM_KEY + 20 * 4);
                uint4 c[2], v;
                do {
                    c[0] = ld_relaxed16(g_cand + lane * 2);
                    c[1] = ld_relaxed16(g_cand + lane * 2 + 64);
                    v = ld_relaxed16(g_gate + tile * 128 + lane * 4);
                } while (__any_sync(0xffffffffu, ((c[0].x ^ tag) | (c[0].z ^ tag) | (c[1].x ^ tag) | (c[1].z ^ tag) | (v.x ^ tag) |
                                                  (v.y ^ tag) | (v.z ^ tag) | (v.w ^ tag)) & 0xF800u));
                const uint32_t a1 = max(c[0].x, c[0].z), b1 = max(c[1].x, c[1].z), l1 = max(a1, b1);
                const uint32_t l2 = max(max(max(c[0].y, c[0].w), max(c[1].y, c[1].w)),
                                        max(max(min(c[0].x, c[0].z), min(c[1].x, c[1].z)), min(a1, b1)));
                const uint32_t k1 = __reduce_max_sync(0xffffffffu, l1);
                const uint32_t k2 = __reduce_max_sync(0xffffffffu, l1 == k1 ? l2 : l1);
                sts16(SM_GATE + lane * 16, v.x, v.y, v.z, v.w);
                __syncwarp();
                if (elect_one()) {
                    bulk_load(SM_XS, P.xp + (~k1 & 2047) * 640 + (cid & 3) * 160, 320, B_XS);
                    bulk_load(SM_XS + 320, P.xp + (~k2 & 2047) * 640 + (cid & 3) * 160, 320, B_XS);
                    sts16(SM_KEY + 16 * 4, k1, k2, 0, 0);
                    mbar_expect_tx(B_XS, 640);
                    mbar_arrive(B_GT);
                    TS(56);
                }
            }
            bar_sync(12, 64);
            pace(clock(), HALO_D);
            uint4 hv[5];
            poll<5>(hv, sc + (SC_HALO - (tile < 2 ? 0 : 16 * SC_SIZE) + lane), 32);
#pragma unroll
            for (int s = 0; s < 5; s++) sts16(SM_HALO + s * 512 + lane * 16, hv[s].x, hv[s].y, hv[s].z, hv[s].w);
            bar_arrive(8, 64);
            TS(25);
        } else if (warp == 15) {
            if (EPF_M) {
                pace(t_start, EPF_T);
                if (lane < EPF_M) l2_prefetch(P.wp + ((lane + EPF_N) * 128 + bid) * 64);
            }
#pragma unroll 1
            for (int i = PF_0; i < PF_N; i++) {
                pace(t_start, (i < 6 ? PF_UP : PF_DN) + i * PF_DT);
                const int ln = (i * 128 + cid) * 32 + lane;
                l2_prefetch((ln < 17280 ? P.upp : ln < 23680 ? P.wop - 17280 * 64 : P.dp - 23680 * 64) + ln * 64);
            }
            int it = smem_u32(smem_raw) == SB ? 0 : 1 << 20;
            while (!mbar_try(B_DONE, 0) || !mbar_try(B_MOD, 0))
                if (++it > (1 << 20)) fault();
        } else {
#pragma unroll 1
            for (int i = 0; i < 10; i++) sts16(SM_SENT + i * 512 + lane * 16, SENT, SENT, SENT, SENT);
            fence_async_smem();
            __syncwarp();
            if (elect_one()) {
                mbar_expect_tx(B_RG, 2560);
                mbar_expect_tx(B_GU, cid < NFFN ? 20480 : 24576);
                asm volatile("mbarrier.expect_tx.relaxed.cta.shared::cta.b64 [%0], 10240;" ::"r"(B_RG2) : "memory");
                pace(t_start, RW1_T);
                bulk_load(SM_RED, P.w_r, 1280, B_RG);
                bulk_load(SM_RED + 1280, P.gate_w, 1280, B_RG);
#pragma unroll 1
                for (int i = 0; i < 5; i++) {
                    pace(t_start, RG1_T0 + i * RG1_DT);
                    tma_3d(SM_HALO + i * 2048, &P.xg, B_RG2, 320 + i * 64, par, p0 + hg * 16);
                }
#pragma unroll
                for (int i = 0; i < 23; i++) mbar_init(B_GUD + i * 8, i == 22 || !i ? 4 : i < 15 + NRS ? 1 : 2);
                bulk_store(sc + SC_HALO, SM_SENT, 5120);
                asm volatile("cp.async.bulk.commit_group;\ncp.async.bulk.wait_group 0;" ::: "memory");
                mbar_arrive(B_RG2);
                TS(43);
                const unsigned goal = (ld_relaxed4(g_cnt + 32) | (NCTA - 1)) + 1;
#pragma unroll 1
                for (int i = 0; i < (!NFFN ? 0 : cid < NFFN ? 8 : 12); i++) {
                    pace(t_start, GU_T0 + i * GU_DT);
                    if (cid < NFFN) tma_2d(SM_F + i * 2560, &P.gate, B_GU, (cid >> 2) * 64, (cid & 3) * 160 + i * 20);
                    else tma_2d(SM_F - 4096 + i * 2048, &P.down, B_GU, min(i, 4 + (i >> 1)) * 64, cid * 32 - 2368 + (i > 8 ? (i & 1) * 16 : 0));
                }
#pragma unroll 1
                for (int i = 0; i < RS_N; i++) {
                    pace(t_start, RS_T0 + i * RS_DT);
                    bulk_store(sc + i * (1280 / RS_N), SM_SENT, 20480 / RS_N);
                }
                asm volatile("cp.async.bulk.commit_group;\ncp.async.bulk.wait_group 0;" ::: "memory");
                red_inc(g_cnt + 32, goal);
                mbar_arrive(B_RS);
                TS(44);
                while (ld_relaxed4(g_cnt + 32) - goal > 0x80000000u) {}
                mbar_arrive(B_INIT);
                TS(45);
            }
        }
    } else if (role >= 8) {
        asm volatile("setmaxnreg.dec.sync.aligned.u32 96;");
        const int t = tid - 256;
        uint32_t tag = ld_relaxed4(g_cnt);
        float gv = 0.f;
        int grow = hg * 16 + (t >> 3);
        mbar_wait(B_RG, 0);
        TS(warp == 8 ? 48 : 63);
        {
            float r0 = 0.f, r1 = 0.f, g0 = 0.f, g1 = 0.f;
            const uint32_t sw = (t >> 4) * 128 + (((t ^ (t >> 4)) & 7) << 4), hi = (t >> 3) & 1;
            mbar_wait(B_XL0, 0);
            tag = (tag * 8 + 2048) & 0xF800u;
            sts4(SM_KEY + 20 * 4, tag);
#pragma unroll 1
            for (int i = 0; i < 5; i++) {
                const int p = (RG_ORDER >> (i * 4)) & 7, kb = 2 * p + hi;
                mbar_wait(p < 3 ? B_FULL + (p & 1) * 32 : B_RG2, p == 2);
                if (p < 2) mbar_wait(B_FULL + p * 32 + 16, 0);
                const uint32_t xa = sw + (kb < 5 ? SM_X + (kb & 3) * 16384 + hg * 2048 : SM_HALO - 5 * 2048 + kb * 2048);
                const uint4 a = lds16(xa), b = lds16(xa + 1024);
                const uint4 w = lds16(SM_RED + p * 256 + (t & 15) * 16), v = lds16(SM_RED + 1280 + p * 256 + (t & 15) * 16);
                if (__ballot_sync(0xffffffffu, lane == 0 || a.w == b.w) && lane == 0 && p < 3) mbar_arrive(B_XE + p * 8);
                const uint32_t as[4] = {a.x, a.y, a.z, a.w}, bs[4] = {b.x, b.y, b.z, b.w};
                const uint32_t ws[4] = {w.x, w.y, w.z, w.w}, vs[4] = {v.x, v.y, v.z, v.w};
#pragma unroll
                for (int e = 0; e < 4; e++) {
                    r0 = fmaf(bf_lo(as[e]), bf_lo(ws[e]), r0);
                    r1 = fmaf(bf_lo(bs[e]), bf_lo(ws[e]), r1);
                    g0 = fmaf(bf_lo(as[e]), bf_lo(vs[e]), g0);
                    g1 = fmaf(bf_lo(bs[e]), bf_lo(vs[e]), g1);
                    r0 = fmaf(bf_hi(as[e]), bf_hi(ws[e]), r0);
                    r1 = fmaf(bf_hi(bs[e]), bf_hi(ws[e]), r1);
                    g0 = fmaf(bf_hi(as[e]), bf_hi(vs[e]), g0);
                    g1 = fmaf(bf_hi(bs[e]), bf_hi(vs[e]), g1);
                }
            }
            const bool up = lane & 4;
            r0 = (hi ? r1 : r0) + __shfl_xor_sync(0xffffffffu, hi ? r0 : r1, 8);
            g0 = (hi ? g1 : g0) + __shfl_xor_sync(0xffffffffu, hi ? g0 : g1, 8);
            float r = (up ? g0 : r0) + __shfl_xor_sync(0xffffffffu, up ? r0 : g0, 4);
            r += __shfl_xor_sync(0xffffffffu, r, 2);
            r = bf_round(r + __shfl_xor_sync(0xffffffffu, r, 1));
            const int row = hg * 16 + (t >> 4) + hi * 8;
            const uint32_t u = f2u(r);
            if (!up) sts4(SM_KEY + (t >> 3) * 4, (((int)u < 0 ? ~u : u | 0x80000000u) & 0xFFFF0000u) | (2047 - (p0 + row) * 2 - par));
            gv = r;
            grow = row;
        }
        TS(warp == 8 ? 61 : 63);
        mbar_wait(B_RG2, 0);
        bar_sync(4, 128);
        if (warp == 8) {
            const uint32_t key = lds4(SM_KEY + (lane & 15) * 4);
            uint32_t k1 = __reduce_max_sync(0xffffffffu, key);
            uint32_t k2 = __reduce_max_sync(0xffffffffu, key == k1 ? 0u : key);
            if (elect_one()) {
                st_relaxed8(g_cand + cid, k1 | tag, k2 | tag);
                red_inc(g_cnt, tag);
            }
            TS(49);
        }
        if ((lane & 7) == 4) st_relaxed4(g_gate + tile * 128 + grow, f2u(bf_round(sigmoidf(gv))) | tag);
        const int cq = lane & 3, w4 = warp & 3;
        const uint32_t la = keep(cq * 256 + (((lane >> 2) ^ cq * 2) << 4));
        const uint32_t sel = keep(0x44444444u ^ (0x54u << (lane >> 2 & 1) * 8 + (lane & 16)));
        if (NFFN) {
            float4 d;
            uint4* dst;
            if (cid < NFFN) {
                uint4 wv[20];
                const uint32_t wa = (w4 < 2 ? SM_F : SM_UP) + (w4 & 1) * 10240;
                mbar_wait(B_GU + (w4 & 2) * 4, 0);
                TS(warp == 10 ? 58 : 63);
                if (GL_T) pace(t_start, GL_T);
#pragma unroll
                for (int i = 0; i < GL_N; i++) wv[i] = lds16((la ^ (i & 1) * 144) + wa + (i >> 1) * 1024);
                TS(warp == 8 ? 42 : warp == 10 ? 53 : 63);
                mbar_wait(B_XS, 0);
                TS(warp == 8 ? 50 : 63);
                uint32_t xv[12];
#pragma unroll
                for (int i = 0; i < 3; i++)
                    asm volatile("ldmatrix.sync.aligned.m8n8.x4.shared.b16 {%0,%1,%2,%3}, [%4];"
                                 : "=r"(xv[4 * i]), "=r"(xv[4 * i + 1]), "=r"(xv[4 * i + 2]), "=r"(xv[4 * i + 3])
                                 : "r"(SM_XS + (lane & 2) * 160 + (w4 & 1) * 160 + (lane >> 3) * 16 + i * 64) : "memory");
#pragma unroll
                for (int i = GL_N; i < 20; i++) wv[i] = lds16((la ^ (i & 1) * 144) + wa + (i >> 1) * 1024);
                d = vec_mma<20>(wv, xv, sel);
                if (lane == 0 && f2u(d.x) != SENT) mbar_arrive(B_GUD);
                TS(warp == 8 ? 54 : warp == 10 ? 59 : 63);
                dst = sc + SC_GU + w4 * 16 + lane;
            } else {
                uint4 wv[2][8], wr[4];
                mbar_wait(B_UP, 0);
#pragma unroll
                for (int i = 0; i < 8; i++) wv[i >> 2][4 + (i & 3)] = lds16((la ^ (i & 1) * 144) + SM_UP + w4 * 4096 + (i >> 1) * 1024);
                if (landed<4>(wv[0] + 4, lane) & landed<4>(wv[1] + 4, lane)) mbar_arrive(B_GUD);
                mbar_wait(B_GU, 0);
#pragma unroll
                for (int i = 0; i < 4; i++) wr[i] = lds16((la ^ (i & 1) * 144) + SM_F + 12288 + w4 * 2048 + (i >> 1) * 1024);
                mbar_wait(B_XS, 0);
                if (w4 < 2) {
                    uint4 pq[2];
                    pace(t_start, HS_T);
                    poll<2>(pq, g_sc + ((cid >> 1) * 4 - 148 + cq) * SC_SIZE + SC_GU + (cid & 1) * 16 + (t >> 2), 32);
                    TS(warp == 8 ? 55 : 63);
                    const bool b1 = cq & 2, b0 = cq & 1;
                    float v[4];
#pragma unroll
                    for (int m = 0; m < 2; m++) {
                        v[2 * m] = u2f(b1 ? pq[m].z : pq[m].x) + __shfl_xor_sync(0xffffffffu, u2f(b1 ? pq[m].x : pq[m].z), 2);
                        v[2 * m + 1] = u2f(b1 ? pq[m].w : pq[m].y) + __shfl_xor_sync(0xffffffffu, u2f(b1 ? pq[m].y : pq[m].w), 2);
                        v[m] = bf_round((b0 ? v[2 * m + 1] : v[2 * m]) + __shfl_xor_sync(0xffffffffu, b0 ? v[2 * m] : v[2 * m + 1], 1));
                    }
                    const uint32_t h = pack2(bf_round(v[0] * sigmoidf(v[0])) * v[1], 0.f);
                    asm volatile("st.shared.u16 [%0], %1;" ::"r"(SM_H + (t & 4) * 16 + (t & 8) * 4 + (t & 2) * 8 + (t >> 4) * 4 + (t & 1) * 2),
                                 "h"((uint16_t)h) : "memory");
                }
                bar_sync(4, 128);
                TS(warp == 8 ? 57 : 63);
                const uint4 h = lds16(SM_H + (lane & 8) * 8 + cq * 16);
                const uint32_t hv[4] = {h.x, h.y, h.z, h.w}, hr[2] = {(w4 & 1) ? h.z : h.x, (w4 & 1) ? h.w : h.y};
                d = vec_mma<4>(wr, hr, sel);
                dst = g_sc + (cid * 5 - 520 + w4) * SC_SIZE + SC_Y + (lane & 1) * 32 + (lane >> 1);
                float c[2][2][4] = {};
                const uint32_t s2 = sel + ((sel & 0x10101010u) >> 3) * 17;
#pragma unroll
                for (int i = 7; i >= 0; i--) {
                    const uint32_t x0 = prmt(hv[i >> 1], (i & 1) ? s2 : sel), x1 = prmt(hv[i >> 1], ((i & 1) ? s2 : sel) >> 16);
#pragma unroll
                    for (int n = 0; n < 2; n++) {
                        if (i >= 4) wv[n][i - 4] = lds16((la ^ (i & 1) * 144) + SM_F - 6144 + w4 * 4096 + n * 2048 + (i >> 1) * 1024);
                        mma16(c[n][i & 1], wv[n][i].x, wv[n][i].y, wv[n][i].z, wv[n][i].w, x0, x1);
                    }
                }
#pragma unroll
                for (int n = 0; n < 2; n++)
                    st_relaxed16(dst + n * 16, f2u(c[n][0][0] + c[n][1][0]), f2u(c[n][0][1] + c[n][1][1]), f2u(c[n][0][2] + c[n][1][2]),
                                 f2u(c[n][0][3] + c[n][1][3]));
                dst += (4 - w4) * SC_SIZE + w4 * 8;
                TS(warp == 8 ? 30 : 63);
            }
            if (lane == 0 && f2u(d.x) != SENT) mbar_arrive(B_DF);
            if (w4 & 1) {
                sts16(SM_RED + 512 + (w4 & 2) * 256 + lane * 16, f2u(d.x), f2u(d.y), f2u(d.z), f2u(d.w));
                bar_arrive(13 + (w4 >> 1), 64);
            } else {
                bar_sync(13 + (w4 >> 1), 64);
                const uint4 o = lds16(SM_RED + 512 + (w4 & 2) * 256 + lane * 16);
                st_relaxed16(dst, f2u(d.x + u2f(o.x)), f2u(d.y + u2f(o.y)), f2u(d.z + u2f(o.z)), f2u(d.w + u2f(o.w)));
            }
        } else {
            if (t < 4) mbar_arrive(B_GUD);
            if (t < 4) mbar_arrive(B_DF);
            mbar_wait(B_XS, 0);
        }
        TS(warp == 8 ? 51 : 63);
        const uint32_t k1 = lds4(SM_KEY + 16 * 4), k2 = lds4(SM_KEY + 17 * 4);
        const uint32_t mine = (tile >> 1) * 256 + (hg & 1) * 128 + par;
        const bool own1 = (~k1 & 0x781) == mine, own2 = (~k2 & 0x781) == mine;
        if ((own1 || own2) && NFFN) {
            const int rg = min(t / 40, 2), un = (hg >> 1) * 40 + t % 40;
            mbar_wait(B_RS, 0);
            pace(t_start, Y_T);
            TS(warp == 8 ? 60 : 63);
#pragma unroll 1
            for (int j = !own1; j <= own2; j++) {
                const uint4* p = g_sc + (rg * 5 + (un >> 5)) * SC_SIZE + SC_Y + j * 32 + (un & 31);
                float y[4];
                bool bad;
                do {
                    uint4 yp[8];
#pragma unroll
                    for (int i = 0; i < 8; i++) yp[i] = ld_relaxed16(p + i * 15 * SC_SIZE);
                    y[0] = y[1] = y[2] = y[3] = 0.f;
                    bad = false;
#pragma unroll
                    for (int i = 0; i < 8; i++) {
                        y[0] += u2f(yp[i].x); y[1] += u2f(yp[i].y); y[2] += u2f(yp[i].z); y[3] += u2f(yp[i].w);
                        bad |= yp[i].w == SENT;
                    }
                } while (__any_sync(0xffffffffu, bad));
                TS(warp == 8 ? 62 : 63);
                sts16(SM_SENT + j * 2048 + t * 16, f2u(y[0]), f2u(y[1]), f2u(y[2]), f2u(y[3]));
                bar_sync(4, 128);
                if (t < 80) {
                    const uint32_t key = j ? k2 : k1, ya = SM_SENT + j * 2048 + t * 8;
                    const float rs = bf_round(sigmoidf(u2f(((int)key < 0 ? key & 0x7FFFFFFFu : ~key) & 0xFFFF0000u)));
                    const float2 y0 = lds8f(ya), y1 = lds8f(ya + 640), y2 = lds8f(ya + 1280);
                    sts4(SM_U + j * 320 + t * 4, pack2(bf_round(y0.x + y1.x + y2.x) * rs, bf_round(y0.y + y1.y + y2.y) * rs));
                }
            }
            bar_sync(4, 128);
        }
        if (t == 0) mbar_arrive(B_MOD);
        TS(warp == 8 ? 52 : 63);
    } else if (role < 0) {
        const int e = blockIdx.x >> 1, half = warp >> 3;
        if (!NFFN) {
            if (tid == 0) red_inc<NCTA / NEXTRA>(g_cnt, 0);
            return;
        }
        uint32_t wf[DN_R][5][4], la[5];
        auto rows = [&](uint32_t l) {
#pragma unroll
            for (int i = 0; i < 5; i++) {
                const uint32_t c = (warp & 7) * 10 + 2 * i + (l >> 3 & 1);
                la[i] = SB + half * 20480 + (c >> 3) * 2048 + (l & 7) * 128 + (l >> 4) * 1024 + (((c ^ l) & 7) << 4);
            }
        };
        rows(lane);
        auto fetch = [&](int j, int n, uint32_t bar) {
#pragma unroll 1
            for (int h = 0; h < n; h++) {
                pace(t_start, min(DN_T0 + (j * 20 + h * 10 + warp) * DN_DT, DN_T1 + (j * 20 + h * 10 + warp) * DN_D1));
                tma_2d(SB + (j % 5) * 40960 + h * 20480 + warp * 2048, &P.down, bar, warp * 64, e * 272 + (j + h * 9) * 16);
            }
        };
        if (warp < 10 && elect_one()) {
            if (warp <= DN_R) mbar_expect_tx(B_FULL + warp * 8, warp < DN_R ? 40960 : (17 - 2 * DN_R) * 20480);
#pragma unroll 1
            for (int j = 0; j < 5; j++) fetch(j, 2, B_FULL + j * 8);
        }
        const uint32_t tag = (ukeep(ld_relaxed4(g_cnt)) * 8 + 2048) & 0xF800u;
#pragma unroll
        for (int j = 0; j < DN_R; j++) {
            uint32_t any = 0;
            mbar_wait(B_FULL + j * 8, 0);
#pragma unroll
            for (int i = 0; i < 5; i++) {
                ldsm_t(wf[j][i], la[i] + j * 40960);
                any ^= wf[j][i][3];
            }
            if (j < 4) {
                if (__syncthreads_count(any == 0) == 1000) fault();
                if (warp < 10 && elect_one()) fetch(j + 5, j < 3 ? 2 : 1, B_FULL + DN_R * 8);
                if (j == 0 && tid == 0) red_inc<NCTA / NEXTRA>(g_cnt, tag);
            }
            TSX(warp == 0 && j == 0 ? 0 : warp == 0 && j == 3 ? 1 : 63);
        }
        if (warp < 9) {
            pace(t_start, H_T - 1000);
            uint4 a[4];
            do {
                a[0] = ld_relaxed16(g_cand + lane * 2);
                a[1] = ld_relaxed16(g_cand + lane * 2 + 64);
            } while (__any_sync(0xffffffffu, ((a[0].x ^ tag) | (a[0].z ^ tag) | (a[1].x ^ tag) | (a[1].z ^ tag)) & 0xF800u));
            const int u = min(tid, 271), wq = e * 136 + (u >> 1);
            const uint4* const p = g_sc + ((wq >> 5) * 4 + (u & 1) * 2) * SC_SIZE + SC_GU + (wq & 31);
            pace(t_start, H_T);
            TSX(warp == 0 ? 3 : 63);
            do {
#pragma unroll
                for (int i = 0; i < 4; i++) a[i] = ld_relaxed16(p + (i & 1) * SC_SIZE + (i >> 1) * 32);
            } while (__any_sync(0xffffffffu, max(max(a[0].w, a[1].w), max(a[2].w, a[3].w)) == SENT));
            TSX(warp == 0 ? 4 : warp == 8 ? 5 : 63);
            float v[4];
#pragma unroll
            for (int m = 0; m < 2; m++) {
                const float x = u2f(a[2 * m].x) + u2f(a[2 * m + 1].x), y = u2f(a[2 * m].y) + u2f(a[2 * m + 1].y);
                const float z = u2f(a[2 * m].z) + u2f(a[2 * m + 1].z), w = u2f(a[2 * m].w) + u2f(a[2 * m + 1].w);
                v[2 * m] = bf_round(((u & 1) ? z : x) + __shfl_xor_sync(0xffffffffu, (u & 1) ? x : z, 1));
                v[2 * m + 1] = bf_round(((u & 1) ? w : y) + __shfl_xor_sync(0xffffffffu, (u & 1) ? y : w, 1));
            }
            if (tid < 272)
                sts4(SM_RED + (u >> 4) * 64 + (u & 2) * 16 + (u & 4) * 4 + (u & 1) * 8 + (u & 8) / 2,
                     pack2(bf_round(v[0] * sigmoidf(v[0])) * v[2], bf_round(v[1] * sigmoidf(v[1])) * v[3]));
        }
        rows(keep(lane));
        mbar_wait(B_FULL + DN_R * 8, 0);
        TSX(warp == 15 ? 2 : 63);
        __syncthreads();
        float c[5][4] = {};
#pragma unroll
        for (int j = 0; j < 9; j++) {
            if (j == 8 && half) break;
            const float2 b = lds8f(SM_RED + half * 576 + j * 64 + (lane & 7) * 8);
            if (j == 1) TSX(warp == 0 ? 6 : 63);
#pragma unroll
            for (int i = 0; i < 5; i++) {
                if (j >= DN_R) ldsm_t(wf[j % DN_R][i], la[i] + (j % 5) * 40960);
                mma16(c[i], wf[j % DN_R][i][0], wf[j % DN_R][i][1], wf[j % DN_R][i][2], wf[j % DN_R][i][3], f2u(b.x), f2u(b.y));
            }
        }
        const uint32_t ra = SB + 7 * 20480 + half * 5248 + (lane & 1) * 2624 + (warp & 7) * 320 + (lane & 2) * 16 + (lane >> 2) * 4;
#pragma unroll
        for (int i = 0; i < 5; i++) sts4(ra + i * 64, f2u((lane & 2) ? ((lane & 1) ? c[i][3] : c[i][2]) : ((lane & 1) ? c[i][1] : c[i][0])));
        TSX(warp == 0 ? 7 : 63);
        __syncthreads();
        if (warp < 10) {
            const uint32_t ya = SB + 7 * 20480 + (warp & 1) * 2624 + (warp >> 1) * 512 + lane * 16;
            const uint4 y0 = lds16(ya), y1 = lds16(ya + 5248);
            st_relaxed16(g_sc + (e * 5 + (warp >> 1)) * SC_SIZE + SC_Y + (tid & 63), f2u(u2f(y0.x) + u2f(y1.x)), f2u(u2f(y0.y) + u2f(y1.y)),
                         f2u(u2f(y0.z) + u2f(y1.z)), f2u(u2f(y0.w) + u2f(y1.w)));
        }
    } else {
        if (E_V && warp == 0 && elect_one()) {
            if (E_V == 2) {
                mbar_expect_tx(B_XL0, 8192);
                tma_3d(SM_X, &P.x, B_XL0, 0, par, p0);
            }
            if (W_S0 > 1) {
                mbar_expect_tx(B_FULL + 8, 15360);
                tma_3d(SM_W + 15360, &P.w, B_FULL + 8, wcm, 32, 0);
                tma_3d(SM_W + 15360 + 12288, &P.wr, B_FULL + 8, wcr, 32, 0);
            }
            if (E_V == 3) {
                mbar_expect_tx(B_XL0, 8192);
                tma_3d(SM_X, &P.x, B_XL0, 0, par, p0);
            }
        }
        asm volatile("setmaxnreg.inc.sync.aligned.u32 192;");
        const int wg = warp >> 2;
        const bool leader = (tid & 127) == 0;
        float am[96], ar[24];
        if (wg == 0) mbar_wait(B_XL0, 0);
        bool rel = false;
        uint32_t nb[40];
        const int odd = (hg >> 1) & 1, kba = ukeep(((hg >> 1) * 5 + 1) >> 1), kbr = ukeep(kba + 2 - odd * 3);
        const int kbs = wg ? -1 : (20 - SKEW) / 2;
        const uint32_t xrow = keep(SM_X + (warp * 16 + (lane & 15)) * 128 + (((lane >> 4) ^ (lane & 7)) << 4));
#pragma unroll 1
        for (int kb = 0; kb < 10; kb++) {
            const uint32_t fb = B_FULL + (kb & 3) * 16, wo = (kb & 3) * 1920, ph = (kb >> 2) & 1;
            const uint32_t xo = desc_lo(SM_X, 16) + wg * 512 + (kb & 3) * 1024;
#pragma unroll
            for (int h = 0; h < 2; h++) {
                mbar_wait(fb + h * 8, ph);
                if (kb == 0 && h == 0) TS(warp == 0 ? 0 : warp == 4 ? 16 : 63);
                TS2(warp == 4 ? kb * 2 + h : 63);
                if (h == 0) {
                    const uint32_t xa = xrow + (kb & 3) * 16384;
                    if (kb == kba) { ldsm2(nb, xa); ldsm2(nb + 8, xa ^ 64); }
                    if (kb == kba + 1) { ldsm2(nb + 16, xa); ldsm2(nb + 24, xa ^ 64); }
                    if (kb == kbr) ldsm2(nb + 32, xa ^ (odd * 64));
                }
                wg_wait<1>();
                if (rel && (h == 0 || kb != kbs)) mbar_arrive(B_EMPTY + ((kb * 16 - 16) & 48) + h * 8);
                if (h == 0 && kb == kbs) {
                    wg_wait<0>();
                    if (rel) mbar_arrive(B_EMPTY + ((19 - SKEW) & 7) * 8);
                    bar_sync(5, 256);
                }
                wg_fence();
                wgmma_main(am, xo + h * 4, desc_lo(SM_W + h * 15360, 4096) + wo, h || kb);
                wgmma_rem(ar, xo + h * 4, desc_lo(SM_W + h * 15360 + 12288, 1024) + wo, h || kb);
                wgmma_main(am, xo + h * 4 + 2, desc_lo(SM_W + h * 15360 + 2048, 4096) + wo, 1);
                wgmma_rem(ar, xo + h * 4 + 2, desc_lo(SM_W + h * 15360 + 12288 + 512, 1024) + wo, 1);
                wg_commit();
            }
            rel = leader;
        }
        if (wg == 1) bar_arrive(5, 256);
        mbar_wait(B_XE + 16, 0);
        mbar_wait(B_RG2, 0);
        mbar_wait(B_EMPTY + 5 * 8, 1);
        wg_wait<0>();
        if (leader) mbar_arrive(B_EMPTY + 3 * 8);
        TS(warp == 0 ? 2 : warp == 4 ? 18 : 63);
        TS2(warp == 0 ? 41 : warp == 4 ? 40 : 63);

        uint32_t kl[10], kh[10], vl[10], vh[10], ql[10], qh[10], kp[10], vp[10];
        if (swp) {
            pack_blocks<true, 1, 2>(kh, am, ar);
            pack_blocks<true, 2, 2>(vh, am, ar);
        } else {
            pack_blocks<false, 1, 2>(kh, am, ar);
            pack_blocks<false, 2, 2>(vh, am, ar);
        }
        const int w4 = warp & 3;
        const uint32_t pbuf = (wg ? SM_HALO1 : SM_HALO) + w4 * 2560 + lane * 16;
        const uint32_t hbuf = warp == 3 ? SM_HALO1 + lane * 16 : pbuf + 2560;
        {
            const uint32_t ex[20] = {kh[0], kh[1], kh[3], kh[4], kh[5], kh[6], kh[8], kh[9], kh[2], kh[7],
                                     vh[0], vh[1], vh[2], vh[3], vh[4], vh[5], vh[6], vh[7], vh[8], vh[9]};
            if (warp == 7) {
                uint4* const hp = sc + SC_HALO + lane;
#pragma unroll
                for (int s = 0; s < 5; s++) st_relaxed16(hp + s * 32, ex[4 * s], ex[4 * s + 1], ex[4 * s + 2], ex[4 * s + 3]);
                bar_arrive(12, 64);
            } else {
#pragma unroll
                for (int s = 0; s < 5; s++) sts16(hbuf + s * 512, ex[4 * s], ex[4 * s + 1], ex[4 * s + 2], ex[4 * s + 3]);
            }
        }
        TSA(warp == 7 ? 22 : warp == 3 ? 23 : 63);
        if (warp == 3) bar_arrive(11, 64);
        if (swp) {
            pack_blocks<true, 2, 0>(vl, am, ar);
            pack_blocks<true, 0, 0>(ql, am, ar);
            pack_blocks<true, 0, 2>(qh, am, ar);
            pack_blocks<true, 1, 0>(kl, am, ar);
        } else {
            pack_blocks<false, 2, 0>(vl, am, ar);
            pack_blocks<false, 0, 0>(ql, am, ar);
            pack_blocks<false, 0, 2>(qh, am, ar);
            pack_blocks<false, 1, 0>(kl, am, ar);
        }
#pragma unroll
        for (int t = 0; t < 10; t++) { vl[t] = movm(vl[t]); vh[t] = movm(vh[t]); }
        mbar_wait(B_RS, 0);
        mbar_wait(B_GT, 0);
        const float g0 = bf_hi(lds4(SM_GATE + warp * 64 + (lane & 28))), g1 = bf_hi(lds4(SM_GATE + 32 + warp * 64 + (lane & 28)));

        const int r = lane >> 2, cq = lane & 3;
        const bool no_prev = warp == 0 && tile < 2, low = cq < 2;
        const bool le0 = 2 * cq <= r, le1 = 2 * cq + 1 <= r;
        const uint32_t mle = (le0 ? 0xFFFFu : 0u) | (le1 ? 0xFFFF0000u : 0u);
        const float scl = 0.22360679774997896f * 1.4426950408889634f;
        uint32_t pl[4], ph[4];
        {
            float sl[4][4], sh[4][4], sp[4][4];
            auto exchange = [&]() {
            TSA(warp == 1 ? 26 : 63);
            bar_sync(6 + wg, 128);
            if (w4 == 0) bar_sync(8 + wg * 3, 64);
            {
                const uint4 a = lds16(pbuf), b = lds16(pbuf + 512), c = lds16(pbuf + 1024), d = lds16(pbuf + 1536), e = lds16(pbuf + 2048);
                kp[0] = a.x; kp[1] = a.y; kp[3] = a.z; kp[4] = a.w; kp[5] = b.x; kp[6] = b.y; kp[8] = b.z; kp[9] = b.w;
                kp[2] = c.x; kp[7] = c.y; vp[0] = c.z; vp[1] = c.w; vp[2] = d.x; vp[3] = d.y; vp[4] = d.z; vp[5] = d.w;
                vp[6] = e.x; vp[7] = e.y; vp[8] = e.z; vp[9] = e.w;
            }
            TSA(warp == 0 ? 3 : warp == 4 ? 19 : warp == 5 ? 27 : 63);
            };
            if (EXCH_FIRST) exchange();
#pragma unroll
            for (int h = 0; h < 4; h++) {
                const int ta = (h >> 1) * 5 + (h & 1) * 3, tc = (h >> 1) * 5 + 2;
                const uint32_t ml = low != (h & 1) ? ql[tc] : 0u, mh = low != (h & 1) ? qh[tc] : 0u;
#pragma unroll
                for (int e = 0; e < 4; e++) sl[h][e] = sh[h][e] = sp[h][e] = 0.f;
                mma16(sl[h], ql[ta], qh[ta], ql[ta + 1], qh[ta + 1], kl[ta], kl[ta + 1]);
                mma16(sh[h], ql[ta], qh[ta], ql[ta + 1], qh[ta + 1], kh[ta], kh[ta + 1]);
                mma8(sl[h], ml, mh, kl[tc]);
                mma8(sh[h], ml, mh, kh[tc]);
            }
            if (!EXCH_FIRST) exchange();
#pragma unroll
            for (int h = 0; h < 4; h++) {
                const int ta = (h >> 1) * 5 + (h & 1) * 3, tc = (h >> 1) * 5 + 2;
                mma16(sp[h], ql[ta], qh[ta], ql[ta + 1], qh[ta + 1], kp[ta], kp[ta + 1]);
                mma8(sp[h], low != (h & 1) ? ql[tc] : 0u, low != (h & 1) ? qh[tc] : 0u, kp[tc]);
            }
#pragma unroll
            for (int t = 0; t < 10; t++) vp[t] = movm(vp[t]);
#pragma unroll
            for (int h = 0; h < 4; h++) {
                if (no_prev) sp[h][0] = sp[h][1] = -1e9f / 0.22360679774997896f;
                const float a0 = le0 ? sl[h][0] : sp[h][0], a1 = le1 ? sl[h][1] : sp[h][1];
                const float b0 = le0 ? sh[h][2] : sl[h][2], b1 = le1 ? sh[h][3] : sl[h][3];
                float ma = fmaxf(a0, a1), mb = fmaxf(b0, b1);
                ma = fmaxf(ma, __shfl_xor_sync(0xffffffffu, ma, 1));
                mb = fmaxf(mb, __shfl_xor_sync(0xffffffffu, mb, 1));
                ma = fmaxf(ma, __shfl_xor_sync(0xffffffffu, ma, 2)) * -scl;
                mb = fmaxf(mb, __shfl_xor_sync(0xffffffffu, mb, 2)) * -scl;
                pl[h] = pack2(ex2(fmaf(a0, scl, ma)), ex2(fmaf(a1, scl, ma)));
                ph[h] = pack2(ex2(fmaf(b0, scl, mb)), ex2(fmaf(b1, scl, mb)));
            }
        }
        TSA(warp == 0 ? 4 : warp == 4 ? 20 : warp == 5 ? 28 : 63);
        uint32_t ol[10], oh[10];
        {
            uint32_t* const po = reinterpret_cast<uint32_t*>(sc + SC_O + warp * 160) + lane;
            const uint32_t ONES = 0x3F803F80u;
            float o[12][4];
#pragma unroll
            for (int hp = 0; hp < 2; hp++) {
#pragma unroll
                for (int h = hp * 2; h < hp * 2 + 2; h++) {
                    const int ta = (h >> 1) * 5 + (h & 1) * 3, tc = (h >> 1) * 5 + 2;
                    const bool mine = (lane < 16) != (h & 1);
                    const uint32_t a0 = pl[h] & mle, a1 = ph[h] & ~mle, a3 = ph[h] & mle, ap = pl[h] & ~mle;
#pragma unroll
                    for (int i = 0; i < 3; i++) o[h * 3 + i][0] = o[h * 3 + i][1] = o[h * 3 + i][2] = o[h * 3 + i][3] = 0.f;
                    mma16(o[h * 3 + 2], a0, a1, 0u, a3, mine ? vl[tc] : ONES, mine ? vh[tc] : ONES);
                    mma16(o[h * 3], a0, a1, 0u, a3, vl[ta], vh[ta]);
                    mma16(o[h * 3 + 1], a0, a1, 0u, a3, vl[ta + 1], vh[ta + 1]);
                    mma8(o[h * 3 + 2], ap, 0u, mine ? vp[tc] : ONES);
                    mma8(o[h * 3], ap, 0u, vp[ta]);
                    mma8(o[h * 3 + 1], ap, 0u, vp[ta + 1]);
                }
                if (hp && wg != (hg & 1)) bar_arrive(2, 256);
                const float (&oa)[4] = o[hp * 6 + 2], (&ob)[4] = o[hp * 6 + 5];
                const float hl = rcp(low ? ob[0] : oa[0]) * g0, hh = rcp(low ? ob[2] : oa[2]) * g1;
                const float gl = __shfl_xor_sync(0xffffffffu, hl, 2), gh = __shfl_xor_sync(0xffffffffu, hh, 2);
                const float ial = low ? gl : hl, iah = low ? gh : hh, ibl = low ? hl : gl, ibh = low ? hh : gh;
#pragma unroll
                for (int i = 0; i < 2; i++) {
                    ol[hp * 5 + i] = pack2(o[hp * 6 + i][0] * ial, o[hp * 6 + i][1] * ial);
                    oh[hp * 5 + i] = pack2(o[hp * 6 + i][2] * iah, o[hp * 6 + i][3] * iah);
                    ol[hp * 5 + 3 + i] = pack2(o[hp * 6 + 3 + i][0] * ibl, o[hp * 6 + 3 + i][1] * ibl);
                    oh[hp * 5 + 3 + i] = pack2(o[hp * 6 + 3 + i][2] * ibh, o[hp * 6 + 3 + i][3] * ibh);
                }
                ol[hp * 5 + 2] = pack2((low ? oa[0] : ob[0]) * gl, (low ? oa[1] : ob[1]) * gl);
                oh[hp * 5 + 2] = pack2((low ? oa[2] : ob[2]) * gh, (low ? oa[3] : ob[3]) * gh);
#pragma unroll
                for (int t = hp * 5; t < hp * 5 + 5; t++) {
                    st_relaxed4(po + t * 32, ol[t]);
                    st_relaxed4(po + 320 + t * 32, oh[t]);
                }
            }
        }
        TS(warp == 0 ? 5 : warp == 4 ? 21 : warp == 5 ? 29 : warp == 1 ? 31 : 63);
        const uint4* ow = sc + (SC_O + (hg & 1) * 640 - hg * SC_SIZE);
        if (wg != (hg & 1)) {
            mbar_wait(B_INIT, 0);
            mbar_wait(B_EMPTY + 3 * 8, 0);
            if (w4 < 2) bar_arrive(9, 256); else bar_sync(9, 256);
            if (w4 == 0) TS(wg ? 26 : 27);
            uint32_t ph = 0;
#pragma unroll 1
            for (int i = w4 + 1 + NRS; i < 8; i += 4) {
                const uint4* src = ow + src_of(i, hg) * SC_SIZE;
                const uint32_t buf = o_buf(i), chk = buf + lane * 132;
                if (i < 5 + NRS) {
                    while (__any_sync(0xffffffffu, ld_relaxed4(&src[(lane & 3) * 160 + 159].w) == SENT)) {}
                    if (w4) pace(clock(), w4 * O_DT - O_D);
                } else {
                    mbar_wait(B_OE + (i - 4) * 8, 0);
                }
                if (i == 1 + NRS) TS(wg ? 3 : 4);
                uint32_t c;
                do {
                    if (elect_one()) {
                        mbar_expect_tx(B_OT + w4 * 8, 10240);
                        bulk_load(buf, src, 10240, B_OT + w4 * 8);
                    }
                    mbar_wait(B_OT + w4 * 8, ph);
                    if (i == 1 + NRS && !ph) TS(wg ? 19 : 20);
                    ph ^= 1;
                    c = max(max(lds4(chk), lds4(chk + 4096)), lds4(chk + 6144));
                } while (__any_sync(0xffffffffu, c == SENT));
                if (lane == 0) mbar_arrive(B_G2 + i * 8);
                TS(32 + i);
            }
            return;
        }

        float oc[80];
        bar_arrive(9, 256);
        bar_sync(2, 256);
        mbar_wait(B_G2, 0);
        TS(w4 == 0 ? 6 : 63);
        wg_fence();
#pragma unroll
        for (int s = 0; s < 5; s++)
            wgmma_own(oc, ol[2 * s], oh[2 * s], ol[2 * s + 1], oh[2 * s + 1], desc_lo(wo_buf(0), 10240) + s * 128, s);
        wg_commit();
        mbar_wait(B_XS, 0);
        const int orow = p0 + wg * 64 + w4 * 16;
        const uint32_t tk1 = ~lds4(SM_KEY + 16 * 4) & 2047, tk2 = ~lds4(SM_KEY + 17 * 4) & 2047;
        const uint32_t sel1 = (tk1 & 1) == par ? (tk1 >> 1) - orow : 99, sel2 = (tk2 & 1) == par ? (tk2 >> 1) - orow : 99;
        const uint32_t n0 = pack2(1.f - g0, 1.f - g0), n1 = pack2(1.f - g1, 1.f - g1);
        const uint32_t stg = SM_OUT + w4 * 5120;
        const uint32_t m128 = keep(stg + (lane & 15) * 128 + (((lane >> 4) ^ (lane & 7)) << 4));
        const uint32_t m64 = keep(stg + 4096 + (lane & 15) * 64 + (((lane >> 4) ^ ((lane >> 1) & 3)) << 4));
        const uint32_t l128 = keep(stg + (lane >> 3) * 128 + (((lane & 7) ^ (lane >> 3)) << 4));
        const uint32_t l64 = keep(stg + 4096 + r * 64 + ((cq ^ (lane >> 3)) << 4));
        char* const o128 = reinterpret_cast<char*>(P.op) + keep(((orow + (lane >> 3)) * 2 + par) * 1280 + kba * 128 + (lane & 7) * 16);
        char* const o64 = reinterpret_cast<char*>(P.op) + keep(((orow + r) * 2 + par) * 1280 + kbr * 128 + odd * 64 + cq * 16);
        mbar_wait(B_INIT, 0);
        wg_wait<0>();
        if (leader) mbar_arrive(B_OE);
        {
            uint32_t af[NRS][20];
            uint32_t m;
            do {
#pragma unroll
                for (int i = 0; i < NRS; i++) {
                    const uint32_t* p = reinterpret_cast<const uint32_t*>(ow + src_of(i + 1, hg) * SC_SIZE + w4 * 160) + lane;
#pragma unroll
                    for (int t = 0; t < 20; t++) af[i][t] = ld_relaxed4(p + t * 32);
                }
                m = 0;
#pragma unroll
                for (int i = 0; i < NRS; i++)
#pragma unroll
                    for (int t = 0; t < 20; t++) m = max(m, af[i][t]);
            } while (__any_sync(0xffffffffu, m == SENT));
            mbar_wait(B_DF, 0);
#pragma unroll
            for (int i = 0; i < NRS; i++) {
                mbar_wait(B_G2 + 8 + i * 8, 0);
                TS(w4 == 0 ? (i ? 11 : 7) : 63);
                wg_fence();
#pragma unroll
                for (int s = 0; s < 5; s++)
                    wgmma_own(oc, af[i][2 * s], af[i][10 + 2 * s], af[i][2 * s + 1], af[i][11 + 2 * s], desc_lo(wo_buf(i + 1), 10240) + s * 128, 1);
                wg_commit();
            }
            if (NRS == 2) {
                wg_wait<1>();
                if (leader) mbar_arrive(B_OE + 8);
            }
        }
#pragma unroll 1
        for (int i = 1 + NRS; i < 8; i++) {
            const uint32_t ao = desc_lo(0, 128) + (o_buf(i) >> 4), wo = desc_lo(0, 10240) + (wo_buf(i) >> 4);
            mbar_wait(B_G2 + i * 8, 0);
            TS(w4 == 0 ? (i < 2 ? 6 + i : i < 7 ? 9 + i : 17) : 63);
            wg_fence();
#pragma unroll
            for (int s = 0; s < 5; s++) wgmma_out(oc, ao + s * 16, wo + s * 128, 1);
            wg_commit();
            if (i < 5) {
                wg_wait<1>();
                if (i > 1 && leader) mbar_arrive(B_OE - 8 + i * 8);
            }
        }
        TS(w4 == 0 ? 8 : 63);

        if (min(sel1, sel2) < 16) {
            mbar_wait(B_MOD, 0);
#pragma unroll 1
            for (int j = 0; j < 2; j++) {
                const uint32_t sel = j ? sel2 : sel1;
#pragma unroll
                for (int t = 0; t < 20; t++) {
                    const uint32_t u = lds4(SM_U + j * 320 + cq * 4 + (t < 16 ? odd * 64 + t * 16 : (odd ? 0 : 256) + (t - 16) * 16));
                    if (sel == r) nb[2 * t] = hadd2(nb[2 * t], u);
                    if (sel == r + 8) nb[2 * t + 1] = hadd2(nb[2 * t + 1], u);
                }
            }
        }
        wg_wait<0>();
        TS(w4 == 0 ? 9 : 63);
        const bool nan = oc[0] != oc[0] || oc[2] != oc[2];
#pragma unroll
        for (int part = 0; part < 3; part++) {
            const int s0 = part ? part * 4 - 4 : 8, ns = part ? 4 : 2;
#pragma unroll
            for (int i = 0; i < 4; i++) {
                if (i >= ns) break;
                const int s = s0 + i;
                const uint32_t y0 = hfma2(n0, nb[s * 4], pack2(oc[s * 8 + 0], oc[s * 8 + 1]));
                const uint32_t y1 = hfma2(n1, nb[s * 4 + 1], pack2(oc[s * 8 + 2], oc[s * 8 + 3]));
                const uint32_t y2 = hfma2(n0, nb[s * 4 + 2], pack2(oc[s * 8 + 4], oc[s * 8 + 5]));
                const uint32_t y3 = hfma2(n1, nb[s * 4 + 3], pack2(oc[s * 8 + 6], oc[s * 8 + 7]));
                asm volatile("stmatrix.sync.aligned.m8n8.x4.shared.b16 [%0], {%1,%2,%3,%4};"
                             ::"r"(((s < 8 ? m128 : m64) ^ ((s & 3) * 32)) + (s & 4) * 512), "r"(y0), "r"(y1), "r"(y2), "r"(y3) : "memory");
            }
            __syncwarp();
            uint4 v[4];
#pragma unroll
            for (int i = 0; i < 4; i++)
                if (i < ns) v[i] = lds16(!part ? l64 + i * 512 : (l128 ^ ((i & 1) * 64)) + i * 512 + s0 * 512);
#pragma unroll
            for (int i = 0; i < 4; i++)
                if (i < ns) *reinterpret_cast<uint4*>(!part ? o64 + i * 8 * 2560 : o128 + i * 4 * 2560 + s0 * 32) = v[i];
            if (part == 0) TS(w4 == 0 ? 1 : 63);
        }
        TS(w4 == 0 ? 10 : 63);
        if (lane == 0) mbar_arrive(B_DONE);
        uint32_t redo;
        asm volatile("{\n.reg .pred p, q;\nsetp.ne.u32 p, %1, 0;\nbar.cta.red.or.pred q, 10, 128, p;\nselp.u32 %0, 1, 0, q;\n}"
                     : "=r"(redo) : "r"((uint32_t)nan) : "memory");
        if (redo) {
            const int cb = hg >> 1;
#pragma unroll 1
            for (int i = 0; i < 8; i++) {
                if (leader) {
                    mbar_expect_tx(B_RE, 25600);
                    tma_3d(SM_W, &P.woa, B_RE, 0, i * 80, (cb * 5 + 1) >> 1);
                    tma_2d(SM_W + 20480, &P.wob, B_RE, cb * 160 + ((cb & 1) ? 0 : 128), i * 80);
                }
#pragma unroll 1
                for (int s = 0; s < 20; s++) {
                    const int w = w4 * 640 + s * 32 + lane;
                    uint32_t v, it = 0;
                    do {
                        v = ld_relaxed4(reinterpret_cast<const uint32_t*>(ow + i * SC_SIZE) + w);
                        if (++it > (1u << 22)) fault();
                    } while ((v >> 16) == 0xFFFFu || (v & 0xFFFFu) == 0xFFFFu);
                    sts4(SM_X + w * 4, v);
                }
                fence_async_smem();
                __syncwarp();
                bar_sync(10, 128);
                mbar_wait(B_RE, i & 1);
                wg_fence();
#pragma unroll
                for (int s = 0; s < 5; s++) wgmma_out(oc, desc_lo(SM_X, 128) + s * 16, desc_lo(SM_W, 10240) + s * 128, s || i);
                wg_commit();
                wg_wait<0>();
                bar_sync(10, 128);
            }
#pragma unroll
            for (int t = 0; t < 40; t++) {
                const int col = (t < 32 ? kba * 64 + (t >> 1) * 8 : kbr * 64 + odd * 32 + ((t - 32) >> 1) * 8) + cq * 2;
                *reinterpret_cast<uint32_t*>(P.op + ((orow + r + (t & 1) * 8) * 2 + par) * 640 + col) =
                    hfma2((t & 1) ? n1 : n0, nb[t], pack2(oc[2 * t], oc[2 * t + 1]));
            }
        }
    }
}

typedef CUresult (*EncodeFn)(CUtensorMap*, CUtensorMapDataType, cuuint32_t, void*, const cuuint64_t*, const cuuint64_t*,
                             const cuuint32_t*, const cuuint32_t*, CUtensorMapInterleave, CUtensorMapSwizzle,
                             CUtensorMapL2promotion, CUtensorMapFloatOOBfill);

void encode(EncodeFn fn, CUtensorMap* m, const void* ptr, int rank, const cuuint64_t* dims, const cuuint64_t* strides,
            const cuuint32_t* box, CUtensorMapSwizzle swz) {
    const cuuint32_t es[4] = {1, 1, 1, 1};
    fn(m, CU_TENSOR_MAP_DATA_TYPE_BFLOAT16, rank, const_cast<void*>(ptr), dims, strides, box, es,
       CU_TENSOR_MAP_INTERLEAVE_NONE, swz, CU_TENSOR_MAP_L2_PROMOTION_L2_128B, CU_TENSOR_MAP_FLOAT_OOB_FILL_NONE);
}

}

extern "C" void kernel_launch(void* const* d_in, const int* in_sizes, int n_in, void* d_out, int out_size) {
    (void)in_sizes; (void)n_in; (void)out_size;
    Params P;
    P.xp = (const __nv_bfloat16*)d_in[0];
    P.wp = (const __nv_bfloat16*)d_in[1];
    P.wop = (const __nv_bfloat16*)d_in[2];
    P.dp = (const __nv_bfloat16*)d_in[7];
    P.upp = (const __nv_bfloat16*)d_in[6];
    P.op = (__nv_bfloat16*)d_out;
    P.w_r = (const __nv_bfloat16*)d_in[4];
    P.gate_w = (const __nv_bfloat16*)d_in[8];

    void* fp = nullptr;
    cudaDriverEntryPointQueryResult st;
    cudaGetDriverEntryPoint("cuTensorMapEncodeTiled", &fp, cudaEnableDefault, &st);
    EncodeFn fn = (EncodeFn)fp;
    const cuuint64_t xd[3] = {640, 2, 1024}, xs[2] = {1280, 2560};
    const cuuint32_t bx[3] = {64, 1, 64}, bx2[3] = {64, 1, 128};
    encode(fn, &P.x2, d_in[0], 3, xd, xs, bx2, CU_TENSOR_MAP_SWIZZLE_128B);
    encode(fn, &P.x, d_in[0], 3, xd, xs, bx, CU_TENSOR_MAP_SWIZZLE_128B);
    const cuuint64_t wd[3] = {640, 640, 3}, ws[2] = {3840, 1280};
    const cuuint32_t bw[3] = {64, 32, 3}, bwr[3] = {16, 32, 3};
    encode(fn, &P.w, d_in[1], 3, wd, ws, bw, CU_TENSOR_MAP_SWIZZLE_128B);
    encode(fn, &P.wr, d_in[1], 3, wd, ws, bwr, CU_TENSOR_MAP_SWIZZLE_32B);
    const cuuint64_t ad[3] = {64, 640, 10}, as[2] = {1280, 128}, bd[2] = {640, 640};
    const cuuint32_t ba[3] = {64, 80, 2}, bb[2] = {32, 80};
    encode(fn, &P.woa, d_in[2], 3, ad, as, ba, CU_TENSOR_MAP_SWIZZLE_128B);
    encode(fn, &P.wob, d_in[2], 2, bd, as, bb, CU_TENSOR_MAP_SWIZZLE_128B);
    const cuuint64_t gd[2] = {1728, 640}, gs[1] = {3456}, dd[2] = {640, 1728};
    const cuuint32_t bg[2] = {64, 20}, bu[2] = {64, 160}, bdn[2] = {64, 16}, bxg[3] = {64, 1, 16};
    encode(fn, &P.xg, d_in[0], 3, xd, xs, bxg, CU_TENSOR_MAP_SWIZZLE_128B);
    encode(fn, &P.gate, d_in[5], 2, gd, gs, bg, CU_TENSOR_MAP_SWIZZLE_128B);
    encode(fn, &P.up, d_in[6], 2, gd, gs, bu, CU_TENSOR_MAP_SWIZZLE_128B);
    encode(fn, &P.down, d_in[7], 2, dd, as, bdn, CU_TENSOR_MAP_SWIZZLE_128B);

    cudaFuncSetAttribute(fused_kernel, cudaFuncAttributeMaxDynamicSharedMemorySize, SM_TOTAL);
    fused_kernel<<<NCTA + NEXTRA, 512, SM_TOTAL, cudaStreamPerThread>>>(P);
}
```

```cpp
#include <cuda_runtime.h>
#include <cuda_bf16.h>
#include <cuda.h>
#include <stdint.h>

namespace {

constexpr int NCTA = 128, NEXTRA = 4;
constexpr int NFFN = 108;
constexpr uint32_t SENT = 0xFFFFFFFFu;

constexpr uint32_t SB = 1024;
constexpr uint32_t SM_W = SB;
constexpr uint32_t SM_X = SB + 122880;
constexpr uint32_t SM_F = SB + 192512;
constexpr uint32_t SM_HALO = SB + 212992;
constexpr uint32_t SM_BAR = SB + 223232;
constexpr uint32_t SM_PROF = SB + 223744;
constexpr uint32_t SM_KEY = SB + 224000;
constexpr uint32_t SM_RED = SB + 224128;
constexpr uint32_t SM_XS = SB + 226688;
constexpr uint32_t SM_SENT = SB + 227328;
constexpr uint32_t SM_U = SM_RED + 1920;
constexpr uint32_t SM_H = SM_RED + 1536;
constexpr uint32_t SM_GATE = SM_RED;
constexpr uint32_t SM_TOTAL = 232448;
constexpr uint32_t SM_HALO1 = SM_X + 32768;
constexpr uint32_t SM_UP = SM_W + 61440;
constexpr uint32_t SM_OUT = SM_W + 61440;

constexpr uint32_t B_XL0 = SM_BAR, B_FULL = SM_BAR + 8, B_GT = SM_BAR + 72, B_RG = SM_BAR + 80, B_RG2 = SM_BAR + 88,
                   B_XS = SM_BAR + 96, B_EMPTY = SM_BAR + 128, B_DONE = SM_BAR + 192, B_XE = SM_BAR + 200,
                   B_GUD = SM_BAR + 224, B_OE = SM_BAR + 232, B_OT = SM_BAR + 264, B_MOD = SM_BAR + 296,
                   B_GU = SM_BAR + 104, B_UP = SM_BAR + 112, B_RS = SM_BAR + 312, B_INIT = SM_BAR + 320,
                   B_RE = SM_BAR + 328, B_G2 = SM_BAR + 336, B_DF = SM_BAR + 400;

struct Params {
    CUtensorMap x, x2, w, wr, woa, wob, xg, gate, up, down;
    __nv_bfloat16* op;
    const __nv_bfloat16 *xp, *wp, *dp, *upp, *wop, *w_r, *gate_w;
};

constexpr int SC_O = 0;
constexpr int SC_HALO = 1280;
constexpr int SC_GU = 1440;
constexpr int SC_Y = 1504;
constexpr int SC_SIZE = 1600;
__device__ __align__(128) uint4 g_sc[NCTA * SC_SIZE];
__device__ __align__(128) uint2 g_cand[NCTA];
__device__ __align__(16) uint32_t g_gate[2048];
__device__ __align__(128) unsigned g_cnt[64];
#define TS(i) do { } while (0)
#define TS2(i) do { } while (0)
#define TSX(i) do { } while (0)

__device__ __forceinline__ uint32_t smem_u32(const void* p) { return (uint32_t)__cvta_generic_to_shared(p); }
__device__ __forceinline__ void fault() { asm volatile("st.shared.u32 [%0], %0;" ::"r"(0x100001) : "memory"); }
__device__ __forceinline__ void mbar_init(uint32_t bar, uint32_t cnt) {
    asm volatile("mbarrier.init.shared::cta.b64 [%0], %1;" ::"r"(bar), "r"(cnt) : "memory");
}
__device__ __forceinline__ void mbar_expect_tx(uint32_t bar, uint32_t bytes) {
    asm volatile("mbarrier.arrive.expect_tx.shared::cta.b64 _, [%0], %1;" ::"r"(bar), "r"(bytes) : "memory");
}
__device__ __forceinline__ void mbar_arrive(uint32_t bar) {
    asm volatile("mbarrier.arrive.shared::cta.b64 _, [%0];" ::"r"(bar) : "memory");
}
__device__ __forceinline__ bool mbar_try(uint32_t bar, uint32_t parity) {
    uint32_t ok;
    asm volatile("{\n.reg .pred p;\nmbarrier.try_wait.parity.shared::cta.b64 p, [%1], %2;\nselp.u32 %0, 1, 0, p;\n}"
                 : "=r"(ok) : "r"(bar), "r"(parity) : "memory");
    return ok;
}
__device__ __forceinline__ void mbar_wait(uint32_t bar, uint32_t parity) {
    asm volatile("{\n.reg .pred p;\nAGAIN:\nmbarrier.try_wait.parity.shared::cta.b64 p, [%0], %1;\n@!p bra AGAIN;\n}"
                 ::"r"(bar), "r"(parity) : "memory");
}
__device__ __forceinline__ void tma_2d(uint32_t dst, const CUtensorMap* m, uint32_t bar, int c0, int c1) {
    asm volatile("cp.async.bulk.tensor.2d.shared::cluster.global.mbarrier::complete_tx::bytes [%0], [%1, {%3, %4}], [%2];"
                 ::"r"(dst), "l"(m), "r"(bar), "r"(c0), "r"(c1) : "memory");
}
__device__ __forceinline__ void bulk_load(uint32_t dst, const void* src, uint32_t bytes, uint32_t bar) {
    asm volatile("cp.async.bulk.shared::cluster.global.mbarrier::complete_tx::bytes [%0], [%1], %2, [%3];"
                 ::"r"(dst), "l"(src), "r"(bytes), "r"(bar) : "memory");
}
__device__ __forceinline__ void bulk_store(void* dst, uint32_t src, uint32_t bytes) {
    asm volatile("cp.async.bulk.global.shared::cta.bulk_group [%0], [%1], %2;" ::"l"(dst), "r"(src), "r"(bytes) : "memory");
}
__device__ __forceinline__ void tma_3d(uint32_t dst, const CUtensorMap* m, uint32_t bar, int c0, int c1, int c2) {
    asm volatile("cp.async.bulk.tensor.3d.shared::cluster.global.mbarrier::complete_tx::bytes [%0], [%1, {%3, %4, %5}], [%2];"
                 ::"r"(dst), "l"(m), "r"(bar), "r"(c0), "r"(c1), "r"(c2) : "memory");
}
__device__ __forceinline__ void fence_async_smem() { asm volatile("fence.proxy.async.shared::cta;" ::: "memory"); }
__device__ __forceinline__ void wg_fence() { asm volatile("wgmma.fence.sync.aligned;" ::: "memory"); }
__device__ __forceinline__ void wg_commit() { asm volatile("wgmma.commit_group.sync.aligned;" ::: "memory"); }
template <int N> __device__ __forceinline__ void wg_wait() { asm volatile("wgmma.wait_group.sync.aligned %0;" ::"n"(N) : "memory"); }
__device__ __forceinline__ void bar_sync(int id, int n) { asm volatile("bar.cta.sync %0, %1;" ::"r"(id), "r"(n) : "memory"); }
__device__ __forceinline__ void bar_arrive(int id, int n) { asm volatile("bar.cta.arrive %0, %1;" ::"r"(id), "r"(n) : "memory"); }

__device__ constexpr uint32_t desc_lo(uint32_t addr, uint32_t lbo) { return (addr >> 4) | ((lbo >> 4) << 16); }
__device__ __forceinline__ bool elect_one() {
    uint32_t p;
    asm volatile("{\n.reg .pred p;\nelect.sync _|p, 0xffffffff;\nselp.u32 %0, 1, 0, p;\n}" : "=r"(p));
    return p;
}
__device__ __forceinline__ uint32_t ld_relaxed4(const void* p) {
    uint32_t v;
    asm volatile("ld.relaxed.gpu.global.u32 %0, [%1];" : "=r"(v) : "l"(p) : "memory");
    return v;
}
__device__ __forceinline__ void st_relaxed4(void* p, uint32_t v) {
    asm volatile("st.relaxed.gpu.global.u32 [%0], %1;" ::"l"(p), "r"(v) : "memory");
}
template <int N = 1>
__device__ __forceinline__ void red_inc(unsigned* p, unsigned after) {
    asm volatile("red.relaxed.gpu.global.add.u32 [%0], %2;" ::"l"(p), "r"(after), "n"(N) : "memory");
}
__device__ __forceinline__ uint32_t lds4(uint32_t a) {
    uint32_t v;
    asm volatile("ld.shared.u32 %0, [%1];" : "=r"(v) : "r"(a) : "memory");
    return v;
}
__device__ __forceinline__ float2 lds8f(uint32_t a) {
    float2 v;
    asm volatile("ld.shared.v2.f32 {%0, %1}, [%2];" : "=f"(v.x), "=f"(v.y) : "r"(a) : "memory");
    return v;
}
__device__ __forceinline__ void sts4(uint32_t a, uint32_t v) { asm volatile("st.shared.u32 [%0], %1;" ::"r"(a), "r"(v) : "memory"); }
__device__ __forceinline__ uint32_t hmul2(uint32_t a, uint32_t b) {
    uint32_t d;
    asm("mul.rn.bf16x2 %0, %1, %2;" : "=r"(d) : "r"(a), "r"(b));
    return d;
}
__device__ __forceinline__ uint32_t hadd2(uint32_t a, uint32_t b) {
    uint32_t d;
    asm("add.rn.bf16x2 %0, %1, %2;" : "=r"(d) : "r"(a), "r"(b));
    return d;
}
__device__ __forceinline__ uint32_t hfma2(uint32_t a, uint32_t b, uint32_t c) {
    uint32_t d;
    asm("fma.rn.bf16x2 %0, %1, %2, %3;" : "=r"(d) : "r"(a), "r"(b), "r"(c));
    return d;
}
__device__ __forceinline__ uint4 ld_relaxed16(const void* p) {
    uint4 v;
    asm volatile("{\n.reg .b128 t;\n.reg .b64 lo, hi;\nld.relaxed.gpu.global.b128 t, [%4];\nmov.b128 {lo, hi}, t;\n"
                 "mov.b64 {%0, %1}, lo;\nmov.b64 {%2, %3}, hi;\n}" : "=r"(v.x), "=r"(v.y), "=r"(v.z), "=r"(v.w) : "l"(p) : "memory");
    return v;
}
__device__ __forceinline__ void st_relaxed16(void* p, uint32_t a, uint32_t b, uint32_t c, uint32_t d) {
    uint64_t lo = (uint64_t)a | ((uint64_t)b << 32), hi = (uint64_t)c | ((uint64_t)d << 32);
    asm volatile("{\n.reg .b128 t;\nmov.b128 t, {%1, %2};\nst.relaxed.gpu.global.b128 [%0], t;\n}" ::"l"(p), "l"(lo), "l"(hi) : "memory");
}
__device__ __forceinline__ void st_relaxed8(void* p, uint32_t a, uint32_t b) {
    asm volatile("{\n.reg .b64 t;\nmov.b64 t, {%1, %2};\nst.relaxed.gpu.global.b64 [%0], t;\n}" ::"l"(p), "r"(a), "r"(b) : "memory");
}
__device__ __forceinline__ uint4 ld_nc16(const void* p) {
    uint4 v;
    asm volatile("ld.global.L1::no_allocate.v4.u32 {%0, %1, %2, %3}, [%4];" : "=r"(v.x), "=r"(v.y), "=r"(v.z), "=r"(v.w) : "l"(p) : "memory");
    return v;
}
__device__ __forceinline__ uint2 ld_nc8(const void* p) {
    uint2 v;
    asm volatile("ld.global.nc.L1::no_allocate.v2.u32 {%0, %1}, [%2];" : "=r"(v.x), "=r"(v.y) : "l"(p));
    return v;
}
__device__ __forceinline__ uint4 lds16(uint32_t a) {
    uint4 v;
    asm volatile("ld.shared.v4.u32 {%0, %1, %2, %3}, [%4];" : "=r"(v.x), "=r"(v.y), "=r"(v.z), "=r"(v.w) : "r"(a) : "memory");
    return v;
}
__device__ __forceinline__ void sts16(uint32_t a, uint32_t x, uint32_t y, uint32_t z, uint32_t w) {
    asm volatile("st.shared.v4.u32 [%0], {%1, %2, %3, %4};" ::"r"(a), "r"(x), "r"(y), "r"(z), "r"(w) : "memory");
}
__device__ __forceinline__ uint32_t pack2(float lo, float hi) {
    uint32_t r;
    asm("cvt.rn.bf16x2.f32 %0, %1, %2;" : "=r"(r) : "f"(hi), "f"(lo));
    return r;
}
__device__ __forceinline__ uint32_t pack2v(float lo, float hi) {
    uint32_t r;
    asm volatile("cvt.rn.bf16x2.f32 %0, %1, %2;" : "=r"(r) : "f"(hi), "f"(lo));
    return r;
}
__device__ __forceinline__ float bf_lo(uint32_t u) { return __uint_as_float(u << 16); }
__device__ __forceinline__ float bf_hi(uint32_t u) { return __uint_as_float(u & 0xFFFF0000u); }
__device__ __forceinline__ float bf_round(float f) { return __bfloat162float(__float2bfloat16_rn(f)); }
__device__ __forceinline__ uint32_t prmt(uint32_t a, uint32_t sel) {
    uint32_t d;
    asm("prmt.b32 %0, %1, 0, %2;" : "=r"(d) : "r"(a), "r"(sel));
    return d;
}
__device__ __forceinline__ uint32_t movm(uint32_t a) {
    uint32_t d;
    asm volatile("movmatrix.sync.aligned.m8n8.trans.b16 %0, %1;" : "=r"(d) : "r"(a));
    return d;
}
__device__ __forceinline__ void mma16(float (&c)[4], uint32_t a0, uint32_t a1, uint32_t a2, uint32_t a3, uint32_t b0, uint32_t b1) {
    asm volatile("mma.sync.aligned.m16n8k16.row.col.f32.bf16.bf16.f32 {%0,%1,%2,%3}, {%4,%5,%6,%7}, {%8,%9}, {%0,%1,%2,%3};"
                 : "+f"(c[0]), "+f"(c[1]), "+f"(c[2]), "+f"(c[3]) : "r"(a0), "r"(a1), "r"(a2), "r"(a3), "r"(b0), "r"(b1));
}
__device__ __forceinline__ void mma8(float (&c)[4], uint32_t a0, uint32_t a1, uint32_t b0) {
    asm volatile("mma.sync.aligned.m16n8k8.row.col.f32.bf16.bf16.f32 {%0,%1,%2,%3}, {%4,%5}, {%6}, {%0,%1,%2,%3};"
                 : "+f"(c[0]), "+f"(c[1]), "+f"(c[2]), "+f"(c[3]) : "r"(a0), "r"(a1), "r"(b0));
}
__device__ __forceinline__ float ex2(float x) { float y; asm("ex2.approx.ftz.f32 %0, %1;" : "=f"(y) : "f"(x)); return y; }
__device__ __forceinline__ float rcp(float x) { float y; asm("rcp.approx.ftz.f32 %0, %1;" : "=f"(y) : "f"(x)); return y; }
__device__ __forceinline__ float sigmoidf(float z) { return rcp(1.0f + ex2(z * -1.4426950408889634f)); }
__device__ __forceinline__ float u2f(uint32_t u) { return __uint_as_float(u); }
__device__ __forceinline__ uint32_t f2u(float f) { return __float_as_uint(f); }

__device__ __forceinline__ void wgmma_main(float (&d)[96], uint32_t a, uint32_t b, int scale_d) {
    asm volatile("{\n.reg .pred p;\n.reg .b64 da, db;\nsetp.ne.b32 p, %98, 0;\n"
        "mov.b64 da, {%96, 0x40000040};\nmov.b64 db, {%97, 0x40000040};\n"
        "wgmma.mma_async.sync.aligned.m64n192k16.f32.bf16.bf16 "
        "{%0, %1, %2, %3, %4, %5, %6, %7, %8, %9, %10, %11, %12, %13, %14, %15, "
        "%16, %17, %18, %19, %20, %21, %22, %23, %24, %25, %26, %27, %28, %29, %30, %31, "
        "%32, %33, %34, %35, %36, %37, %38, %39, %40, %41, %42, %43, %44, %45, %46, %47, "
        "%48, %49, %50, %51, %52, %53, %54, %55, %56, %57, %58, %59, %60, %61, %62, %63, "
        "%64, %65, %66, %67, %68, %69, %70, %71, %72, %73, %74, %75, %76, %77, %78, %79, "
        "%80, %81, %82, %83, %84, %85, %86, %87, %88, %89, %90, %91, %92, %93, %94, %95}, "
        "da, db, p, 1, 1, 0, 1;\n}\n"
        : "+f"(d[0]), "+f"(d[1]), "+f"(d[2]), "+f"(d[3]), "+f"(d[4]), "+f"(d[5]), "+f"(d[6]), "+f"(d[7]),
          "+f"(d[8]), "+f"(d[9]), "+f"(d[10]), "+f"(d[11]), "+f"(d[12]), "+f"(d[13]), "+f"(d[14]), "+f"(d[15]),
          "+f"(d[16]), "+f"(d[17]), "+f"(d[18]), "+f"(d[19]), "+f"(d[20]), "+f"(d[21]), "+f"(d[22]), "+f"(d[23]),
          "+f"(d[24]), "+f"(d[25]), "+f"(d[26]), "+f"(d[27]), "+f"(d[28]), "+f"(d[29]), "+f"(d[30]), "+f"(d[31]),
          "+f"(d[32]), "+f"(d[33]), "+f"(d[34]), "+f"(d[35]), "+f"(d[36]), "+f"(d[37]), "+f"(d[38]), "+f"(d[39]),
          "+f"(d[40]), "+f"(d[41]), "+f"(d[42]), "+f"(d[43]), "+f"(d[44]), "+f"(d[45]), "+f"(d[46]), "+f"(d[47]),
          "+f"(d[48]), "+f"(d[49]), "+f"(d[50]), "+f"(d[51]), "+f"(d[52]), "+f"(d[53]), "+f"(d[54]), "+f"(d[55]),
          "+f"(d[56]), "+f"(d[57]), "+f"(d[58]), "+f"(d[59]), "+f"(d[60]), "+f"(d[61]), "+f"(d[62]), "+f"(d[63]),
          "+f"(d[64]), "+f"(d[65]), "+f"(d[66]), "+f"(d[67]), "+f"(d[68]), "+f"(d[69]), "+f"(d[70]), "+f"(d[71]),
          "+f"(d[72]), "+f"(d[73]), "+f"(d[74]), "+f"(d[75]), "+f"(d[76]), "+f"(d[77]), "+f"(d[78]), "+f"(d[79]),
          "+f"(d[80]), "+f"(d[81]), "+f"(d[82]), "+f"(d[83]), "+f"(d[84]), "+f"(d[85]), "+f"(d[86]), "+f"(d[87]),
          "+f"(d[88]), "+f"(d[89]), "+f"(d[90]), "+f"(d[91]), "+f"(d[92]), "+f"(d[93]), "+f"(d[94]), "+f"(d[95])
        : "r"(a), "r"(b), "r"(scale_d));
}

__device__ __forceinline__ void wgmma_rem(float (&d)[24], uint32_t a, uint32_t b, int scale_d) {
    asm volatile("{\n.reg .pred p;\n.reg .b64 da, db;\nsetp.ne.b32 p, %26, 0;\n"
        "mov.b64 da, {%24, 0x40000040};\nmov.b64 db, {%25, 0xC0000010};\n"
        "wgmma.mma_async.sync.aligned.m64n48k16.f32.bf16.bf16 "
        "{%0, %1, %2, %3, %4, %5, %6, %7, %8, %9, %10, %11, %12, %13, %14, %15, "
        "%16, %17, %18, %19, %20, %21, %22, %23}, "
        "da, db, p, 1, 1, 0, 1;\n}\n"
        : "+f"(d[0]), "+f"(d[1]), "+f"(d[2]), "+f"(d[3]), "+f"(d[4]), "+f"(d[5]), "+f"(d[6]), "+f"(d[7]),
          "+f"(d[8]), "+f"(d[9]), "+f"(d[10]), "+f"(d[11]), "+f"(d[12]), "+f"(d[13]), "+f"(d[14]), "+f"(d[15]),
          "+f"(d[16]), "+f"(d[17]), "+f"(d[18]), "+f"(d[19]), "+f"(d[20]), "+f"(d[21]), "+f"(d[22]), "+f"(d[23])
        : "r"(a), "r"(b), "r"(scale_d));
}

__device__ __forceinline__ void wgmma_out(float (&d)[80], uint32_t a, uint32_t b, int scale_d) {
    asm volatile("{\n.reg .pred p;\n.reg .b64 da, db;\nsetp.ne.b32 p, %82, 0;\n"
        "mov.b64 da, {%80, 0x50};\nmov.b64 db, {%81, 0x40000040};\n"
        "wgmma.mma_async.sync.aligned.m64n160k16.f32.bf16.bf16 "
        "{%0, %1, %2, %3, %4, %5, %6, %7, %8, %9, %10, %11, %12, %13, %14, %15, "
        "%16, %17, %18, %19, %20, %21, %22, %23, %24, %25, %26, %27, %28, %29, %30, %31, "
        "%32, %33, %34, %35, %36, %37, %38, %39, %40, %41, %42, %43, %44, %45, %46, %47, "
        "%48, %49, %50, %51, %52, %53, %54, %55, %56, %57, %58, %59, %60, %61, %62, %63, "
        "%64, %65, %66, %67, %68, %69, %70, %71, %72, %73, %74, %75, %76, %77, %78, %79}, "
        "da, db, p, 1, 1, 0, 1;\n}\n"
        : "+f"(d[0]), "+f"(d[1]), "+f"(d[2]), "+f"(d[3]), "+f"(d[4]), "+f"(d[5]), "+f"(d[6]), "+f"(d[7]),
          "+f"(d[8]), "+f"(d[9]), "+f"(d[10]), "+f"(d[11]), "+f"(d[12]), "+f"(d[13]), "+f"(d[14]), "+f"(d[15]),
          "+f"(d[16]), "+f"(d[17]), "+f"(d[18]), "+f"(d[19]), "+f"(d[20]), "+f"(d[21]), "+f"(d[22]), "+f"(d[23]),
          "+f"(d[24]), "+f"(d[25]), "+f"(d[26]), "+f"(d[27]), "+f"(d[28]), "+f"(d[29]), "+f"(d[30]), "+f"(d[31]),
          "+f"(d[32]), "+f"(d[33]), "+f"(d[34]), "+f"(d[35]), "+f"(d[36]), "+f"(d[37]), "+f"(d[38]), "+f"(d[39]),
          "+f"(d[40]), "+f"(d[41]), "+f"(d[42]), "+f"(d[43]), "+f"(d[44]), "+f"(d[45]), "+f"(d[46]), "+f"(d[47]),
          "+f"(d[48]), "+f"(d[49]), "+f"(d[50]), "+f"(d[51]), "+f"(d[52]), "+f"(d[53]), "+f"(d[54]), "+f"(d[55]),
          "+f"(d[56]), "+f"(d[57]), "+f"(d[58]), "+f"(d[59]), "+f"(d[60]), "+f"(d[61]), "+f"(d[62]), "+f"(d[63]),
          "+f"(d[64]), "+f"(d[65]), "+f"(d[66]), "+f"(d[67]), "+f"(d[68]), "+f"(d[69]), "+f"(d[70]), "+f"(d[71]),
          "+f"(d[72]), "+f"(d[73]), "+f"(d[74]), "+f"(d[75]), "+f"(d[76]), "+f"(d[77]), "+f"(d[78]), "+f"(d[79])
        : "r"(a), "r"(b), "r"(scale_d));
}

__device__ __forceinline__ void wgmma_own(float (&d)[80], uint32_t a0, uint32_t a1, uint32_t a2, uint32_t a3, uint32_t b, int scale_d) {
    asm volatile("{\n.reg .pred p;\n.reg .b64 db;\nsetp.ne.b32 p, %85, 0;\nmov.b64 db, {%84, 0x40000040};\n"
        "wgmma.mma_async.sync.aligned.m64n160k16.f32.bf16.bf16 "
        "{%0, %1, %2, %3, %4, %5, %6, %7, %8, %9, %10, %11, %12, %13, %14, %15, "
        "%16, %17, %18, %19, %20, %21, %22, %23, %24, %25, %26, %27, %28, %29, %30, %31, "
        "%32, %33, %34, %35, %36, %37, %38, %39, %40, %41, %42, %43, %44, %45, %46, %47, "
        "%48, %49, %50, %51, %52, %53, %54, %55, %56, %57, %58, %59, %60, %61, %62, %63, "
        "%64, %65, %66, %67, %68, %69, %70, %71, %72, %73, %74, %75, %76, %77, %78, %79}, "
        "{%80, %81, %82, %83}, db, p, 1, 1, 1;\n}\n"
        : "+f"(d[0]), "+f"(d[1]), "+f"(d[2]), "+f"(d[3]), "+f"(d[4]), "+f"(d[5]), "+f"(d[6]), "+f"(d[7]),
          "+f"(d[8]), "+f"(d[9]), "+f"(d[10]), "+f"(d[11]), "+f"(d[12]), "+f"(d[13]), "+f"(d[14]), "+f"(d[15]),
          "+f"(d[16]), "+f"(d[17]), "+f"(d[18]), "+f"(d[19]), "+f"(d[20]), "+f"(d[21]), "+f"(d[22]), "+f"(d[23]),
          "+f"(d[24]), "+f"(d[25]), "+f"(d[26]), "+f"(d[27]), "+f"(d[28]), "+f"(d[29]), "+f"(d[30]), "+f"(d[31]),
          "+f"(d[32]), "+f"(d[33]), "+f"(d[34]), "+f"(d[35]), "+f"(d[36]), "+f"(d[37]), "+f"(d[38]), "+f"(d[39]),
          "+f"(d[40]), "+f"(d[41]), "+f"(d[42]), "+f"(d[43]), "+f"(d[44]), "+f"(d[45]), "+f"(d[46]), "+f"(d[47]),
          "+f"(d[48]), "+f"(d[49]), "+f"(d[50]), "+f"(d[51]), "+f"(d[52]), "+f"(d[53]), "+f"(d[54]), "+f"(d[55]),
          "+f"(d[56]), "+f"(d[57]), "+f"(d[58]), "+f"(d[59]), "+f"(d[60]), "+f"(d[61]), "+f"(d[62]), "+f"(d[63]),
          "+f"(d[64]), "+f"(d[65]), "+f"(d[66]), "+f"(d[67]), "+f"(d[68]), "+f"(d[69]), "+f"(d[70]), "+f"(d[71]),
          "+f"(d[72]), "+f"(d[73]), "+f"(d[74]), "+f"(d[75]), "+f"(d[76]), "+f"(d[77]), "+f"(d[78]), "+f"(d[79])
        : "r"(a0), "r"(a1), "r"(a2), "r"(a3), "r"(b), "r"(scale_d));
}

#define TSA(i) do { } while (0)
#define MAP_TILE(b) (((b) & 3) | (((b) >> 5) << 2))
#define MAP_HG(b) ((((b) >> 2) & 7) ^ (((b) & 32) ? 6 : 0))
#define B_OFF 0
#define W_S0 2
#define E_V 0
#define MAPV 1
#define SKEW 4
#define PACE 500
#define PACE_W0 (-600)
#define PACE_A 250
#define PACE_B 450
#define RG_ORDER 0x24130
#define GU_T0 3600
#define GU_DT 300
#define RS_T0 9000
#define RS_DT 120
#define EXCH_FIRST 1
#define HALO_D 300
#define PF_UP 4200
#define O_D 0
#define O_DT 300
#define PF_DN 4200
#define PF_DT 450
#define GX_NS 200
#define NRS 2
#define C5_D 600
#define C6_D 100
#define PF_N 4
#define PF_0 4
#define EPF_N 15
#define EPF_M 15
#define EPF_T 900
#define RG1_T0 1700
#define RG1_DT 200
#define RW1_T 0
#define Y_T 16500
#define GL_T 0
#define DN_T0 500
#define DN_DT 68
#define DN_T1 100000
#define DN_D1 45
#define DN_R 5
#define H_T 13500
#define HS_T 13500
#define GL_N 16
#define C1_T 0
#define C0_T 0
#define RS_N 10
#define CAND_T 9000

__device__ __forceinline__ uint32_t keep(uint32_t v) { return __shfl_xor_sync(0xffffffffu, v, 0); }
__device__ __forceinline__ uint32_t ukeep(uint32_t v) { return __shfl_sync(0xffffffffu, v, 0); }
__device__ __forceinline__ void ldsm2(uint32_t* d, uint32_t a) {
    asm volatile("ldmatrix.sync.aligned.m8n8.x4.shared.b16 {%0,%1,%2,%3}, [%8];\nldmatrix.sync.aligned.m8n8.x4.shared.b16 {%4,%5,%6,%7}, [%9];"
                 : "=r"(d[0]), "=r"(d[1]), "=r"(d[2]), "=r"(d[3]), "=r"(d[4]), "=r"(d[5]), "=r"(d[6]), "=r"(d[7])
                 : "r"(a), "r"(a ^ 32) : "memory");
}
__device__ __forceinline__ void ldsm_t(uint32_t (&d)[4], uint32_t a) {
    asm volatile("ldmatrix.sync.aligned.m8n8.x4.trans.shared.b16 {%0,%1,%2,%3}, [%4];"
                 : "=r"(d[0]), "=r"(d[1]), "=r"(d[2]), "=r"(d[3]) : "r"(a) : "memory");
}
template <bool SWP, int SEG, int E>
__device__ __forceinline__ void pack_blocks(uint32_t (&d)[10], const float (&am)[96], const float (&ar)[24]) {
#pragma unroll
    for (int t = 0; t < 10; t++) {
        const float* p = (SWP ? t < 2 : t >= 8) ? ar + (SEG * 2 + (t & 1)) * 4 + E : am + (SEG * 8 + t - (SWP ? 2 : 0)) * 4 + E;
        d[t] = pack2v(p[0], p[1]);
    }
}
__device__ __forceinline__ int src_of(int i, int hg) { return i == 0 ? hg : i - (i <= hg); }

__device__ constexpr uint32_t o_buf(int i) { return ((0x99ADA3D1u >> ((i - NRS) & 3) * 8) & 255) << 10; }
__device__ constexpr uint32_t wo_buf(int i) { return SM_W + ((0x10342103u >> i * 4) & 7) * 30720; }

template <int N>
__device__ __forceinline__ void poll(uint4 (&a)[N], const uint4* p, int stride) {
    bool bad;
    do {
        bad = false;
#pragma unroll
        for (int s = 0; s < N; s++) a[s] = ld_relaxed16(p + s * stride);
#pragma unroll
        for (int s = 0; s < N; s++) bad |= a[s].w == SENT;
    } while (__any_sync(0xffffffffu, bad));
}
__device__ __forceinline__ void pace(unsigned t0, int t) {
    asm volatile("{\n.reg .pred p;\n.reg .s32 d;\nAGAIN:\nmov.u32 d, %%clock;\nsub.s32 d, d, %0;\nsetp.lt.s32 p, d, 0;\n"
                 "@p nanosleep.u32 20;\n@p bra AGAIN;\n}" ::"r"(t0 + t) : "memory");
}
__device__ __forceinline__ void l2_prefetch(const void* p) { asm volatile("prefetch.global.L2 [%0];" ::"l"(p) : "memory"); }

template <int N>
__device__ __forceinline__ bool landed(const uint4* w, int lane) {
    uint32_t a = 0;
#pragma unroll
    for (int i = 0; i < N; i++) a ^= w[i].w;
    return __ballot_sync(0xffffffffu, lane == 0 || a == 0) && lane == 0;
}
template <int N>
__device__ __forceinline__ float4 vec_mma(const uint4 (&w)[N], const uint32_t* x, uint32_t sel) {
    float c[4][4] = {};
    const uint32_t s[4] = {sel, sel >> 16, sel + ((sel & 0x10101010u) >> 3) * 17, (sel + ((sel & 0x10101010u) >> 3) * 17) >> 16};
#pragma unroll
    for (int i = 0; i < N; i++)
        mma16(c[i & 3], w[i].x, w[i].y, w[i].z, w[i].w, prmt(x[i >> 1], s[(i & 1) * 2]), prmt(x[i >> 1], s[(i & 1) * 2 + 1]));
    return make_float4((c[0][0] + c[1][0]) + (c[2][0] + c[3][0]), (c[0][1] + c[1][1]) + (c[2][1] + c[3][1]),
                       (c[0][2] + c[1][2]) + (c[2][2] + c[3][2]), (c[0][3] + c[1][3]) + (c[2][3] + c[3][3]));
}

__global__ void __launch_bounds__(512, 1) fused_kernel(const __grid_constant__ Params P) {
    extern __shared__ __align__(1024) uint8_t smem_raw[];
    const unsigned t_start = clock();
    const int tid = threadIdx.x, lane = tid & 31;
    const int warp = __shfl_sync(0xffffffffu, threadIdx.x >> 5, 0);
    const int role = blockIdx.x >= NCTA ? -1 : warp;
    const unsigned bid = blockIdx.x, e = bid & 3;
    const int tile = MAP_TILE(bid), hg = MAP_HG(bid);
    const int cid = tile * 8 + hg;
    const int par = tile & 1, p0 = (tile >> 1) * 128;
    uint4* const sc = g_sc + cid * SC_SIZE;
    const bool swp = (hg & 3) == 3;
    const int wcm = hg * 80 + (swp ? 16 : 0), wcr = hg * 80 + (swp ? 0 : 64);
    if (EPF_N && warp == 15 && lane < EPF_N) l2_prefetch(P.wp + (lane * 128 + bid) * 64);
    if (warp < 7 && elect_one()) {
#pragma unroll
        for (int i = 0; i < 4; i++) mbar_init(SM_BAR + warp * 32 + i * 8, warp < 4 ? 1 : warp < 6 ? 2 : 4);
        asm volatile("fence.mbarrier_init.release.cluster;" ::: "memory");
        if (role == 0) {
            mbar_expect_tx(B_FULL, 15360 + 8192);
            tma_3d(SM_X + 8192, &P.x, B_FULL, 0, par, p0 + 64);
            tma_3d(SM_W, &P.w, B_FULL, wcm, 0, 0);
            tma_3d(SM_W + 12288, &P.wr, B_FULL, wcr, 0, 0);
            TS(40);
            if (E_V < 2) {
                mbar_expect_tx(B_XL0, 8192);
                tma_3d(SM_X, &P.x, B_XL0, 0, par, p0);
            }
            if (W_S0 > 1 && E_V < 1) {
                mbar_expect_tx(B_FULL + 8, 15360);
                tma_3d(SM_W + 15360, &P.w, B_FULL + 8, wcm, 32, 0);
                tma_3d(SM_W + 15360 + 12288, &P.wr, B_FULL + 8, wcr, 32, 0);
            }
        }
    }
    __syncthreads();

    if (role >= 12) {
        asm volatile("setmaxnreg.dec.sync.aligned.u32 32;");
        if (warp == 12) {
            if (elect_one()) {
#pragma unroll 1
                for (int s = W_S0; s < 20; s++) {
                    const uint32_t fb = B_FULL + (s & 7) * 8, dst = SM_W + (s & 7) * 15360;
                    mbar_wait(fb + (B_EMPTY - B_FULL), ~(s >> 3) & 1);
                    pace(t_start, max(PACE_A + s * PACE_B, PACE_W0 + s * PACE));
                    mbar_expect_tx(fb, (s & 1) ? 15360 : 15360 + 16384);
                    tma_3d(dst, &P.w, fb, wcm, s * 32, 0);
                    tma_3d(dst + 12288, &P.wr, fb, wcr, s * 32, 0);
                    TS2(20 + s);
                    if (s == W_S0) TS(41);
                }
                mbar_wait(B_RG2, 0);
                if (NFFN) {
                    mbar_wait(B_EMPTY + 5 * 8, 1);
                    mbar_expect_tx(B_UP, cid < NFFN ? 20480 : 16384);
                    TS(46);
                    if (cid < NFFN) tma_2d(SM_UP, &P.up, B_UP, (cid >> 2) * 64, (cid & 3) * 160);
                    else
#pragma unroll 1
                        for (int i = 0; i < 8; i++) tma_2d(SM_UP + i * 2048, &P.down, B_UP, i * 64, cid * 32 - 2352);
                }
                const int cb = hg >> 1, ca = (cb * 5 + 1) >> 1, cr = cb * 160 + ((cb & 1) ? 0 : 128);
#pragma unroll 1
                for (int j = 0; j < 8; j++) {
                    const int i = j ^ (j == 3 || j == 4 ? 7 : 0);
                    if (j != 3) mbar_wait(j < 3 ? B_EMPTY + ((2 * j + 7) & 7) * 8 : B_GUD + (j - 4) * 8, j == 0);
                    if (j >= 5) pace(clock(), j == 5 ? C5_D : C6_D);
                    if (C1_T && j == 1) pace(t_start, C1_T);
                    if (C0_T && j == 0) pace(t_start, C0_T);
                    const uint32_t dst = wo_buf(i), gb = B_G2 + i * 8;
                    mbar_expect_tx(gb, 25600);
                    tma_3d(dst, &P.woa, gb, 0, src_of(i, hg) * 80, ca);
                    tma_2d(dst + 20480, &P.wob, gb, cr, src_of(i, hg) * 80);
                }
            }
        } else if (warp == 14) {
            if (elect_one()) {
#pragma unroll 1
                for (int kb = 1; kb < 10; kb++) {
                    const uint32_t fb = B_FULL + (kb & 3) * 16, dst = SM_X + (kb & 3) * 16384;
                    mbar_wait(fb + (B_EMPTY - B_FULL + 8), ~(kb >> 2) & 1);
                    if (kb >= 4) mbar_wait(B_XE + (kb - 4 >> 1) * 8, 0);
                    pace(t_start, max(PACE_A - PACE_B / 2 + 2 * kb * PACE_B, PACE_W0 - 50 + (2 * kb + 1) * PACE));
                    tma_3d(dst, &P.x2, fb, kb * 64, par, p0);
                }
            }
            __syncwarp();
            pace(t_start, CAND_T);
            {
                const uint32_t tag = lds4(SM_KEY + 20 * 4);
                uint4 c[2], v;
                do {
                    c[0] = ld_relaxed16(g_cand + lane * 2);
                    c[1] = ld_relaxed16(g_cand + lane * 2 + 64);
                    v = ld_relaxed16(g_gate + tile * 128 + lane * 4);
                } while (__any_sync(0xffffffffu, ((c[0].x ^ tag) | (c[0].z ^ tag) | (c[1].x ^ tag) | (c[1].z ^ tag) | (v.x ^ tag) |
                                                  (v.y ^ tag) | (v.z ^ tag) | (v.w ^ tag)) & 0xF800u));
                const uint32_t a1 = max(c[0].x, c[0].z), b1 = max(c[1].x, c[1].z), l1 = max(a1, b1);
                const uint32_t l2 = max(max(max(c[0].y, c[0].w), max(c[1].y, c[1].w)),
                                        max(max(min(c[0].x, c[0].z), min(c[1].x, c[1].z)), min(a1, b1)));
                const uint32_t k1 = __reduce_max_sync(0xffffffffu, l1);
                const uint32_t k2 = __reduce_max_sync(0xffffffffu, l1 == k1 ? l2 : l1);
                sts16(SM_GATE + lane * 16, v.x, v.y, v.z, v.w);
                __syncwarp();
                if (elect_one()) {
                    bulk_load(SM_XS, P.xp + (~k1 & 2047) * 640 + (cid & 3) * 160, 320, B_XS);
                    bulk_load(SM_XS + 320, P.xp + (~k2 & 2047) * 640 + (cid & 3) * 160, 320, B_XS);
                    sts16(SM_KEY + 16 * 4, k1, k2, 0, 0);
                    mbar_expect_tx(B_XS, 640);
                    mbar_arrive(B_GT);
                    TS(56);
                }
            }
            bar_sync(12, 64);
            pace(clock(), HALO_D);
            uint4 hv[5];
            poll<5>(hv, sc + (SC_HALO - (tile < 2 ? 0 : 16 * SC_SIZE) + lane), 32);
#pragma unroll
            for (int s = 0; s < 5; s++) sts16(SM_HALO + s * 512 + lane * 16, hv[s].x, hv[s].y, hv[s].z, hv[s].w);
            bar_arrive(8, 64);
            TS(25);
        } else if (warp == 15) {
            if (EPF_M) {
                pace(t_start, EPF_T);
                if (lane < EPF_M) l2_prefetch(P.wp + ((lane + EPF_N) * 128 + bid) * 64);
            }
#pragma unroll 1
            for (int i = PF_0; i < PF_N; i++) {
                pace(t_start, (i < 6 ? PF_UP : PF_DN) + i * PF_DT);
                const int ln = (i * 128 + cid) * 32 + lane;
                l2_prefetch((ln < 17280 ? P.upp : ln < 23680 ? P.wop - 17280 * 64 : P.dp - 23680 * 64) + ln * 64);
            }
            int it = smem_u32(smem_raw) == SB ? 0 : 1 << 20;
            while (!mbar_try(B_DONE, 0) || !mbar_try(B_MOD, 0))
                if (++it > (1 << 20)) fault();
        } else {
#pragma unroll 1
            for (int i = 0; i < 10; i++) sts16(SM_SENT + i * 512 + lane * 16, SENT, SENT, SENT, SENT);
            fence_async_smem();
            __syncwarp();
            if (elect_one()) {
                mbar_expect_tx(B_RG, 2560);
                mbar_expect_tx(B_GU, cid < NFFN ? 20480 : 24576);
                asm volatile("mbarrier.expect_tx.relaxed.cta.shared::cta.b64 [%0], 10240;" ::"r"(B_RG2) : "memory");
                pace(t_start, RW1_T);
                bulk_load(SM_RED, P.w_r, 1280, B_RG);
                bulk_load(SM_RED + 1280, P.gate_w, 1280, B_RG);
#pragma unroll 1
                for (int i = 0; i < 5; i++) {
                    pace(t_start, RG1_T0 + i * RG1_DT);
                    tma_3d(SM_HALO + i * 2048, &P.xg, B_RG2, 320 + i * 64, par, p0 + hg * 16);
                }
#pragma unroll
                for (int i = 0; i < 23; i++) mbar_init(B_GUD + i * 8, i == 22 || !i ? 4 : i < 15 + NRS ? 1 : 2);
                bulk_store(sc + SC_HALO, SM_SENT, 5120);
                asm volatile("cp.async.bulk.commit_group;\ncp.async.bulk.wait_group 0;" ::: "memory");
                mbar_arrive(B_RG2);
                TS(43);
                const unsigned goal = (ld_relaxed4(g_cnt + 32) | (NCTA - 1)) + 1;
#pragma unroll 1
                for (int i = 0; i < (!NFFN ? 0 : cid < NFFN ? 8 : 12); i++) {
                    pace(t_start, GU_T0 + i * GU_DT);
                    if (cid < NFFN) tma_2d(SM_F + i * 2560, &P.gate, B_GU, (cid >> 2) * 64, (cid & 3) * 160 + i * 20);
                    else tma_2d(SM_F - 4096 + i * 2048, &P.down, B_GU, min(i, 4 + (i >> 1)) * 64, cid * 32 - 2368 + (i > 8 ? (i & 1) * 16 : 0));
                }
#pragma unroll 1
                for (int i = 0; i < RS_N; i++) {
                    pace(t_start, RS_T0 + i * RS_DT);
                    bulk_store(sc + i * (1280 / RS_N), SM_SENT, 20480 / RS_N);
                }
                asm volatile("cp.async.bulk.commit_group;\ncp.async.bulk.wait_group 0;" ::: "memory");
                red_inc(g_cnt + 32, goal);
                mbar_arrive(B_RS);
                TS(44);
                while (ld_relaxed4(g_cnt + 32) - goal > 0x80000000u) {}
                mbar_arrive(B_INIT);
                TS(45);
            }
        }
    } else if (role >= 8) {
        asm volatile("setmaxnreg.dec.sync.aligned.u32 96;");
        const int t = tid - 256;
        uint32_t tag = ld_relaxed4(g_cnt);
        float gv = 0.f;
        int grow = hg * 16 + (t >> 3);
        mbar_wait(B_RG, 0);
        TS(warp == 8 ? 48 : 63);
        {
            float r0 = 0.f, r1 = 0.f, g0 = 0.f, g1 = 0.f;
            const uint32_t sw = (t >> 4) * 128 + (((t ^ (t >> 4)) & 7) << 4), hi = (t >> 3) & 1;
            mbar_wait(B_XL0, 0);
            tag = (tag * 8 + 2048) & 0xF800u;
            sts4(SM_KEY + 20 * 4, tag);
#pragma unroll 1
            for (int i = 0; i < 5; i++) {
                const int p = (RG_ORDER >> (i * 4)) & 7, kb = 2 * p + hi;
                mbar_wait(p < 3 ? B_FULL + (p & 1) * 32 : B_RG2, p == 2);
                if (p < 2) mbar_wait(B_FULL + p * 32 + 16, 0);
                const uint32_t xa = sw + (kb < 5 ? SM_X + (kb & 3) * 16384 + hg * 2048 : SM_HALO - 5 * 2048 + kb * 2048);
                const uint4 a = lds16(xa), b = lds16(xa + 1024);
                const uint4 w = lds16(SM_RED + p * 256 + (t & 15) * 16), v = lds16(SM_RED + 1280 + p * 256 + (t & 15) * 16);
                if (__ballot_sync(0xffffffffu, lane == 0 || a.w == b.w) && lane == 0 && p < 3) mbar_arrive(B_XE + p * 8);
                const uint32_t as[4] = {a.x, a.y, a.z, a.w}, bs[4] = {b.x, b.y, b.z, b.w};
                const uint32_t ws[4] = {w.x, w.y, w.z, w.w}, vs[4] = {v.x, v.y, v.z, v.w};
#pragma unroll
                for (int e = 0; e < 4; e++) {
                    r0 = fmaf(bf_lo(as[e]), bf_lo(ws[e]), r0);
                    r1 = fmaf(bf_lo(bs[e]), bf_lo(ws[e]), r1);
                    g0 = fmaf(bf_lo(as[e]), bf_lo(vs[e]), g0);
                    g1 = fmaf(bf_lo(bs[e]), bf_lo(vs[e]), g1);
                    r0 = fmaf(bf_hi(as[e]), bf_hi(ws[e]), r0);
                    r1 = fmaf(bf_hi(bs[e]), bf_hi(ws[e]), r1);
                    g0 = fmaf(bf_hi(as[e]), bf_hi(vs[e]), g0);
                    g1 = fmaf(bf_hi(bs[e]), bf_hi(vs[e]), g1);
                }
            }
            const bool up = lane & 4;
            r0 = (hi ? r1 : r0) + __shfl_xor_sync(0xffffffffu, hi ? r0 : r1, 8);
            g0 = (hi ? g1 : g0) + __shfl_xor_sync(0xffffffffu, hi ? g0 : g1, 8);
            float r = (up ? g0 : r0) + __shfl_xor_sync(0xffffffffu, up ? r0 : g0, 4);
            r += __shfl_xor_sync(0xffffffffu, r, 2);
            r = bf_round(r + __shfl_xor_sync(0xffffffffu, r, 1));
            const int row = hg * 16 + (t >> 4) + hi * 8;
            const uint32_t u = f2u(r);
            if (!up) sts4(SM_KEY + (t >> 3) * 4, (((int)u < 0 ? ~u : u | 0x80000000u) & 0xFFFF0000u) | (2047 - (p0 + row) * 2 - par));
            gv = r;
            grow = row;
        }
        TS(warp == 8 ? 61 : 63);
        mbar_wait(B_RG2, 0);
        bar_sync(4, 128);
        if (warp == 8) {
            const uint32_t key = lds4(SM_KEY + (lane & 15) * 4);
            uint32_t k1 = __reduce_max_sync(0xffffffffu, key);
            uint32_t k2 = __reduce_max_sync(0xffffffffu, key == k1 ? 0u : key);
            if (elect_one()) {
                st_relaxed8(g_cand + cid, k1 | tag, k2 | tag);
                red_inc<MAPV == 3 ? 2 : 1>(g_cnt, tag);
            }
            TS(49);
        }
        if ((lane & 7) == 4) st_relaxed4(g_gate + tile * 128 + grow, f2u(bf_round(sigmoidf(gv))) | tag);
        const int cq = lane & 3, w4 = warp & 3;
        const uint32_t la = keep(cq * 256 + (((lane >> 2) ^ cq * 2) << 4));
        const uint32_t sel = keep(0x44444444u ^ (0x54u << (lane >> 2 & 1) * 8 + (lane & 16)));
        if (NFFN) {
            float4 d;
            uint4* dst;
            if (cid < NFFN) {
                uint4 wv[20];
                const uint32_t wa = (w4 < 2 ? SM_F : SM_UP) + (w4 & 1) * 10240;
                mbar_wait(B_GU + (w4 & 2) * 4, 0);
                TS(warp == 10 ? 58 : 63);
                if (GL_T) pace(t_start, GL_T);
#pragma unroll
                for (int i = 0; i < GL_N; i++) wv[i] = lds16((la ^ (i & 1) * 144) + wa + (i >> 1) * 1024);
                TS(warp == 8 ? 42 : warp == 10 ? 53 : 63);
                mbar_wait(B_XS, 0);
                TS(warp == 8 ? 50 : 63);
                uint32_t xv[12];
#pragma unroll
                for (int i = 0; i < 3; i++)
                    asm volatile("ldmatrix.sync.aligned.m8n8.x4.shared.b16 {%0,%1,%2,%3}, [%4];"
                                 : "=r"(xv[4 * i]), "=r"(xv[4 * i + 1]), "=r"(xv[4 * i + 2]), "=r"(xv[4 * i + 3])
                                 : "r"(SM_XS + (lane & 2) * 160 + (w4 & 1) * 160 + (lane >> 3) * 16 + i * 64) : "memory");
#pragma unroll
                for (int i = GL_N; i < 20; i++) wv[i] = lds16((la ^ (i & 1) * 144) + wa + (i >> 1) * 1024);
                d = vec_mma<20>(wv, xv, sel);
                if (lane == 0 && f2u(d.x) != SENT) mbar_arrive(B_GUD);
                TS(warp == 8 ? 54 : warp == 10 ? 59 : 63);
                dst = sc + SC_GU + w4 * 16 + lane;
            } else {
                uint4 wv[2][8], wr[4];
                mbar_wait(B_UP, 0);
#pragma unroll
                for (int i = 0; i < 8; i++) wv[i >> 2][4 + (i & 3)] = lds16((la ^ (i & 1) * 144) + SM_UP + w4 * 4096 + (i >> 1) * 1024);
                if (landed<4>(wv[0] + 4, lane) & landed<4>(wv[1] + 4, lane)) mbar_arrive(B_GUD);
                mbar_wait(B_GU, 0);
#pragma unroll
                for (int i = 0; i < 4; i++) wr[i] = lds16((la ^ (i & 1) * 144) + SM_F + 12288 + w4 * 2048 + (i >> 1) * 1024);
                mbar_wait(B_XS, 0);
                if (w4 < 2) {
                    uint4 pq[2];
                    pace(t_start, HS_T);
                    poll<2>(pq, g_sc + ((cid >> 1) * 4 - 148 + cq) * SC_SIZE + SC_GU + (cid & 1) * 16 + (t >> 2), 32);
                    TS(warp == 8 ? 55 : 63);
                    const bool b1 = cq & 2, b0 = cq & 1;
                    float v[4];
#pragma unroll
                    for (int m = 0; m < 2; m++) {
                        v[2 * m] = u2f(b1 ? pq[m].z : pq[m].x) + __shfl_xor_sync(0xffffffffu, u2f(b1 ? pq[m].x : pq[m].z), 2);
                        v[2 * m + 1] = u2f(b1 ? pq[m].w : pq[m].y) + __shfl_xor_sync(0xffffffffu, u2f(b1 ? pq[m].y : pq[m].w), 2);
                        v[m] = bf_round((b0 ? v[2 * m + 1] : v[2 * m]) + __shfl_xor_sync(0xffffffffu, b0 ? v[2 * m] : v[2 * m + 1], 1));
                    }
                    const uint32_t h = pack2(bf_round(v[0] * sigmoidf(v[0])) * v[1], 0.f);
                    asm volatile("st.shared.u16 [%0], %1;" ::"r"(SM_H + (t & 4) * 16 + (t & 8) * 4 + (t & 2) * 8 + (t >> 4) * 4 + (t & 1) * 2),
                                 "h"((uint16_t)h) : "memory");
                }
                bar_sync(4, 128);
                TS(warp == 8 ? 57 : 63);
                const uint4 h = lds16(SM_H + (lane & 8) * 8 + cq * 16);
                const uint32_t hv[4] = {h.x, h.y, h.z, h.w}, hr[2] = {(w4 & 1) ? h.z : h.x, (w4 & 1) ? h.w : h.y};
                d = vec_mma<4>(wr, hr, sel);
                dst = g_sc + (cid * 5 - 520 + w4) * SC_SIZE + SC_Y + (lane & 1) * 32 + (lane >> 1);
                float c[2][2][4] = {};
                const uint32_t s2 = sel + ((sel & 0x10101010u) >> 3) * 17;
#pragma unroll
                for (int i = 7; i >= 0; i--) {
                    const uint32_t x0 = prmt(hv[i >> 1], (i & 1) ? s2 : sel), x1 = prmt(hv[i >> 1], ((i & 1) ? s2 : sel) >> 16);
#pragma unroll
                    for (int n = 0; n < 2; n++) {
                        if (i >= 4) wv[n][i - 4] = lds16((la ^ (i & 1) * 144) + SM_F - 6144 + w4 * 4096 + n * 2048 + (i >> 1) * 1024);
                        mma16(c[n][i & 1], wv[n][i].x, wv[n][i].y, wv[n][i].z, wv[n][i].w, x0, x1);
                    }
                }
#pragma unroll
                for (int n = 0; n < 2; n++)
                    st_relaxed16(dst + n * 16, f2u(c[n][0][0] + c[n][1][0]), f2u(c[n][0][1] + c[n][1][1]), f2u(c[n][0][2] + c[n][1][2]),
                                 f2u(c[n][0][3] + c[n][1][3]));
                dst += (4 - w4) * SC_SIZE + w4 * 8;
                TS(warp == 8 ? 30 : 63);
            }
            if (lane == 0 && f2u(d.x) != SENT) mbar_arrive(B_DF);
            if (w4 & 1) {
                sts16(SM_RED + 512 + (w4 & 2) * 256 + lane * 16, f2u(d.x), f2u(d.y), f2u(d.z), f2u(d.w));
                bar_arrive(13 + (w4 >> 1), 64);
            } else {
                bar_sync(13 + (w4 >> 1), 64);
                const uint4 o = lds16(SM_RED + 512 + (w4 & 2) * 256 + lane * 16);
                st_relaxed16(dst, f2u(d.x + u2f(o.x)), f2u(d.y + u2f(o.y)), f2u(d.z + u2f(o.z)), f2u(d.w + u2f(o.w)));
            }
        } else {
            if (t < 4) mbar_arrive(B_GUD);
            if (t < 4) mbar_arrive(B_DF);
            mbar_wait(B_XS, 0);
        }
        TS(warp == 8 ? 51 : 63);
        const uint32_t k1 = lds4(SM_KEY + 16 * 4), k2 = lds4(SM_KEY + 17 * 4);
        const uint32_t mine = (tile >> 1) * 256 + (hg & 1) * 128 + par;
        const bool own1 = (~k1 & 0x781) == mine, own2 = (~k2 & 0x781) == mine;
        if ((own1 || own2) && NFFN) {
            const int rg = min(t / 40, 2), un = (hg >> 1) * 40 + t % 40;
            mbar_wait(B_RS, 0);
            pace(t_start, Y_T);
            TS(warp == 8 ? 60 : 63);
#pragma unroll 1
            for (int j = !own1; j <= own2; j++) {
                const uint4* p = g_sc + (rg * 5 + (un >> 5)) * SC_SIZE + SC_Y + j * 32 + (un & 31);
                float y[4];
                bool bad;
                do {
                    uint4 yp[8];
#pragma unroll
                    for (int i = 0; i < 8; i++) yp[i] = ld_relaxed16(p + i * 15 * SC_SIZE);
                    y[0] = y[1] = y[2] = y[3] = 0.f;
                    bad = false;
#pragma unroll
                    for (int i = 0; i < 8; i++) {
                        y[0] += u2f(yp[i].x); y[1] += u2f(yp[i].y); y[2] += u2f(yp[i].z); y[3] += u2f(yp[i].w);
                        bad |= yp[i].w == SENT;
                    }
                } while (__any_sync(0xffffffffu, bad));
                TS(warp == 8 ? 62 : 63);
                sts16(SM_SENT + j * 2048 + t * 16, f2u(y[0]), f2u(y[1]), f2u(y[2]), f2u(y[3]));
                bar_sync(4, 128);
                if (t < 80) {
                    const uint32_t key = j ? k2 : k1, ya = SM_SENT + j * 2048 + t * 8;
                    const float rs = bf_round(sigmoidf(u2f(((int)key < 0 ? key & 0x7FFFFFFFu : ~key) & 0xFFFF0000u)));
                    const float2 y0 = lds8f(ya), y1 = lds8f(ya + 640), y2 = lds8f(ya + 1280);
                    sts4(SM_U + j * 320 + t * 4, pack2(bf_round(y0.x + y1.x + y2.x) * rs, bf_round(y0.y + y1.y + y2.y) * rs));
                }
            }
            bar_sync(4, 128);
        }
        if (t == 0) mbar_arrive(B_MOD);
        TS(warp == 8 ? 52 : 63);
    } else if (role < 0) {
        const int half = warp >> 3;
        if (!NFFN) {
            if (tid == 0) red_inc<NCTA / NEXTRA>(g_cnt, 0);
            return;
        }
        uint32_t wf[DN_R][5][4], la[5];
        auto rows = [&](uint32_t l) {
#pragma unroll
            for (int i = 0; i < 5; i++) {
                const uint32_t c = (warp & 7) * 10 + 2 * i + (l >> 3 & 1);
                la[i] = SB + half * 20480 + (c >> 3) * 2048 + (l & 7) * 128 + (l >> 4) * 1024 + (((c ^ l) & 7) << 4);
            }
        };
        rows(lane);
        auto fetch = [&](int j, int n, uint32_t bar) {
#pragma unroll 1
            for (int h = 0; h < n; h++) {
                pace(t_start, min(DN_T0 + (j * 20 + h * 10 + warp) * DN_DT, DN_T1 + (j * 20 + h * 10 + warp) * DN_D1));
                tma_2d(SB + (j % 5) * 40960 + h * 20480 + warp * 2048, &P.down, bar, warp * 64, e * 272 + (j + h * 9) * 16);
            }
        };
        if (warp < 10 && elect_one()) {
            if (warp <= DN_R) mbar_expect_tx(B_FULL + warp * 8, warp < DN_R ? 40960 : (17 - 2 * DN_R) * 20480);
#pragma unroll 1
            for (int j = 0; j < 5; j++) fetch(j, 2, B_FULL + j * 8);
        }
        const uint32_t tag = (ukeep(ld_relaxed4(g_cnt)) * 8 + 2048) & 0xF800u;
#pragma unroll
        for (int j = 0; j < DN_R; j++) {
            uint32_t any = 0;
            mbar_wait(B_FULL + j * 8, 0);
#pragma unroll
            for (int i = 0; i < 5; i++) {
                ldsm_t(wf[j][i], la[i] + j * 40960);
                any ^= wf[j][i][3];
            }
            if (j < 4) {
                if (__syncthreads_count(any == 0) == 1000) fault();
                if (warp < 10 && elect_one()) fetch(j + 5, j < 3 ? 2 : 1, B_FULL + DN_R * 8);
                if (j == 0 && tid == 0) red_inc<NCTA / NEXTRA>(g_cnt, tag);
            }
            TSX(warp == 0 && j == 0 ? 0 : warp == 0 && j == 3 ? 1 : 63);
        }
        if (warp < 9) {
            pace(t_start, H_T - 1000);
            uint4 a[4];
            do {
                a[0] = ld_relaxed16(g_cand + lane * 2);
                a[1] = ld_relaxed16(g_cand + lane * 2 + 64);
            } while (__any_sync(0xffffffffu, ((a[0].x ^ tag) | (a[0].z ^ tag) | (a[1].x ^ tag) | (a[1].z ^ tag)) & 0xF800u));
            const int u = min(tid, 271), wq = e * 136 + (u >> 1);
            const uint4* const p = g_sc + ((wq >> 5) * 4 + (u & 1) * 2) * SC_SIZE + SC_GU + (wq & 31);
            pace(t_start, H_T);
            TSX(warp == 0 ? 3 : 63);
            do {
#pragma unroll
                for (int i = 0; i < 4; i++) a[i] = ld_relaxed16(p + (i & 1) * SC_SIZE + (i >> 1) * 32);
            } while (__any_sync(0xffffffffu, max(max(a[0].w, a[1].w), max(a[2].w, a[3].w)) == SENT));
            TSX(warp == 0 ? 4 : warp == 8 ? 5 : 63);
            float v[4];
#pragma unroll
            for (int m = 0; m < 2; m++) {
                const float x = u2f(a[2 * m].x) + u2f(a[2 * m + 1].x), y = u2f(a[2 * m].y) + u2f(a[2 * m + 1].y);
                const float z = u2f(a[2 * m].z) + u2f(a[2 * m + 1].z), w = u2f(a[2 * m].w) + u2f(a[2 * m + 1].w);
                v[2 * m] = bf_round(((u & 1) ? z : x) + __shfl_xor_sync(0xffffffffu, (u & 1) ? x : z, 1));
                v[2 * m + 1] = bf_round(((u & 1) ? w : y) + __shfl_xor_sync(0xffffffffu, (u & 1) ? y : w, 1));
            }
            if (tid < 272)
                sts4(SM_RED + (u >> 4) * 64 + (u & 2) * 16 + (u & 4) * 4 + (u & 1) * 8 + (u & 8) / 2,
                     pack2(bf_round(v[0] * sigmoidf(v[0])) * v[2], bf_round(v[1] * sigmoidf(v[1])) * v[3]));
        }
        rows(keep(lane));
        mbar_wait(B_FULL + DN_R * 8, 0);
        TSX(warp == 15 ? 2 : 63);
        __syncthreads();
        float c[5][4] = {};
#pragma unroll
        for (int j = 0; j < 9; j++) {
            if (j == 8 && half) break;
            const float2 b = lds8f(SM_RED + half * 576 + j * 64 + (lane & 7) * 8);
            if (j == 1) TSX(warp == 0 ? 6 : 63);
#pragma unroll
            for (int i = 0; i < 5; i++) {
                if (j >= DN_R) ldsm_t(wf[j % DN_R][i], la[i] + (j % 5) * 40960);
                mma16(c[i], wf[j % DN_R][i][0], wf[j % DN_R][i][1], wf[j % DN_R][i][2], wf[j % DN_R][i][3], f2u(b.x), f2u(b.y));
            }
        }
        const uint32_t ra = SB + 7 * 20480 + half * 5248 + (lane & 1) * 2624 + (warp & 7) * 320 + (lane & 2) * 16 + (lane >> 2) * 4;
#pragma unroll
        for (int i = 0; i < 5; i++) sts4(ra + i * 64, f2u((lane & 2) ? ((lane & 1) ? c[i][3] : c[i][2]) : ((lane & 1) ? c[i][1] : c[i][0])));
        TSX(warp == 0 ? 7 : 63);
        __syncthreads();
        if (warp < 10) {
            const uint32_t ya = SB + 7 * 20480 + (warp & 1) * 2624 + (warp >> 1) * 512 + lane * 16;
            const uint4 y0 = lds16(ya), y1 = lds16(ya + 5248);
            st_relaxed16(g_sc + (e * 5 + (warp >> 1)) * SC_SIZE + SC_Y + (tid & 63), f2u(u2f(y0.x) + u2f(y1.x)), f2u(u2f(y0.y) + u2f(y1.y)),
                         f2u(u2f(y0.z) + u2f(y1.z)), f2u(u2f(y0.w) + u2f(y1.w)));
        }
    } else {
        if (E_V && warp == 0 && elect_one()) {
            if (E_V == 2) {
                mbar_expect_tx(B_XL0, 8192);
                tma_3d(SM_X, &P.x, B_XL0, 0, par, p0);
            }
            if (W_S0 > 1) {
                mbar_expect_tx(B_FULL + 8, 15360);
                tma_3d(SM_W + 15360, &P.w, B_FULL + 8, wcm, 32, 0);
                tma_3d(SM_W + 15360 + 12288, &P.wr, B_FULL + 8, wcr, 32, 0);
            }
            if (E_V == 3) {
                mbar_expect_tx(B_XL0, 8192);
                tma_3d(SM_X, &P.x, B_XL0, 0, par, p0);
            }
        }
        asm volatile("setmaxnreg.inc.sync.aligned.u32 192;");
        const int wg = warp >> 2;
        const bool leader = (tid & 127) == 0;
        float am[96], ar[24];
        if (wg == 0) mbar_wait(B_XL0, 0);
        bool rel = false;
        uint32_t nb[40];
        const int odd = (hg >> 1) & 1, kba = ukeep(((hg >> 1) * 5 + 1) >> 1), kbr = ukeep(kba + 2 - odd * 3);
        const int kbs = wg ? -1 : (20 - SKEW) / 2;
        const uint32_t xrow = keep(SM_X + (warp * 16 + (lane & 15)) * 128 + (((lane >> 4) ^ (lane & 7)) << 4));
#pragma unroll 1
        for (int kb = 0; kb < 10; kb++) {
            const uint32_t fb = B_FULL + (kb & 3) * 16, wo = (kb & 3) * 1920, ph = (kb >> 2) & 1;
            const uint32_t xo = desc_lo(SM_X, 16) + wg * 512 + (kb & 3) * 1024;
#pragma unroll
            for (int h = 0; h < 2; h++) {
                mbar_wait(fb + h * 8, ph);
                if (kb == 0 && h == 0) TS(warp == 0 ? 0 : warp == 4 ? 16 : 63);
                TS2(warp == 4 ? kb * 2 + h : 63);
                if (h == 0) {
                    const uint32_t xa = xrow + (kb & 3) * 16384;
                    if (kb == kba) { ldsm2(nb, xa); ldsm2(nb + 8, xa ^ 64); }
                    if (kb == kba + 1) { ldsm2(nb + 16, xa); ldsm2(nb + 24, xa ^ 64); }
                    if (kb == kbr) ldsm2(nb + 32, xa ^ (odd * 64));
                }
                wg_wait<1>();
                if (rel && (h == 0 || kb != kbs)) mbar_arrive(B_EMPTY + ((kb * 16 - 16) & 48) + h * 8);
                if (h == 0 && kb == kbs) {
                    wg_wait<0>();
                    if (rel) mbar_arrive(B_EMPTY + ((19 - SKEW) & 7) * 8);
                    bar_sync(5, 256);
                }
                wg_fence();
                wgmma_main(am, xo + h * 4, desc_lo(SM_W + h * 15360, 4096) + wo, h || kb);
                wgmma_rem(ar, xo + h * 4, desc_lo(SM_W + h * 15360 + 12288, 1024) + wo, h || kb);
                wgmma_main(am, xo + h * 4 + 2, desc_lo(SM_W + h * 15360 + 2048, 4096) + wo, 1);
                wgmma_rem(ar, xo + h * 4 + 2, desc_lo(SM_W + h * 15360 + 12288 + 512, 1024) + wo, 1);
                wg_commit();
            }
            rel = leader;
        }
        if (wg == 1) bar_arrive(5, 256);
        mbar_wait(B_XE + 16, 0);
        mbar_wait(B_RG2, 0);
        mbar_wait(B_EMPTY + 5 * 8, 1);
        wg_wait<0>();
        if (leader) mbar_arrive(B_EMPTY + 3 * 8);
        TS(warp == 0 ? 2 : warp == 4 ? 18 : 63);
        TS2(warp == 0 ? 41 : warp == 4 ? 40 : 63);

        uint32_t kl[10], kh[10], vl[10], vh[10], ql[10], qh[10], kp[10], vp[10];
        if (swp) {
            pack_blocks<true, 1, 2>(kh, am, ar);
            pack_blocks<true, 2, 2>(vh, am, ar);
        } else {
            pack_blocks<false, 1, 2>(kh, am, ar);
            pack_blocks<false, 2, 2>(vh, am, ar);
        }
        const int w4 = warp & 3;
        const uint32_t pbuf = (wg ? SM_HALO1 : SM_HALO) + w4 * 2560 + lane * 16;
        const uint32_t hbuf = warp == 3 ? SM_HALO1 + lane * 16 : pbuf + 2560;
        {
            const uint32_t ex[20] = {kh[0], kh[1], kh[3], kh[4], kh[5], kh[6], kh[8], kh[9], kh[2], kh[7],
                                     vh[0], vh[1], vh[2], vh[3], vh[4], vh[5], vh[6], vh[7], vh[8], vh[9]};
            if (warp == 7) {
                uint4* const hp = sc + SC_HALO + lane;
#pragma unroll
                for (int s = 0; s < 5; s++) st_relaxed16(hp + s * 32, ex[4 * s], ex[4 * s + 1], ex[4 * s + 2], ex[4 * s + 3]);
                bar_arrive(12, 64);
            } else {
#pragma unroll
                for (int s = 0; s < 5; s++) sts16(hbuf + s * 512, ex[4 * s], ex[4 * s + 1], ex[4 * s + 2], ex[4 * s + 3]);
            }
        }
        TSA(warp == 7 ? 22 : warp == 3 ? 23 : 63);
        if (warp == 3) bar_arrive(11, 64);
        if (swp) {
            pack_blocks<true, 2, 0>(vl, am, ar);
            pack_blocks<true, 0, 0>(ql, am, ar);
            pack_blocks<true, 0, 2>(qh, am, ar);
            pack_blocks<true, 1, 0>(kl, am, ar);
        } else {
            pack_blocks<false, 2, 0>(vl, am, ar);
            pack_blocks<false, 0, 0>(ql, am, ar);
            pack_blocks<false, 0, 2>(qh, am, ar);
            pack_blocks<false, 1, 0>(kl, am, ar);
        }
#pragma unroll
        for (int t = 0; t < 10; t++) { vl[t] = movm(vl[t]); vh[t] = movm(vh[t]); }
        mbar_wait(B_RS, 0);
        mbar_wait(B_GT, 0);
        const float g0 = bf_hi(lds4(SM_GATE + warp * 64 + (lane & 28))), g1 = bf_hi(lds4(SM_GATE + 32 + warp * 64 + (lane & 28)));

        const int r = lane >> 2, cq = lane & 3;
        const bool no_prev = warp == 0 && tile < 2, low = cq < 2;
        const bool le0 = 2 * cq <= r, le1 = 2 * cq + 1 <= r;
        const uint32_t mle = (le0 ? 0xFFFFu : 0u) | (le1 ? 0xFFFF0000u : 0u);
        const float scl = 0.22360679774997896f * 1.4426950408889634f;
        uint32_t pl[4], ph[4];
        {
            float sl[4][4], sh[4][4], sp[4][4];
            auto exchange = [&]() {
            TSA(warp == 1 ? 26 : 63);
            bar_sync(6 + wg, 128);
            if (w4 == 0) bar_sync(8 + wg * 3, 64);
            {
                const uint4 a = lds16(pbuf), b = lds16(pbuf + 512), c = lds16(pbuf + 1024), d = lds16(pbuf + 1536), e = lds16(pbuf + 2048);
                kp[0] = a.x; kp[1] = a.y; kp[3] = a.z; kp[4] = a.w; kp[5] = b.x; kp[6] = b.y; kp[8] = b.z; kp[9] = b.w;
                kp[2] = c.x; kp[7] = c.y; vp[0] = c.z; vp[1] = c.w; vp[2] = d.x; vp[3] = d.y; vp[4] = d.z; vp[5] = d.w;
                vp[6] = e.x; vp[7] = e.y; vp[8] = e.z; vp[9] = e.w;
            }
            TSA(warp == 0 ? 3 : warp == 4 ? 19 : warp == 5 ? 27 : 63);
            };
            if (EXCH_FIRST) exchange();
#pragma unroll
            for (int h = 0; h < 4; h++) {
                const int ta = (h >> 1) * 5 + (h & 1) * 3, tc = (h >> 1) * 5 + 2;
                const uint32_t ml = low != (h & 1) ? ql[tc] : 0u, mh = low != (h & 1) ? qh[tc] : 0u;
#pragma unroll
                for (int e = 0; e < 4; e++) sl[h][e] = sh[h][e] = sp[h][e] = 0.f;
                mma16(sl[h], ql[ta], qh[ta], ql[ta + 1], qh[ta + 1], kl[ta], kl[ta + 1]);
                mma16(sh[h], ql[ta], qh[ta], ql[ta + 1], qh[ta + 1], kh[ta], kh[ta + 1]);
                mma8(sl[h], ml, mh, kl[tc]);
                mma8(sh[h], ml, mh, kh[tc]);
            }
            if (!EXCH_FIRST) exchange();
#pragma unroll
            for (int h = 0; h < 4; h++) {
                const int ta = (h >> 1) * 5 + (h & 1) * 3, tc = (h >> 1) * 5 + 2;
                mma16(sp[h], ql[ta], qh[ta], ql[ta + 1], qh[ta + 1], kp[ta], kp[ta + 1]);
                mma8(sp[h], low != (h & 1) ? ql[tc] : 0u, low != (h & 1) ? qh[tc] : 0u, kp[tc]);
            }
#pragma unroll
            for (int t = 0; t < 10; t++) vp[t] = movm(vp[t]);
#pragma unroll
            for (int h = 0; h < 4; h++) {
                if (no_prev) sp[h][0] = sp[h][1] = -1e9f / 0.22360679774997896f;
                const float a0 = le0 ? sl[h][0] : sp[h][0], a1 = le1 ? sl[h][1] : sp[h][1];
                const float b0 = le0 ? sh[h][2] : sl[h][2], b1 = le1 ? sh[h][3] : sl[h][3];
                float ma = fmaxf(a0, a1), mb = fmaxf(b0, b1);
                ma = fmaxf(ma, __shfl_xor_sync(0xffffffffu, ma, 1));
                mb = fmaxf(mb, __shfl_xor_sync(0xffffffffu, mb, 1));
                ma = fmaxf(ma, __shfl_xor_sync(0xffffffffu, ma, 2)) * -scl;
                mb = fmaxf(mb, __shfl_xor_sync(0xffffffffu, mb, 2)) * -scl;
                pl[h] = pack2(ex2(fmaf(a0, scl, ma)), ex2(fmaf(a1, scl, ma)));
                ph[h] = pack2(ex2(fmaf(b0, scl, mb)), ex2(fmaf(b1, scl, mb)));
            }
        }
        TSA(warp == 0 ? 4 : warp == 4 ? 20 : warp == 5 ? 28 : 63);
        uint32_t ol[10], oh[10];
        {
            uint32_t* const po = reinterpret_cast<uint32_t*>(sc + SC_O + warp * 160) + lane;
            const uint32_t ONES = 0x3F803F80u;
            float o[12][4];
#pragma unroll
            for (int hp = 0; hp < 2; hp++) {
#pragma unroll
                for (int h = hp * 2; h < hp * 2 + 2; h++) {
                    const int ta = (h >> 1) * 5 + (h & 1) * 3, tc = (h >> 1) * 5 + 2;
                    const bool mine = (lane < 16) != (h & 1);
                    const uint32_t a0 = pl[h] & mle, a1 = ph[h] & ~mle, a3 = ph[h] & mle, ap = pl[h] & ~mle;
#pragma unroll
                    for (int i = 0; i < 3; i++) o[h * 3 + i][0] = o[h * 3 + i][1] = o[h * 3 + i][2] = o[h * 3 + i][3] = 0.f;
                    mma16(o[h * 3 + 2], a0, a1, 0u, a3, mine ? vl[tc] : ONES, mine ? vh[tc] : ONES);
                    mma16(o[h * 3], a0, a1, 0u, a3, vl[ta], vh[ta]);
                    mma16(o[h * 3 + 1], a0, a1, 0u, a3, vl[ta + 1], vh[ta + 1]);
                    mma8(o[h * 3 + 2], ap, 0u, mine ? vp[tc] : ONES);
                    mma8(o[h * 3], ap, 0u, vp[ta]);
                    mma8(o[h * 3 + 1], ap, 0u, vp[ta + 1]);
                }
                if (hp && wg != (hg & 1)) bar_arrive(2, 256);
                const float (&oa)[4] = o[hp * 6 + 2], (&ob)[4] = o[hp * 6 + 5];
                const float hl = rcp(low ? ob[0] : oa[0]) * g0, hh = rcp(low ? ob[2] : oa[2]) * g1;
                const float gl = __shfl_xor_sync(0xffffffffu, hl, 2), gh = __shfl_xor_sync(0xffffffffu, hh, 2);
                const float ial = low ? gl : hl, iah = low ? gh : hh, ibl = low ? hl : gl, ibh = low ? hh : gh;
#pragma unroll
                for (int i = 0; i < 2; i++) {
                    ol[hp * 5 + i] = pack2(o[hp * 6 + i][0] * ial, o[hp * 6 + i][1] * ial);
                    oh[hp * 5 + i] = pack2(o[hp * 6 + i][2] * iah, o[hp * 6 + i][3] * iah);
                    ol[hp * 5 + 3 + i] = pack2(o[hp * 6 + 3 + i][0] * ibl, o[hp * 6 + 3 + i][1] * ibl);
                    oh[hp * 5 + 3 + i] = pack2(o[hp * 6 + 3 + i][2] * ibh, o[hp * 6 + 3 + i][3] * ibh);
                }
                ol[hp * 5 + 2] = pack2((low ? oa[0] : ob[0]) * gl, (low ? oa[1] : ob[1]) * gl);
                oh[hp * 5 + 2] = pack2((low ? oa[2] : ob[2]) * gh, (low ? oa[3] : ob[3]) * gh);
#pragma unroll
                for (int t = hp * 5; t < hp * 5 + 5; t++) {
                    st_relaxed4(po + t * 32, ol[t]);
                    st_relaxed4(po + 320 + t * 32, oh[t]);
                }
            }
        }
        TS(warp == 0 ? 5 : warp == 4 ? 21 : warp == 5 ? 29 : warp == 1 ? 31 : 63);
        const uint4* ow = sc + (SC_O + (hg & 1) * 640 - hg * SC_SIZE);
        if (wg != (hg & 1)) {
            mbar_wait(B_INIT, 0);
            mbar_wait(B_EMPTY + 3 * 8, 0);
            if (w4 < 2) bar_arrive(9, 256); else bar_sync(9, 256);
            if (w4 == 0) TS(wg ? 26 : 27);
            uint32_t ph = 0;
#pragma unroll 1
            for (int i = w4 + 1 + NRS; i < 8; i += 4) {
                const uint4* src = ow + src_of(i, hg) * SC_SIZE;
                const uint32_t buf = o_buf(i), chk = buf + lane * 132;
                if (i < 5 + NRS) {
                    while (__any_sync(0xffffffffu, ld_relaxed4(&src[(lane & 3) * 160 + 159].w) == SENT)) {}
                    if (w4) pace(clock(), w4 * O_DT - O_D);
                } else {
                    mbar_wait(B_OE + (i - 4) * 8, 0);
                }
                if (i == 1 + NRS) TS(wg ? 3 : 4);
                uint32_t c;
                do {
                    if (elect_one()) {
                        mbar_expect_tx(B_OT + w4 * 8, 10240);
                        bulk_load(buf, src, 10240, B_OT + w4 * 8);
                    }
                    mbar_wait(B_OT + w4 * 8, ph);
                    if (i == 1 + NRS && !ph) TS(wg ? 19 : 20);
                    ph ^= 1;
                    c = max(max(lds4(chk), lds4(chk + 4096)), lds4(chk + 6144));
                } while (__any_sync(0xffffffffu, c == SENT));
                if (lane == 0) mbar_arrive(B_G2 + i * 8);
                TS(32 + i);
            }
            return;
        }

        float oc[80];
        bar_arrive(9, 256);
        bar_sync(2, 256);
        mbar_wait(B_G2, 0);
        TS(w4 == 0 ? 6 : 63);
        wg_fence();
#pragma unroll
        for (int s = 0; s < 5; s++)
            wgmma_own(oc, ol[2 * s], oh[2 * s], ol[2 * s + 1], oh[2 * s + 1], desc_lo(wo_buf(0), 10240) + s * 128, s);
        wg_commit();
        mbar_wait(B_XS, 0);
        const int orow = p0 + wg * 64 + w4 * 16;
        const uint32_t tk1 = ~lds4(SM_KEY + 16 * 4) & 2047, tk2 = ~lds4(SM_KEY + 17 * 4) & 2047;
        const uint32_t sel1 = (tk1 & 1) == par ? (tk1 >> 1) - orow : 99, sel2 = (tk2 & 1) == par ? (tk2 >> 1) - orow : 99;
        const uint32_t n0 = pack2(1.f - g0, 1.f - g0), n1 = pack2(1.f - g1, 1.f - g1);
        const uint32_t stg = SM_OUT + w4 * 5120;
        const uint32_t m128 = keep(stg + (lane & 15) * 128 + (((lane >> 4) ^ (lane & 7)) << 4));
        const uint32_t m64 = keep(stg + 4096 + (lane & 15) * 64 + (((lane >> 4) ^ ((lane >> 1) & 3)) << 4));
        const uint32_t l128 = keep(stg + (lane >> 3) * 128 + (((lane & 7) ^ (lane >> 3)) << 4));
        const uint32_t l64 = keep(stg + 4096 + r * 64 + ((cq ^ (lane >> 3)) << 4));
        char* const o128 = reinterpret_cast<char*>(P.op) + keep(((orow + (lane >> 3)) * 2 + par) * 1280 + kba * 128 + (lane & 7) * 16);
        char* const o64 = reinterpret_cast<char*>(P.op) + keep(((orow + r) * 2 + par) * 1280 + kbr * 128 + odd * 64 + cq * 16);
        mbar_wait(B_INIT, 0);
        wg_wait<0>();
        if (leader) mbar_arrive(B_OE);
        {
            uint32_t af[NRS][20];
            uint32_t m;
            do {
#pragma unroll
                for (int i = 0; i < NRS; i++) {
                    const uint32_t* p = reinterpret_cast<const uint32_t*>(ow + src_of(i + 1, hg) * SC_SIZE + w4 * 160) + lane;
#pragma unroll
                    for (int t = 0; t < 20; t++) af[i][t] = ld_relaxed4(p + t * 32);
                }
                m = 0;
#pragma unroll
                for (int i = 0; i < NRS; i++)
#pragma unroll
                    for (int t = 0; t < 20; t++) m = max(m, af[i][t]);
            } while (__any_sync(0xffffffffu, m == SENT));
            mbar_wait(B_DF, 0);
#pragma unroll
            for (int i = 0; i < NRS; i++) {
                mbar_wait(B_G2 + 8 + i * 8, 0);
                TS(w4 == 0 ? (i ? 11 : 7) : 63);
                wg_fence();
#pragma unroll
                for (int s = 0; s < 5; s++)
                    wgmma_own(oc, af[i][2 * s], af[i][10 + 2 * s], af[i][2 * s + 1], af[i][11 + 2 * s], desc_lo(wo_buf(i + 1), 10240) + s * 128, 1);
                wg_commit();
            }
            if (NRS == 2) {
                wg_wait<1>();
                if (leader) mbar_arrive(B_OE + 8);
            }
        }
#pragma unroll 1
        for (int i = 1 + NRS; i < 8; i++) {
            const uint32_t ao = desc_lo(0, 128) + (o_buf(i) >> 4), wo = desc_lo(0, 10240) + (wo_buf(i) >> 4);
            mbar_wait(B_G2 + i * 8, 0);
            TS(w4 == 0 ? (i < 2 ? 6 + i : i < 7 ? 9 + i : 17) : 63);
            wg_fence();
#pragma unroll
            for (int s = 0; s < 5; s++) wgmma_out(oc, ao + s * 16, wo + s * 128, 1);
            wg_commit();
            if (i < 5) {
                wg_wait<1>();
                if (i > 1 && leader) mbar_arrive(B_OE - 8 + i * 8);
            }
        }
        TS(w4 == 0 ? 8 : 63);

        if (min(sel1, sel2) < 16) {
            mbar_wait(B_MOD, 0);
#pragma unroll 1
            for (int j = 0; j < 2; j++) {
                const uint32_t sel = j ? sel2 : sel1;
#pragma unroll
                for (int t = 0; t < 20; t++) {
                    const uint32_t u = lds4(SM_U + j * 320 + cq * 4 + (t < 16 ? odd * 64 + t * 16 : (odd ? 0 : 256) + (t - 16) * 16));
                    if (sel == r) nb[2 * t] = hadd2(nb[2 * t], u);
                    if (sel == r + 8) nb[2 * t + 1] = hadd2(nb[2 * t + 1], u);
                }
            }
        }
        wg_wait<0>();
        TS(w4 == 0 ? 9 : 63);
        const bool nan = oc[0] != oc[0] || oc[2] != oc[2];
#pragma unroll
        for (int part = 0; part < 3; part++) {
            const int s0 = part ? part * 4 - 4 : 8, ns = part ? 4 : 2;
#pragma unroll
            for (int i = 0; i < 4; i++) {
                if (i >= ns) break;
                const int s = s0 + i;
                const uint32_t y0 = hfma2(n0, nb[s * 4], pack2(oc[s * 8 + 0], oc[s * 8 + 1]));
                const uint32_t y1 = hfma2(n1, nb[s * 4 + 1], pack2(oc[s * 8 + 2], oc[s * 8 + 3]));
                const uint32_t y2 = hfma2(n0, nb[s * 4 + 2], pack2(oc[s * 8 + 4], oc[s * 8 + 5]));
                const uint32_t y3 = hfma2(n1, nb[s * 4 + 3], pack2(oc[s * 8 + 6], oc[s * 8 + 7]));
                asm volatile("stmatrix.sync.aligned.m8n8.x4.shared.b16 [%0], {%1,%2,%3,%4};"
                             ::"r"(((s < 8 ? m128 : m64) ^ ((s & 3) * 32)) + (s & 4) * 512), "r"(y0), "r"(y1), "r"(y2), "r"(y3) : "memory");
            }
            __syncwarp();
            uint4 v[4];
#pragma unroll
            for (int i = 0; i < 4; i++)
                if (i < ns) v[i] = lds16(!part ? l64 + i * 512 : (l128 ^ ((i & 1) * 64)) + i * 512 + s0 * 512);
#pragma unroll
            for (int i = 0; i < 4; i++)
                if (i < ns) *reinterpret_cast<uint4*>(!part ? o64 + i * 8 * 2560 : o128 + i * 4 * 2560 + s0 * 32) = v[i];
            if (part == 0) TS(w4 == 0 ? 1 : 63);
        }
        TS(w4 == 0 ? 10 : 63);
        if (lane == 0) mbar_arrive(B_DONE);
        uint32_t redo;
        asm volatile("{\n.reg .pred p, q;\nsetp.ne.u32 p, %1, 0;\nbar.cta.red.or.pred q, 10, 128, p;\nselp.u32 %0, 1, 0, q;\n}"
                     : "=r"(redo) : "r"((uint32_t)nan) : "memory");
        if (redo) {
            const int cb = hg >> 1;
#pragma unroll 1
            for (int i = 0; i < 8; i++) {
                if (leader) {
                    mbar_expect_tx(B_RE, 25600);
                    tma_3d(SM_W, &P.woa, B_RE, 0, i * 80, (cb * 5 + 1) >> 1);
                    tma_2d(SM_W + 20480, &P.wob, B_RE, cb * 160 + ((cb & 1) ? 0 : 128), i * 80);
                }
#pragma unroll 1
                for (int s = 0; s < 20; s++) {
                    const int w = w4 * 640 + s * 32 + lane;
                    uint32_t v, it = 0;
                    do {
                        v = ld_relaxed4(reinterpret_cast<const uint32_t*>(ow + i * SC_SIZE) + w);
                        if (++it > (1u << 22)) fault();
                    } while ((v >> 16) == 0xFFFFu || (v & 0xFFFFu) == 0xFFFFu);
                    sts4(SM_X + w * 4, v);
                }
                fence_async_smem();
                __syncwarp();
                bar_sync(10, 128);
                mbar_wait(B_RE, i & 1);
                wg_fence();
#pragma unroll
                for (int s = 0; s < 5; s++) wgmma_out(oc, desc_lo(SM_X, 128) + s * 16, desc_lo(SM_W, 10240) + s * 128, s || i);
                wg_commit();
                wg_wait<0>();
                bar_sync(10, 128);
            }
#pragma unroll
            for (int t = 0; t < 40; t++) {
                const int col = (t < 32 ? kba * 64 + (t >> 1) * 8 : kbr * 64 + odd * 32 + ((t - 32) >> 1) * 8) + cq * 2;
                *reinterpret_cast<uint32_t*>(P.op + ((orow + r + (t & 1) * 8) * 2 + par) * 640 + col) =
                    hfma2((t & 1) ? n1 : n0, nb[t], pack2(oc[2 * t], oc[2 * t + 1]));
            }
        }
    }
}

typedef CUresult (*EncodeFn)(CUtensorMap*, CUtensorMapDataType, cuuint32_t, void*, const cuuint64_t*, const cuuint64_t*,
                             const cuuint32_t*, const cuuint32_t*, CUtensorMapInterleave, CUtensorMapSwizzle,
                             CUtensorMapL2promotion, CUtensorMapFloatOOBfill);

void encode(EncodeFn fn, CUtensorMap* m, const void* ptr, int rank, const cuuint64_t* dims, const cuuint64_t* strides,
            const cuuint32_t* box, CUtensorMapSwizzle swz) {
    const cuuint32_t es[4] = {1, 1, 1, 1};
    fn(m, CU_TENSOR_MAP_DATA_TYPE_BFLOAT16, rank, const_cast<void*>(ptr), dims, strides, box, es,
       CU_TENSOR_MAP_INTERLEAVE_NONE, swz, CU_TENSOR_MAP_L2_PROMOTION_L2_128B, CU_TENSOR_MAP_FLOAT_OOB_FILL_NONE);
}

}

extern "C" void kernel_launch(void* const* d_in, const int* in_sizes, int n_in, void* d_out, int out_size) {
    (void)in_sizes; (void)n_in; (void)out_size;
    Params P;
    P.xp = (const __nv_bfloat16*)d_in[0];
    P.wp = (const __nv_bfloat16*)d_in[1];
    P.wop = (const __nv_bfloat16*)d_in[2];
    P.dp = (const __nv_bfloat16*)d_in[7];
    P.upp = (const __nv_bfloat16*)d_in[6];
    P.op = (__nv_bfloat16*)d_out;
    P.w_r = (const __nv_bfloat16*)d_in[4];
    P.gate_w = (const __nv_bfloat16*)d_in[8];

    void* fp = nullptr;
    cudaDriverEntryPointQueryResult st;
    cudaGetDriverEntryPoint("cuTensorMapEncodeTiled", &fp, cudaEnableDefault, &st);
    EncodeFn fn = (EncodeFn)fp;
    const cuuint64_t xd[3] = {640, 2, 1024}, xs[2] = {1280, 2560};
    const cuuint32_t bx[3] = {64, 1, 64}, bx2[3] = {64, 1, 128};
    encode(fn, &P.x2, d_in[0], 3, xd, xs, bx2, CU_TENSOR_MAP_SWIZZLE_128B);
    encode(fn, &P.x, d_in[0], 3, xd, xs, bx, CU_TENSOR_MAP_SWIZZLE_128B);
    const cuuint64_t wd[3] = {640, 640, 3}, ws[2] = {3840, 1280};
    const cuuint32_t bw[3] = {64, 32, 3}, bwr[3] = {16, 32, 3};
    encode(fn, &P.w, d_in[1], 3, wd, ws, bw, CU_TENSOR_MAP_SWIZZLE_128B);
    encode(fn, &P.wr, d_in[1], 3, wd, ws, bwr, CU_TENSOR_MAP_SWIZZLE_32B);
    const cuuint64_t ad[3] = {64, 640, 10}, as[2] = {1280, 128}, bd[2] = {640, 640};
    const cuuint32_t ba[3] = {64, 80, 2}, bb[2] = {32, 80};
    encode(fn, &P.woa, d_in[2], 3, ad, as, ba, CU_TENSOR_MAP_SWIZZLE_128B);
    encode(fn, &P.wob, d_in[2], 2, bd, as, bb, CU_TENSOR_MAP_SWIZZLE_128B);
    const cuuint64_t gd[2] = {1728, 640}, gs[1] = {3456}, dd[2] = {640, 1728};
    const cuuint32_t bg[2] = {64, 20}, bu[2] = {64, 160}, bdn[2] = {64, 16}, bxg[3] = {64, 1, 16};
    encode(fn, &P.xg, d_in[0], 3, xd, xs, bxg, CU_TENSOR_MAP_SWIZZLE_128B);
    encode(fn, &P.gate, d_in[5], 2, gd, gs, bg, CU_TENSOR_MAP_SWIZZLE_128B);
    encode(fn, &P.up, d_in[6], 2, gd, gs, bu, CU_TENSOR_MAP_SWIZZLE_128B);
    encode(fn, &P.down, d_in[7], 2, dd, as, bdn, CU_TENSOR_MAP_SWIZZLE_128B);

    cudaFuncSetAttribute(fused_kernel, cudaFuncAttributeMaxDynamicSharedMemorySize, SM_TOTAL);
    fused_kernel<<<NCTA + (MAPV == 3 ? 0 : NEXTRA), 512, SM_TOTAL, cudaStreamPerThread>>>(P);
}
```

```cpp
#include <cuda_runtime.h>
#include <cuda_bf16.h>
#include <cuda.h>
#include <stdint.h>

namespace {

constexpr int NCTA = 128, NEXTRA = 4;
constexpr int NFFN = 108;
constexpr uint32_t SENT = 0xFFFFFFFFu;

constexpr uint32_t SB = 1024;
constexpr uint32_t SM_W = SB;
constexpr uint32_t SM_X = SB + 122880;
constexpr uint32_t SM_F = SB + 192512;
constexpr uint32_t SM_HALO = SB + 212992;
constexpr uint32_t SM_BAR = SB + 223232;
constexpr uint32_t SM_PROF = SB + 223744;
constexpr uint32_t SM_KEY = SB + 224000;
constexpr uint32_t SM_RED = SB + 224128;
constexpr uint32_t SM_XS = SB + 226688;
constexpr uint32_t SM_SENT = SB + 227328;
constexpr uint32_t SM_U = SM_RED + 1920;
constexpr uint32_t SM_H = SM_RED + 1536;
constexpr uint32_t SM_GATE = SM_RED;
constexpr uint32_t SM_TOTAL = 232448;
constexpr uint32_t SM_HALO1 = SM_X + 32768;
constexpr uint32_t SM_UP = SM_W + 61440;
constexpr uint32_t SM_OUT = SM_W + 61440;

constexpr uint32_t B_XL0 = SM_BAR, B_FULL = SM_BAR + 8, B_GT = SM_BAR + 72, B_RG = SM_BAR + 80, B_RG2 = SM_BAR + 88,
                   B_XS = SM_BAR + 96, B_EMPTY = SM_BAR + 128, B_DONE = SM_BAR + 192, B_XE = SM_BAR + 200,
                   B_GUD = SM_BAR + 224, B_OE = SM_BAR + 232, B_OT = SM_BAR + 264, B_MOD = SM_BAR + 296,
                   B_GU = SM_BAR + 104, B_UP = SM_BAR + 112, B_RS = SM_BAR + 312, B_INIT = SM_BAR + 320,
                   B_RE = SM_BAR + 328, B_G2 = SM_BAR + 336, B_DF = SM_BAR + 400;

struct Params {
    CUtensorMap x, x2, w, wr, woa, wob, xg, gate, up, down;
    __nv_bfloat16* op;
    const __nv_bfloat16 *xp, *wp, *dp, *upp, *wop, *w_r, *gate_w;
};

constexpr int SC_O = 0;
constexpr int SC_HALO = 1280;
constexpr int SC_GU = 1440;
constexpr int SC_Y = 1504;
constexpr int SC_SIZE = 1600;
__device__ __align__(128) uint4 g_sc[NCTA * SC_SIZE];
__device__ __align__(128) uint2 g_cand[NCTA];
__device__ __align__(16) uint32_t g_gate[2048];
__device__ __align__(128) unsigned g_cnt[64];
#define TS(i) do { } while (0)
#define TS2(i) do { } while (0)
#define TSX(i) do { } while (0)

#define TS5(i) do { } while (0)
__device__ __forceinline__ uint32_t smem_u32(const void* p) { return (uint32_t)__cvta_generic_to_shared(p); }
__device__ __forceinline__ void fault() { asm volatile("st.shared.u32 [%0], %0;" ::"r"(0x100001) : "memory"); }
__device__ __forceinline__ void mbar_init(uint32_t bar, uint32_t cnt) {
    asm volatile("mbarrier.init.shared::cta.b64 [%0], %1;" ::"r"(bar), "r"(cnt) : "memory");
}
__device__ __forceinline__ void mbar_expect_tx(uint32_t bar, uint32_t bytes) {
    asm volatile("mbarrier.arrive.expect_tx.shared::cta.b64 _, [%0], %1;" ::"r"(bar), "r"(bytes) : "memory");
}
__device__ __forceinline__ void mbar_arrive(uint32_t bar) {
    asm volatile("mbarrier.arrive.shared::cta.b64 _, [%0];" ::"r"(bar) : "memory");
}
__device__ __forceinline__ bool mbar_try(uint32_t bar, uint32_t parity) {
    uint32_t ok;
    asm volatile("{\n.reg .pred p;\nmbarrier.try_wait.parity.shared::cta.b64 p, [%1], %2;\nselp.u32 %0, 1, 0, p;\n}"
                 : "=r"(ok) : "r"(bar), "r"(parity) : "memory");
    return ok;
}
__device__ __forceinline__ void mbar_wait(uint32_t bar, uint32_t parity) {
    asm volatile("{\n.reg .pred p;\nAGAIN:\nmbarrier.try_wait.parity.shared::cta.b64 p, [%0], %1;\n@!p bra AGAIN;\n}"
                 ::"r"(bar), "r"(parity) : "memory");
}
__device__ __forceinline__ void tma_2d(uint32_t dst, const CUtensorMap* m, uint32_t bar, int c0, int c1) {
    asm volatile("cp.async.bulk.tensor.2d.shared::cluster.global.mbarrier::complete_tx::bytes [%0], [%1, {%3, %4}], [%2];"
                 ::"r"(dst), "l"(m), "r"(bar), "r"(c0), "r"(c1) : "memory");
}
__device__ __forceinline__ void bulk_load(uint32_t dst, const void* src, uint32_t bytes, uint32_t bar) {
    asm volatile("cp.async.bulk.shared::cluster.global.mbarrier::complete_tx::bytes [%0], [%1], %2, [%3];"
                 ::"r"(dst), "l"(src), "r"(bytes), "r"(bar) : "memory");
}
__device__ __forceinline__ void bulk_store(void* dst, uint32_t src, uint32_t bytes) {
    asm volatile("cp.async.bulk.global.shared::cta.bulk_group [%0], [%1], %2;" ::"l"(dst), "r"(src), "r"(bytes) : "memory");
}
__device__ __forceinline__ void tma_3d(uint32_t dst, const CUtensorMap* m, uint32_t bar, int c0, int c1, int c2) {
    asm volatile("cp.async.bulk.tensor.3d.shared::cluster.global.mbarrier::complete_tx::bytes [%0], [%1, {%3, %4, %5}], [%2];"
                 ::"r"(dst), "l"(m), "r"(bar), "r"(c0), "r"(c1), "r"(c2) : "memory");
}
__device__ __forceinline__ void fence_async_smem() { asm volatile("fence.proxy.async.shared::cta;" ::: "memory"); }
__device__ __forceinline__ void wg_fence() { asm volatile("wgmma.fence.sync.aligned;" ::: "memory"); }
__device__ __forceinline__ void wg_commit() { asm volatile("wgmma.commit_group.sync.aligned;" ::: "memory"); }
template <int N> __device__ __forceinline__ void wg_wait() { asm volatile("wgmma.wait_group.sync.aligned %0;" ::"n"(N) : "memory"); }
__device__ __forceinline__ void bar_sync(int id, int n) { asm volatile("bar.cta.sync %0, %1;" ::"r"(id), "r"(n) : "memory"); }
__device__ __forceinline__ void bar_arrive(int id, int n) { asm volatile("bar.cta.arrive %0, %1;" ::"r"(id), "r"(n) : "memory"); }

__device__ constexpr uint32_t desc_lo(uint32_t addr, uint32_t lbo) { return (addr >> 4) | ((lbo >> 4) << 16); }
__device__ __forceinline__ bool elect_one() {
    uint32_t p;
    asm volatile("{\n.reg .pred p;\nelect.sync _|p, 0xffffffff;\nselp.u32 %0, 1, 0, p;\n}" : "=r"(p));
    return p;
}
__device__ __forceinline__ uint32_t ld_relaxed4(const void* p) {
    uint32_t v;
    asm volatile("ld.relaxed.gpu.global.u32 %0, [%1];" : "=r"(v) : "l"(p) : "memory");
    return v;
}
__device__ __forceinline__ void st_relaxed4(void* p, uint32_t v) {
    asm volatile("st.relaxed.gpu.global.u32 [%0], %1;" ::"l"(p), "r"(v) : "memory");
}
template <int N = 1>
__device__ __forceinline__ void red_inc(unsigned* p, unsigned after) {
    asm volatile("red.relaxed.gpu.global.add.u32 [%0], %2;" ::"l"(p), "r"(after), "n"(N) : "memory");
}
__device__ __forceinline__ uint32_t lds4(uint32_t a) {
    uint32_t v;
    asm volatile("ld.shared.u32 %0, [%1];" : "=r"(v) : "r"(a) : "memory");
    return v;
}
__device__ __forceinline__ float2 lds8f(uint32_t a) {
    float2 v;
    asm volatile("ld.shared.v2.f32 {%0, %1}, [%2];" : "=f"(v.x), "=f"(v.y) : "r"(a) : "memory");
    return v;
}
__device__ __forceinline__ void sts4(uint32_t a, uint32_t v) { asm volatile("st.shared.u32 [%0], %1;" ::"r"(a), "r"(v) : "memory"); }
__device__ __forceinline__ uint32_t hmul2(uint32_t a, uint32_t b) {
    uint32_t d;
    asm("mul.rn.bf16x2 %0, %1, %2;" : "=r"(d) : "r"(a), "r"(b));
    return d;
}
__device__ __forceinline__ uint32_t hadd2(uint32_t a, uint32_t b) {
    uint32_t d;
    asm("add.rn.bf16x2 %0, %1, %2;" : "=r"(d) : "r"(a), "r"(b));
    return d;
}
__device__ __forceinline__ uint32_t hfma2(uint32_t a, uint32_t b, uint32_t c) {
    uint32_t d;
    asm("fma.rn.bf16x2 %0, %1, %2, %3;" : "=r"(d) : "r"(a), "r"(b), "r"(c));
    return d;
}
__device__ __forceinline__ uint4 ld_relaxed16(const void* p) {
    uint4 v;
    asm volatile("{\n.reg .b128 t;\n.reg .b64 lo, hi;\nld.relaxed.gpu.global.b128 t, [%4];\nmov.b128 {lo, hi}, t;\n"
                 "mov.b64 {%0, %1}, lo;\nmov.b64 {%2, %3}, hi;\n}" : "=r"(v.x), "=r"(v.y), "=r"(v.z), "=r"(v.w) : "l"(p) : "memory");
    return v;
}
__device__ __forceinline__ void st_relaxed16(void* p, uint32_t a, uint32_t b, uint32_t c, uint32_t d) {
    uint64_t lo = (uint64_t)a | ((uint64_t)b << 32), hi = (uint64_t)c | ((uint64_t)d << 32);
    asm volatile("{\n.reg .b128 t;\nmov.b128 t, {%1, %2};\nst.relaxed.gpu.global.b128 [%0], t;\n}" ::"l"(p), "l"(lo), "l"(hi) : "memory");
}
__device__ __forceinline__ void st_relaxed8(void* p, uint32_t a, uint32_t b) {
    asm volatile("{\n.reg .b64 t;\nmov.b64 t, {%1, %2};\nst.relaxed.gpu.global.b64 [%0], t;\n}" ::"l"(p), "r"(a), "r"(b) : "memory");
}
__device__ __forceinline__ uint2 ld_relaxed8(const void* p) {
    uint2 v;
    asm volatile("{\n.reg .b64 t;\nld.relaxed.gpu.global.b64 t, [%2];\nmov.b64 {%0, %1}, t;\n}" : "=r"(v.x), "=r"(v.y) : "l"(p) : "memory");
    return v;
}
__device__ __forceinline__ uint4 ld_nc16(const void* p) {
    uint4 v;
    asm volatile("ld.global.L1::no_allocate.v4.u32 {%0, %1, %2, %3}, [%4];" : "=r"(v.x), "=r"(v.y), "=r"(v.z), "=r"(v.w) : "l"(p) : "memory");
    return v;
}
__device__ __forceinline__ uint2 ld_nc8(const void* p) {
    uint2 v;
    asm volatile("ld.global.nc.L1::no_allocate.v2.u32 {%0, %1}, [%2];" : "=r"(v.x), "=r"(v.y) : "l"(p));
    return v;
}
__device__ __forceinline__ uint4 lds16(uint32_t a) {
    uint4 v;
    asm volatile("ld.shared.v4.u32 {%0, %1, %2, %3}, [%4];" : "=r"(v.x), "=r"(v.y), "=r"(v.z), "=r"(v.w) : "r"(a) : "memory");
    return v;
}
__device__ __forceinline__ void sts16(uint32_t a, uint32_t x, uint32_t y, uint32_t z, uint32_t w) {
    asm volatile("st.shared.v4.u32 [%0], {%1, %2, %3, %4};" ::"r"(a), "r"(x), "r"(y), "r"(z), "r"(w) : "memory");
}
__device__ __forceinline__ uint32_t pack2(float lo, float hi) {
    uint32_t r;
    asm("cvt.rn.bf16x2.f32 %0, %1, %2;" : "=r"(r) : "f"(hi), "f"(lo));
    return r;
}
__device__ __forceinline__ uint32_t pack2v(float lo, float hi) {
    uint32_t r;
    asm volatile("cvt.rn.bf16x2.f32 %0, %1, %2;" : "=r"(r) : "f"(hi), "f"(lo));
    return r;
}
__device__ __forceinline__ float bf_lo(uint32_t u) { return __uint_as_float(u << 16); }
__device__ __forceinline__ float bf_hi(uint32_t u) { return __uint_as_float(u & 0xFFFF0000u); }
__device__ __forceinline__ float bf_round(float f) { return __bfloat162float(__float2bfloat16_rn(f)); }
__device__ __forceinline__ uint32_t prmt(uint32_t a, uint32_t sel) {
    uint32_t d;
    asm("prmt.b32 %0, %1, 0, %2;" : "=r"(d) : "r"(a), "r"(sel));
    return d;
}
__device__ __forceinline__ uint32_t movm(uint32_t a) {
    uint32_t d;
    asm volatile("movmatrix.sync.aligned.m8n8.trans.b16 %0, %1;" : "=r"(d) : "r"(a));
    return d;
}
__device__ __forceinline__ void mma16(float (&c)[4], uint32_t a0, uint32_t a1, uint32_t a2, uint32_t a3, uint32_t b0, uint32_t b1) {
    asm volatile("mma.sync.aligned.m16n8k16.row.col.f32.bf16.bf16.f32 {%0,%1,%2,%3}, {%4,%5,%6,%7}, {%8,%9}, {%0,%1,%2,%3};"
                 : "+f"(c[0]), "+f"(c[1]), "+f"(c[2]), "+f"(c[3]) : "r"(a0), "r"(a1), "r"(a2), "r"(a3), "r"(b0), "r"(b1));
}
__device__ __forceinline__ void mma8(float (&c)[4], uint32_t a0, uint32_t a1, uint32_t b0) {
    asm volatile("mma.sync.aligned.m16n8k8.row.col.f32.bf16.bf16.f32 {%0,%1,%2,%3}, {%4,%5}, {%6}, {%0,%1,%2,%3};"
                 : "+f"(c[0]), "+f"(c[1]), "+f"(c[2]), "+f"(c[3]) : "r"(a0), "r"(a1), "r"(b0));
}
__device__ __forceinline__ float ex2(float x) { float y; asm("ex2.approx.ftz.f32 %0, %1;" : "=f"(y) : "f"(x)); return y; }
__device__ __forceinline__ float rcp(float x) { float y; asm("rcp.approx.ftz.f32 %0, %1;" : "=f"(y) : "f"(x)); return y; }
__device__ __forceinline__ float sigmoidf(float z) { return rcp(1.0f + ex2(z * -1.4426950408889634f)); }
__device__ __forceinline__ float u2f(uint32_t u) { return __uint_as_float(u); }
__device__ __forceinline__ uint32_t f2u(float f) { return __float_as_uint(f); }

__device__ __forceinline__ void wgmma_main(float (&d)[96], uint32_t a, uint32_t b, int scale_d) {
    asm volatile("{\n.reg .pred p;\n.reg .b64 da, db;\nsetp.ne.b32 p, %98, 0;\n"
        "mov.b64 da, {%96, 0x40000040};\nmov.b64 db, {%97, 0x40000040};\n"
        "wgmma.mma_async.sync.aligned.m64n192k16.f32.bf16.bf16 "
        "{%0, %1, %2, %3, %4, %5, %6, %7, %8, %9, %10, %11, %12, %13, %14, %15, "
        "%16, %17, %18, %19, %20, %21, %22, %23, %24, %25, %26, %27, %28, %29, %30, %31, "
        "%32, %33, %34, %35, %36, %37, %38, %39, %40, %41, %42, %43, %44, %45, %46, %47, "
        "%48, %49, %50, %51, %52, %53, %54, %55, %56, %57, %58, %59, %60, %61, %62, %63, "
        "%64, %65, %66, %67, %68, %69, %70, %71, %72, %73, %74, %75, %76, %77, %78, %79, "
        "%80, %81, %82, %83, %84, %85, %86, %87, %88, %89, %90, %91, %92, %93, %94, %95}, "
        "da, db, p, 1, 1, 0, 1;\n}\n"
        : "+f"(d[0]), "+f"(d[1]), "+f"(d[2]), "+f"(d[3]), "+f"(d[4]), "+f"(d[5]), "+f"(d[6]), "+f"(d[7]),
          "+f"(d[8]), "+f"(d[9]), "+f"(d[10]), "+f"(d[11]), "+f"(d[12]), "+f"(d[13]), "+f"(d[14]), "+f"(d[15]),
          "+f"(d[16]), "+f"(d[17]), "+f"(d[18]), "+f"(d[19]), "+f"(d[20]), "+f"(d[21]), "+f"(d[22]), "+f"(d[23]),
          "+f"(d[24]), "+f"(d[25]), "+f"(d[26]), "+f"(d[27]), "+f"(d[28]), "+f"(d[29]), "+f"(d[30]), "+f"(d[31]),
          "+f"(d[32]), "+f"(d[33]), "+f"(d[34]), "+f"(d[35]), "+f"(d[36]), "+f"(d[37]), "+f"(d[38]), "+f"(d[39]),
          "+f"(d[40]), "+f"(d[41]), "+f"(d[42]), "+f"(d[43]), "+f"(d[44]), "+f"(d[45]), "+f"(d[46]), "+f"(d[47]),
          "+f"(d[48]), "+f"(d[49]), "+f"(d[50]), "+f"(d[51]), "+f"(d[52]), "+f"(d[53]), "+f"(d[54]), "+f"(d[55]),
          "+f"(d[56]), "+f"(d[57]), "+f"(d[58]), "+f"(d[59]), "+f"(d[60]), "+f"(d[61]), "+f"(d[62]), "+f"(d[63]),
          "+f"(d[64]), "+f"(d[65]), "+f"(d[66]), "+f"(d[67]), "+f"(d[68]), "+f"(d[69]), "+f"(d[70]), "+f"(d[71]),
          "+f"(d[72]), "+f"(d[73]), "+f"(d[74]), "+f"(d[75]), "+f"(d[76]), "+f"(d[77]), "+f"(d[78]), "+f"(d[79]),
          "+f"(d[80]), "+f"(d[81]), "+f"(d[82]), "+f"(d[83]), "+f"(d[84]), "+f"(d[85]), "+f"(d[86]), "+f"(d[87]),
          "+f"(d[88]), "+f"(d[89]), "+f"(d[90]), "+f"(d[91]), "+f"(d[92]), "+f"(d[93]), "+f"(d[94]), "+f"(d[95])
        : "r"(a), "r"(b), "r"(scale_d));
}

__device__ __forceinline__ void wgmma_rem(float (&d)[24], uint32_t a, uint32_t b, int scale_d) {
    asm volatile("{\n.reg .pred p;\n.reg .b64 da, db;\nsetp.ne.b32 p, %26, 0;\n"
        "mov.b64 da, {%24, 0x40000040};\nmov.b64 db, {%25, 0xC0000010};\n"
        "wgmma.mma_async.sync.aligned.m64n48k16.f32.bf16.bf16 "
        "{%0, %1, %2, %3, %4, %5, %6, %7, %8, %9, %10, %11, %12, %13, %14, %15, "
        "%16, %17, %18, %19, %20, %21, %22, %23}, "
        "da, db, p, 1, 1, 0, 1;\n}\n"
        : "+f"(d[0]), "+f"(d[1]), "+f"(d[2]), "+f"(d[3]), "+f"(d[4]), "+f"(d[5]), "+f"(d[6]), "+f"(d[7]),
          "+f"(d[8]), "+f"(d[9]), "+f"(d[10]), "+f"(d[11]), "+f"(d[12]), "+f"(d[13]), "+f"(d[14]), "+f"(d[15]),
          "+f"(d[16]), "+f"(d[17]), "+f"(d[18]), "+f"(d[19]), "+f"(d[20]), "+f"(d[21]), "+f"(d[22]), "+f"(d[23])
        : "r"(a), "r"(b), "r"(scale_d));
}

__device__ __forceinline__ void wgmma_out(float (&d)[80], uint32_t a, uint32_t b, int scale_d) {
    asm volatile("{\n.reg .pred p;\n.reg .b64 da, db;\nsetp.ne.b32 p, %82, 0;\n"
        "mov.b64 da, {%80, 0x50};\nmov.b64 db, {%81, 0x40000040};\n"
        "wgmma.mma_async.sync.aligned.m64n160k16.f32.bf16.bf16 "
        "{%0, %1, %2, %3, %4, %5, %6, %7, %8, %9, %10, %11, %12, %13, %14, %15, "
        "%16, %17, %18, %19, %20, %21, %22, %23, %24, %25, %26, %27, %28, %29, %30, %31, "
        "%32, %33, %34, %35, %36, %37, %38, %39, %40, %41, %42, %43, %44, %45, %46, %47, "
        "%48, %49, %50, %51, %52, %53, %54, %55, %56, %57, %58, %59, %60, %61, %62, %63, "
        "%64, %65, %66, %67, %68, %69, %70, %71, %72, %73, %74, %75, %76, %77, %78, %79}, "
        "da, db, p, 1, 1, 0, 1;\n}\n"
        : "+f"(d[0]), "+f"(d[1]), "+f"(d[2]), "+f"(d[3]), "+f"(d[4]), "+f"(d[5]), "+f"(d[6]), "+f"(d[7]),
          "+f"(d[8]), "+f"(d[9]), "+f"(d[10]), "+f"(d[11]), "+f"(d[12]), "+f"(d[13]), "+f"(d[14]), "+f"(d[15]),
          "+f"(d[16]), "+f"(d[17]), "+f"(d[18]), "+f"(d[19]), "+f"(d[20]), "+f"(d[21]), "+f"(d[22]), "+f"(d[23]),
          "+f"(d[24]), "+f"(d[25]), "+f"(d[26]), "+f"(d[27]), "+f"(d[28]), "+f"(d[29]), "+f"(d[30]), "+f"(d[31]),
          "+f"(d[32]), "+f"(d[33]), "+f"(d[34]), "+f"(d[35]), "+f"(d[36]), "+f"(d[37]), "+f"(d[38]), "+f"(d[39]),
          "+f"(d[40]), "+f"(d[41]), "+f"(d[42]), "+f"(d[43]), "+f"(d[44]), "+f"(d[45]), "+f"(d[46]), "+f"(d[47]),
          "+f"(d[48]), "+f"(d[49]), "+f"(d[50]), "+f"(d[51]), "+f"(d[52]), "+f"(d[53]), "+f"(d[54]), "+f"(d[55]),
          "+f"(d[56]), "+f"(d[57]), "+f"(d[58]), "+f"(d[59]), "+f"(d[60]), "+f"(d[61]), "+f"(d[62]), "+f"(d[63]),
          "+f"(d[64]), "+f"(d[65]), "+f"(d[66]), "+f"(d[67]), "+f"(d[68]), "+f"(d[69]), "+f"(d[70]), "+f"(d[71]),
          "+f"(d[72]), "+f"(d[73]), "+f"(d[74]), "+f"(d[75]), "+f"(d[76]), "+f"(d[77]), "+f"(d[78]), "+f"(d[79])
        : "r"(a), "r"(b), "r"(scale_d));
}

__device__ __forceinline__ void wgmma_own(float (&d)[80], uint32_t a0, uint32_t a1, uint32_t a2, uint32_t a3, uint32_t b, int scale_d) {
    asm volatile("{\n.reg .pred p;\n.reg .b64 db;\nsetp.ne.b32 p, %85, 0;\nmov.b64 db, {%84, 0x40000040};\n"
        "wgmma.mma_async.sync.aligned.m64n160k16.f32.bf16.bf16 "
        "{%0, %1, %2, %3, %4, %5, %6, %7, %8, %9, %10, %11, %12, %13, %14, %15, "
        "%16, %17, %18, %19, %20, %21, %22, %23, %24, %25, %26, %27, %28, %29, %30, %31, "
        "%32, %33, %34, %35, %36, %37, %38, %39, %40, %41, %42, %43, %44, %45, %46, %47, "
        "%48, %49, %50, %51, %52, %53, %54, %55, %56, %57, %58, %59, %60, %61, %62, %63, "
        "%64, %65, %66, %67, %68, %69, %70, %71, %72, %73, %74, %75, %76, %77, %78, %79}, "
        "{%80, %81, %82, %83}, db, p, 1, 1, 1;\n}\n"
        : "+f"(d[0]), "+f"(d[1]), "+f"(d[2]), "+f"(d[3]), "+f"(d[4]), "+f"(d[5]), "+f"(d[6]), "+f"(d[7]),
          "+f"(d[8]), "+f"(d[9]), "+f"(d[10]), "+f"(d[11]), "+f"(d[12]), "+f"(d[13]), "+f"(d[14]), "+f"(d[15]),
          "+f"(d[16]), "+f"(d[17]), "+f"(d[18]), "+f"(d[19]), "+f"(d[20]), "+f"(d[21]), "+f"(d[22]), "+f"(d[23]),
          "+f"(d[24]), "+f"(d[25]), "+f"(d[26]), "+f"(d[27]), "+f"(d[28]), "+f"(d[29]), "+f"(d[30]), "+f"(d[31]),
          "+f"(d[32]), "+f"(d[33]), "+f"(d[34]), "+f"(d[35]), "+f"(d[36]), "+f"(d[37]), "+f"(d[38]), "+f"(d[39]),
          "+f"(d[40]), "+f"(d[41]), "+f"(d[42]), "+f"(d[43]), "+f"(d[44]), "+f"(d[45]), "+f"(d[46]), "+f"(d[47]),
          "+f"(d[48]), "+f"(d[49]), "+f"(d[50]), "+f"(d[51]), "+f"(d[52]), "+f"(d[53]), "+f"(d[54]), "+f"(d[55]),
          "+f"(d[56]), "+f"(d[57]), "+f"(d[58]), "+f"(d[59]), "+f"(d[60]), "+f"(d[61]), "+f"(d[62]), "+f"(d[63]),
          "+f"(d[64]), "+f"(d[65]), "+f"(d[66]), "+f"(d[67]), "+f"(d[68]), "+f"(d[69]), "+f"(d[70]), "+f"(d[71]),
          "+f"(d[72]), "+f"(d[73]), "+f"(d[74]), "+f"(d[75]), "+f"(d[76]), "+f"(d[77]), "+f"(d[78]), "+f"(d[79])
        : "r"(a0), "r"(a1), "r"(a2), "r"(a3), "r"(b), "r"(scale_d));
}

__device__ __forceinline__ void wgmma_vec(float (&d)[8], uint32_t a, uint32_t b, int scale_d) {
    asm volatile("{\n.reg .pred p;\n.reg .b64 da, db;\nsetp.ne.b32 p, %10, 0;\n"
        "mov.b64 da, {%8, 0x40000040};\nmov.b64 db, {%9, 0x14};\n"
        "wgmma.mma_async.sync.aligned.m64n16k16.f32.bf16.bf16 {%0, %1, %2, %3, %4, %5, %6, %7}, da, db, p, 1, 1, 1, 0;\n}\n"
        : "+f"(d[0]), "+f"(d[1]), "+f"(d[2]), "+f"(d[3]), "+f"(d[4]), "+f"(d[5]), "+f"(d[6]), "+f"(d[7])
        : "r"(a), "r"(b), "r"(scale_d));
}

#define TSA(i) do { } while (0)
#define MAP_TILE(b) ((((b) >> 1) & 14) | ((b) & 1))
#define MAP_HG(b) (((b) >> 5) | ((b) & 2) << 1)
#define B_OFF 0
#define W_S0 2
#define E_V 0
#define MAPV 4
#define GW 0
#define GU_DS (GU_DT * 7 / 11)
#define GU_ST 90
#define X_OFF 350
#define RW_REG 0
#define P2W 4
#define RES_V 2
#define Y2_T 17000
#define ENT_V 0
#define TPF 1
#define SKEW 4
#define PACE 500
#define PACE_W0 (-600)
#define PACE_A 250
#define PACE_B 450
#define RG_ORDER 0x24130
#define GU_T0 3600
#define GU_DT 750
#define RS_T0 9000
#define RS_DT 120
#define EXCH_FIRST 1
#define HALO_D 300
#define PF_UP 4200
#define O_D 0
#define O_DT 300
#define PF_DN 4200
#define PF_DT 450
#define GX_NS 200
#define NRS 2
#define C5_D 600
#define C6_D 100
#define PF_N 4
#define PF_0 4
#define EPF_N 15
#define EPF_M 15
#define EPF_T 900
#define RG1_T0 1700
#define RG1_DT 200
#define RW1_T 0
#define Y_T 15800
#define GL_T 0
#define DN_T0 500
#define DN_DT 68
#define DN_T1 100000
#define DN_D1 45
#define DN_R 5
#define H_T 13500
#define HS_T 13500
#define GL_N 16
#define C1_T 0
#define C0_T 0
#define RS_N 10
#define CAND_T 9000

__device__ __forceinline__ uint32_t keep(uint32_t v) { return __shfl_xor_sync(0xffffffffu, v, 0); }
__device__ __forceinline__ uint32_t ukeep(uint32_t v) { return __shfl_sync(0xffffffffu, v, 0); }
__device__ __forceinline__ void ldsm2(uint32_t* d, uint32_t a) {
    asm volatile("ldmatrix.sync.aligned.m8n8.x4.shared.b16 {%0,%1,%2,%3}, [%8];\nldmatrix.sync.aligned.m8n8.x4.shared.b16 {%4,%5,%6,%7}, [%9];"
                 : "=r"(d[0]), "=r"(d[1]), "=r"(d[2]), "=r"(d[3]), "=r"(d[4]), "=r"(d[5]), "=r"(d[6]), "=r"(d[7])
                 : "r"(a), "r"(a ^ 32) : "memory");
}
__device__ __forceinline__ void ldsm_t(uint32_t (&d)[4], uint32_t a) {
    asm volatile("ldmatrix.sync.aligned.m8n8.x4.trans.shared.b16 {%0,%1,%2,%3}, [%4];"
                 : "=r"(d[0]), "=r"(d[1]), "=r"(d[2]), "=r"(d[3]) : "r"(a) : "memory");
}
template <bool SWP, int SEG, int E>
__device__ __forceinline__ void pack_blocks(uint32_t (&d)[10], const float (&am)[96], const float (&ar)[24]) {
#pragma unroll
    for (int t = 0; t < 10; t++) {
        const float* p = (SWP ? t < 2 : t >= 8) ? ar + (SEG * 2 + (t & 1)) * 4 + E : am + (SEG * 8 + t - (SWP ? 2 : 0)) * 4 + E;
        d[t] = pack2v(p[0], p[1]);
    }
}
__device__ __forceinline__ int src_of(int i, int hg) { return i == 0 ? hg : i - (i <= hg); }

__device__ constexpr uint32_t o_buf(int i) { return ((0x99ADA3D1u >> ((i - NRS) & 3) * 8) & 255) << 10; }
__device__ constexpr uint32_t wo_buf(int i) { return SM_W + ((0x10342103u >> i * 4) & 7) * 30720; }

template <int N>
__device__ __forceinline__ void poll(uint4 (&a)[N], const uint4* p, int stride) {
    bool bad;
    do {
        bad = false;
#pragma unroll
        for (int s = 0; s < N; s++) a[s] = ld_relaxed16(p + s * stride);
#pragma unroll
        for (int s = 0; s < N; s++) bad |= a[s].w == SENT;
    } while (__any_sync(0xffffffffu, bad));
}
__device__ __forceinline__ void pace(unsigned t0, int t) {
    asm volatile("{\n.reg .pred p;\n.reg .s32 d;\nAGAIN:\nmov.u32 d, %%clock;\nsub.s32 d, d, %0;\nsetp.lt.s32 p, d, 0;\n"
                 "@p nanosleep.u32 20;\n@p bra AGAIN;\n}" ::"r"(t0 + t) : "memory");
}
__device__ __forceinline__ void l2_prefetch(const void* p) { asm volatile("prefetch.global.L2 [%0];" ::"l"(p) : "memory"); }

template <int N>
__device__ __forceinline__ bool landed(const uint4* w, int lane) {
    uint32_t a = 0;
#pragma unroll
    for (int i = 0; i < N; i++) a ^= w[i].w;
    return __ballot_sync(0xffffffffu, lane == 0 || a == 0) && lane == 0;
}
__device__ __forceinline__ void swiglu(const uint4 (&a)[4], uint32_t dst, uint32_t stride) {
    const float g0 = bf_round((u2f(a[0].x) + u2f(a[1].x)) + (u2f(a[2].x) + u2f(a[3].x)));
    const float g1 = bf_round((u2f(a[0].y) + u2f(a[1].y)) + (u2f(a[2].y) + u2f(a[3].y)));
    const float u0 = bf_round((u2f(a[0].z) + u2f(a[1].z)) + (u2f(a[2].z) + u2f(a[3].z)));
    const float u1 = bf_round((u2f(a[0].w) + u2f(a[1].w)) + (u2f(a[2].w) + u2f(a[3].w)));
    const uint32_t h = pack2(bf_round(g0 * sigmoidf(g0)) * u0, bf_round(g1 * sigmoidf(g1)) * u1);
    asm volatile("st.shared.u16 [%0], %2;\nst.shared.u16 [%1], %3;" ::"r"(dst), "r"(dst + stride), "h"((uint16_t)h), "h"((uint16_t)(h >> 16)) : "memory");
}
template <int N>
__device__ __forceinline__ float4 vec_mma(const uint4 (&w)[N], const uint32_t* x, uint32_t sel) {
    float c[4][4] = {};
    const uint32_t s[4] = {sel, sel >> 16, sel + ((sel & 0x10101010u) >> 3) * 17, (sel + ((sel & 0x10101010u) >> 3) * 17) >> 16};
#pragma unroll
    for (int i = 0; i < N; i++)
        mma16(c[i & 3], w[i].x, w[i].y, w[i].z, w[i].w, prmt(x[i >> 1], s[(i & 1) * 2]), prmt(x[i >> 1], s[(i & 1) * 2 + 1]));
    return make_float4((c[0][0] + c[1][0]) + (c[2][0] + c[3][0]), (c[0][1] + c[1][1]) + (c[2][1] + c[3][1]),
                       (c[0][2] + c[1][2]) + (c[2][2] + c[3][2]), (c[0][3] + c[1][3]) + (c[2][3] + c[3][3]));
}

__global__ void __launch_bounds__(512, 1) fused_kernel(const __grid_constant__ Params P) {
    extern __shared__ __align__(1024) uint8_t smem_raw[];
    const unsigned t_start = clock();
    const int tid = threadIdx.x, lane = tid & 31;
    unsigned sm, bid;
    asm("mov.u32 %0, %%smid;" : "=r"(sm));
    const CUtensorMap* mx = &P.x;
    asm volatile("" : "+l"(mx));
    if ((unsigned)(tid - 480) < EPF_N) l2_prefetch(P.wp + (tid * 132 + sm) * 64 - 480 * 132 * 64);
    const int warp = __shfl_sync(0xffffffffu, threadIdx.x >> 5, 0);
    constexpr uint32_t rk = 0;
    asm("{\n.reg .pred p;\n.reg .b32 t, u;\nshr.u32 t, %1, 1;\nmad.lo.s32 u, t, 14, -928;\nmad.lo.s32 t, t, 37, -925;\nmax.s32 t, t, 0;\n"
        "shr.u32 t, t, 7;\nand.b32 t, t, 14;\nsetp.ge.u32 p, %1, 124;\nselp.b32 t, u, t, p;\nadd.s32 %0, %1, t;\n}" : "=r"(bid) : "r"(sm));
    const int hg = MAP_HG(bid), par = bid & 1, p0 = (MAP_TILE(bid) >> 1) * 128;
    const bool swp = (hg & 3) == 3;
    const int wcm = hg * 80 + (swp ? 16 : 0), wcr = hg * 80 + (swp ? 0 : 64);
    if (warp == 0) {
        if (elect_one()) {
#pragma unroll
            for (int i = 0; i < 4; i++) mbar_init(SM_BAR + i * 8, 1);
            asm volatile("fence.mbarrier_init.release.cluster;" ::: "memory");
            if (bid < NCTA) {
                mbar_expect_tx(B_FULL, 15360 + 8192);
                tma_3d(SM_X + 8192, mx, B_FULL, 0, par, p0 + 64);
                tma_3d(SM_W, mx + 2, B_FULL, wcm, 0, 0);
                tma_3d(SM_W + 12288, mx + 3, B_FULL, wcr, 0, 0);
                TS(40);
                mbar_expect_tx(B_XL0, 8192);
                tma_3d(SM_X, mx, B_XL0, 0, par, p0);
                mbar_expect_tx(B_FULL + 8, 15360);
                tma_3d(SM_W + 15360, mx + 2, B_FULL + 8, wcm, 32, 0);
                tma_3d(SM_W + 15360 + 12288, mx + 3, B_FULL + 8, wcr, 32, 0);
            }
        }
    }
    if ((unsigned)(warp - 1) < 6 && elect_one()) {
#pragma unroll
        for (int i = 0; i < 4; i++) mbar_init(SM_BAR + warp * 32 + i * 8, warp < 4 ? 1 : warp < 6 ? 2 : 4);
        asm volatile("fence.mbarrier_init.release.cluster;" ::: "memory");
    }
    asm volatile("" : "+r"(bid));
    const int role = bid >= NCTA ? -1 : warp, e = (bid + 2) & 3;
    const int tile = MAP_TILE(bid), cid = tile * 8 + hg;
    uint4* const sc = g_sc + cid * SC_SIZE;
    __syncthreads();

    if (role >= 12) {
        asm volatile("setmaxnreg.dec.sync.aligned.u32 32;");
        if (warp == 12) {
            if (elect_one()) {
#pragma unroll 1
                for (int s = W_S0; s < 20; s++) {
                    const uint32_t fb = B_FULL + (s & 7) * 8, dst = SM_W + (s & 7) * 15360;
                    mbar_wait(fb + (B_EMPTY - B_FULL), ~(s >> 3) & 1);
                    pace(t_start, max(PACE_A + s * PACE_B, PACE_W0 + s * PACE));
                    mbar_expect_tx(fb, (s & 1) ? 15360 : 15360 + 16384);
                    tma_3d(dst, &P.w, fb, wcm, s * 32, 0);
                    tma_3d(dst + 12288, &P.wr, fb, wcr, s * 32, 0);
                    TS2(20 + s);
                    if (s == W_S0) TS(41);
                }
                mbar_wait(B_RG2, 0);
                if (NFFN) {
                    mbar_wait(B_EMPTY + 5 * 8, 1);
                    mbar_expect_tx(B_UP, cid < NFFN ? 20480 : 16384);
                    TS(46);
                    if (cid < NFFN) tma_2d(SM_UP, &P.up, B_UP, (cid >> 2) * 64, (cid & 3) * 160);
                    else
#pragma unroll 1
                        for (int i = 0; i < 8; i++) tma_2d(SM_UP + i * 2048, &P.down, B_UP, i * 64, cid * 32 - 2352);
                }
                const int cb = hg >> 1, ca = (cb * 5 + 1) >> 1, cr = cb * 160 + ((cb & 1) ? 0 : 128);
#pragma unroll 1
                for (int j = 0; j < 8; j++) {
                    const int i = j ^ (j == 3 || j == 4 ? 7 : 0);
                    if (j != 3) mbar_wait(j < 3 ? B_EMPTY + ((2 * j + 7) & 7) * 8 : B_GUD + (j - 4) * 8, j == 0);
                    if (j >= 5) pace(clock(), j == 5 ? C5_D : C6_D);
                    if (C1_T && j == 1) pace(t_start, C1_T);
                    if (C0_T && j == 0) pace(t_start, C0_T);
                    const uint32_t dst = wo_buf(i), gb = B_G2 + i * 8;
                    mbar_expect_tx(gb, 25600);
                    tma_3d(dst, &P.woa, gb, 0, src_of(i, hg) * 80, ca);
                    tma_2d(dst + 20480, &P.wob, gb, cr, src_of(i, hg) * 80);
                }
            }
        } else if (warp == 14) {
            if (elect_one()) {
#pragma unroll 1
                for (int kb = 1; kb < 10; kb++) {
                    const uint32_t fb = B_FULL + (kb & 3) * 16, dst = SM_X + (kb & 3) * 16384;
                    mbar_wait(fb + (B_EMPTY - B_FULL + 8), ~(kb >> 2) & 1);
                    if (kb >= 4) mbar_wait(B_XE + (kb - 4 >> 1) * 8, 0);
                    pace(t_start, max(PACE_A - PACE_B / 2 + 2 * kb * PACE_B, PACE_W0 - X_OFF + (2 * kb + 1) * PACE));
                    tma_3d(dst, &P.x2, fb, kb * 64, par, p0);
                    TS5(41 + kb);
                }
            }
            __syncwarp();
            pace(t_start, CAND_T);
            {
                const uint32_t tag = lds4(SM_KEY + 20 * 4);
                uint4 c[2], v;
                do {
                    c[0] = ld_relaxed16(g_cand + lane * 2);
                    c[1] = ld_relaxed16(g_cand + lane * 2 + 64);
                    v = ld_relaxed16(g_gate + tile * 128 + lane * 4);
                } while (__any_sync(0xffffffffu, ((c[0].x ^ tag) | (c[0].z ^ tag) | (c[1].x ^ tag) | (c[1].z ^ tag) | (v.x ^ tag) |
                                                  (v.y ^ tag) | (v.z ^ tag) | (v.w ^ tag)) & 0xF800u));
                const uint32_t a1 = max(c[0].x, c[0].z), b1 = max(c[1].x, c[1].z), l1 = max(a1, b1);
                const uint32_t l2 = max(max(max(c[0].y, c[0].w), max(c[1].y, c[1].w)),
                                        max(max(min(c[0].x, c[0].z), min(c[1].x, c[1].z)), min(a1, b1)));
                const uint32_t k1 = __reduce_max_sync(0xffffffffu, l1);
                const uint32_t k2 = __reduce_max_sync(0xffffffffu, l1 == k1 ? l2 : l1);
                sts16(SM_GATE + lane * 16, v.x, v.y, v.z, v.w);
                __syncwarp();
                if (elect_one()) {
                    bulk_load(SM_XS, P.xp + (~k1 & 2047) * 640 + (cid & 3) * 160, 320, B_XS);
                    bulk_load(SM_XS + 320, P.xp + (~k2 & 2047) * 640 + (cid & 3) * 160, 320, B_XS);
                    sts16(SM_KEY + 16 * 4, k1, k2, 0, 0);
                    mbar_expect_tx(B_XS, 640);
                    mbar_arrive(B_GT);
                    TS(56);
                }
            }
            bar_sync(12, 64);
            pace(clock(), HALO_D);
            uint4 hv[5];
            poll<5>(hv, sc + (SC_HALO - (tile < 2 ? 0 : 16 * SC_SIZE) + lane), 32);
#pragma unroll
            for (int s = 0; s < 5; s++) sts16(SM_HALO + s * 512 + lane * 16, hv[s].x, hv[s].y, hv[s].z, hv[s].w);
            bar_arrive(8, 64);
            TS(25);
        } else if (warp == 15) {
            if (EPF_M) {
                pace(t_start, EPF_T);
                if (lane < EPF_M) l2_prefetch(P.wp + (EPF_N * 132 + lane * 128 + bid) * 64);
            }
#pragma unroll 1
            for (int i = PF_0; i < PF_N; i++) {
                pace(t_start, (i < 6 ? PF_UP : PF_DN) + i * PF_DT);
                const int ln = (i * 128 + cid) * 32 + lane;
                l2_prefetch((ln < 17280 ? P.upp : ln < 23680 ? P.wop - 17280 * 64 : P.dp - 23680 * 64) + ln * 64);
            }
            int it = (smem_u32(smem_raw) & 0xFFFFFF) == SB ? 0 : 1 << 20;
            while (!mbar_try(B_DONE, 0) || !mbar_try(B_MOD, 0))
                if (++it > (1 << 20)) fault();
        } else {
#pragma unroll 1
            for (int i = 0; i < 10; i++) sts16(SM_SENT + i * 512 + lane * 16, SENT, SENT, SENT, SENT);
            fence_async_smem();
            __syncwarp();
            if (elect_one()) {
                if (!RW_REG) mbar_expect_tx(B_RG, 2560);
                mbar_expect_tx(B_GU, cid < NFFN ? 20480 : 24576);
                asm volatile("mbarrier.expect_tx.relaxed.cta.shared::cta.b64 [%0], 10240;" ::"r"(B_RG2 + rk) : "memory");
                pace(t_start, RW1_T);
                bulk_load(SM_RED, P.w_r, 1280, B_RG);
                bulk_load(SM_RED + 1280, P.gate_w, 1280, B_RG);
#pragma unroll 1
                for (int i = 0; i < 5; i++) {
                    pace(t_start, RG1_T0 + i * RG1_DT);
                    tma_3d(SM_HALO + i * 2048, &P.xg, B_RG2, 320 + i * 64, par, p0 + hg * 16);
                }
#pragma unroll
                for (int i = 0; i < 23; i++) mbar_init(B_GUD + i * 8, i == 22 || !i ? 4 : i < 15 + NRS ? 1 : 2);
                bulk_store(sc + SC_HALO, SM_SENT, 5120);
                asm volatile("cp.async.bulk.commit_group;\ncp.async.bulk.wait_group 0;" ::: "memory");
                mbar_arrive(B_RG2);
                TS(43);
                const unsigned goal = (ld_relaxed4(g_cnt + 32) | (NCTA - 1)) + 1;
#pragma unroll 1
                for (int i = 0; i < (!NFFN ? 0 : cid < NFFN ? 8 : 12); i++) {
                    pace(t_start, GU_T0 + i * (cid < NFFN ? GU_DT : GU_DS) + (cid & 7) * GU_ST);
                    if (cid < NFFN) tma_2d(SM_F + i * 2560, &P.gate, B_GU, (cid >> 2) * 64, (cid & 3) * 160 + i * 20);
                    else tma_2d(SM_F - 4096 + i * 2048, &P.down, B_GU, min(i, 4 + (i >> 1)) * 64, cid * 32 - 2368 + (i > 8 ? (i & 1) * 16 : 0));
                }
#pragma unroll 1
                for (int i = 0; i < RS_N; i++) {
                    pace(t_start, RS_T0 + i * RS_DT);
                    bulk_store(sc + i * (1280 / RS_N), SM_SENT, 20480 / RS_N);
                }
                asm volatile("cp.async.bulk.commit_group;\ncp.async.bulk.wait_group 0;" ::: "memory");
                red_inc(g_cnt + 32, goal);
                mbar_arrive(B_RS);
                TS(44);
                while (ld_relaxed4(g_cnt + 32) - goal > 0x80000000u) {}
                mbar_arrive(B_INIT);
                TS(45);
            }
        }
    } else if (role >= 8) {
        asm volatile("setmaxnreg.dec.sync.aligned.u32 96;");
        const int t = tid - 256;
        uint32_t tag = ld_relaxed4(g_cnt);
        float gv = 0.f;
        int grow = hg * 16 + (t >> 3);
        mbar_wait(B_RG, 0);
        TS(warp == 8 ? 48 : 63);
        {
            float r0 = 0.f, r1 = 0.f, g0 = 0.f, g1 = 0.f;
            const uint32_t sw = (t >> 4) * 128 + (((t ^ (t >> 4)) & 7) << 4), hi = (t >> 3) & 1;
            mbar_wait(B_XL0, 0);
            tag = (tag * 8 + 2048) & 0xF800u;
            sts4(SM_KEY + 20 * 4, tag);
#pragma unroll 1
            for (int i = 0; i < 5; i++) {
                const int p = (RG_ORDER >> (i * 4)) & 7, kb = 2 * p + hi;
                mbar_wait(p < 3 ? B_FULL + (p & 1) * 32 : B_RG2, p == 2);
                if (p < 2) mbar_wait(B_FULL + p * 32 + 16, 0);
                const uint32_t xa = sw + (kb < 5 ? SM_X + (kb & 3) * 16384 + hg * 2048 : SM_HALO - 5 * 2048 + kb * 2048);
                const uint4 a = lds16(xa), b = lds16(xa + 1024);
                const uint4 w = lds16(SM_RED + p * 256 + (t & 15) * 16), v = lds16(SM_RED + 1280 + p * 256 + (t & 15) * 16);
                if (__ballot_sync(0xffffffffu, lane == 0 || a.w == b.w) && lane == 0 && p < 3) mbar_arrive(B_XE + p * 8);
                TS5(warp == 8 ? 51 + i : 63);
                const uint32_t as[4] = {a.x, a.y, a.z, a.w}, bs[4] = {b.x, b.y, b.z, b.w};
                const uint32_t ws[4] = {w.x, w.y, w.z, w.w}, vs[4] = {v.x, v.y, v.z, v.w};
#pragma unroll
                for (int e = 0; e < 4; e++) {
                    r0 = fmaf(bf_lo(as[e]), bf_lo(ws[e]), r0);
                    r1 = fmaf(bf_lo(bs[e]), bf_lo(ws[e]), r1);
                    g0 = fmaf(bf_lo(as[e]), bf_lo(vs[e]), g0);
                    g1 = fmaf(bf_lo(bs[e]), bf_lo(vs[e]), g1);
                    r0 = fmaf(bf_hi(as[e]), bf_hi(ws[e]), r0);
                    r1 = fmaf(bf_hi(bs[e]), bf_hi(ws[e]), r1);
                    g0 = fmaf(bf_hi(as[e]), bf_hi(vs[e]), g0);
                    g1 = fmaf(bf_hi(bs[e]), bf_hi(vs[e]), g1);
                }
            }
            const bool up = lane & 4;
            r0 = (hi ? r1 : r0) + __shfl_xor_sync(0xffffffffu, hi ? r0 : r1, 8);
            g0 = (hi ? g1 : g0) + __shfl_xor_sync(0xffffffffu, hi ? g0 : g1, 8);
            float r = (up ? g0 : r0) + __shfl_xor_sync(0xffffffffu, up ? r0 : g0, 4);
            r += __shfl_xor_sync(0xffffffffu, r, 2);
            r = bf_round(r + __shfl_xor_sync(0xffffffffu, r, 1));
            const int row = hg * 16 + (t >> 4) + hi * 8;
            const uint32_t u = f2u(r);
            if (!up) sts4(SM_KEY + (t >> 3) * 4, (((int)u < 0 ? ~u : u | 0x80000000u) & 0xFFFF0000u) | (2047 - (p0 + row) * 2 - par));
            gv = r;
            grow = row;
        }
        TS(warp == 8 ? 61 : 63);
        mbar_wait(B_RG2, 0);
        bar_sync(4, 128);
        if (warp == 8) {
            const uint32_t key = lds4(SM_KEY + (lane & 15) * 4);
            uint32_t k1 = __reduce_max_sync(0xffffffffu, key);
            uint32_t k2 = __reduce_max_sync(0xffffffffu, key == k1 ? 0u : key);
            if (elect_one()) {
                st_relaxed8(g_cand + cid, k1 | tag, k2 | tag);
                red_inc<MAPV == 3 ? 2 : 1>(g_cnt, tag);
            }
            TS(49);
        }
        if ((lane & 7) == 4) st_relaxed4(g_gate + tile * 128 + grow, f2u(bf_round(sigmoidf(gv))) | tag);
        const int cq = lane & 3, w4 = warp & 3;
        const uint32_t la = keep(cq * 256 + (((lane >> 2) ^ cq * 2) << 4));
        const uint32_t sel = keep(0x44444444u ^ (0x54u << (lane >> 2 & 1) * 8 + (lane & 16)));
        if (NFFN) {
            float4 d;
            uint4* dst;
            if (cid < NFFN) {
                float dg[8], du[8];
                mbar_wait(B_GU, 0);
                mbar_wait(B_XS, 0);
                TS(warp == 8 ? 50 : 63);
                if (GW & 1) mbar_wait(B_EMPTY + 3 * 8, 0);
                wg_fence();
#pragma unroll
                for (int i = 0; i < 10; i++) wgmma_vec(dg, desc_lo(SM_F + i * 2048, 16), desc_lo(SM_XS + i * 32, 16), i);
                wg_commit();
                mbar_wait(B_UP, 0);
                TS(warp == 10 ? 58 : 63);
                if (GW & 2) mbar_wait(B_EMPTY + 3 * 8, 0);
                wg_fence();
#pragma unroll
                for (int i = 0; i < 10; i++) wgmma_vec(du, desc_lo(SM_UP + i * 2048, 16), desc_lo(SM_XS + i * 32, 16), i);
                wg_commit();
                wg_wait<0>();
                if (lane == 0) mbar_arrive(B_GUD), mbar_arrive(B_DF);
                TS(warp == 8 ? 54 : warp == 10 ? 59 : 63);
                if (cq == 0) {
                    st_relaxed16(sc + SC_GU + w4 * 16 + (lane >> 2), f2u(dg[0]), f2u(dg[4]), f2u(du[0]), f2u(du[4]));
                    st_relaxed16(sc + SC_GU + w4 * 16 + 8 + (lane >> 2), f2u(dg[2]), f2u(dg[6]), f2u(du[2]), f2u(du[6]));
                }
            } else {
                uint4 wv[2][8], wr[4];
                mbar_wait(B_UP, 0);
#pragma unroll
                for (int i = 0; i < 8; i++) wv[i >> 2][4 + (i & 3)] = lds16((la ^ (i & 1) * 144) + SM_UP + w4 * 4096 + (i >> 1) * 1024);
                if (landed<4>(wv[0] + 4, lane) & landed<4>(wv[1] + 4, lane)) mbar_arrive(B_GUD);
                mbar_wait(B_GU, 0);
#pragma unroll
                for (int i = 0; i < 4; i++) wr[i] = lds16((la ^ (i & 1) * 144) + SM_F + 12288 + w4 * 2048 + (i >> 1) * 1024);
                mbar_wait(B_XS, 0);
                if (w4 == 0) {
                    uint4 pq[4];
                    pace(t_start, HS_T);
                    poll<4>(pq, g_sc + ((cid >> 1) * 4 - 148) * SC_SIZE + SC_GU + (cid & 1) * 32 + lane, SC_SIZE);
                    TS(warp == 8 ? 55 : 63);
                    swiglu(pq, SM_H + (lane & 6) * 8 + (lane >> 3) * 4 + (lane & 1) * 2, 64);
                }
                bar_sync(4, 128);
                TS(warp == 8 ? 57 : 63);
                const uint4 h = lds16(SM_H + (lane & 8) * 8 + cq * 16);
                const uint32_t hv[4] = {h.x, h.y, h.z, h.w}, hr[2] = {(w4 & 1) ? h.z : h.x, (w4 & 1) ? h.w : h.y};
                d = vec_mma<4>(wr, hr, sel);
                dst = g_sc + (cid * 5 - 520 + w4) * SC_SIZE + SC_Y + (lane & 1) * 32 + (lane >> 1);
                float c[2][2][4] = {};
                const uint32_t s2 = sel + ((sel & 0x10101010u) >> 3) * 17;
#pragma unroll
                for (int i = 7; i >= 0; i--) {
                    const uint32_t x0 = prmt(hv[i >> 1], (i & 1) ? s2 : sel), x1 = prmt(hv[i >> 1], ((i & 1) ? s2 : sel) >> 16);
#pragma unroll
                    for (int n = 0; n < 2; n++) {
                        if (i >= 4) wv[n][i - 4] = lds16((la ^ (i & 1) * 144) + SM_F - 6144 + w4 * 4096 + n * 2048 + (i >> 1) * 1024);
                        mma16(c[n][i & 1], wv[n][i].x, wv[n][i].y, wv[n][i].z, wv[n][i].w, x0, x1);
                    }
                }
#pragma unroll
                for (int n = 0; n < 2; n++)
                    st_relaxed16(dst + n * 16, f2u(c[n][0][0] + c[n][1][0]), f2u(c[n][0][1] + c[n][1][1]), f2u(c[n][0][2] + c[n][1][2]),
                                 f2u(c[n][0][3] + c[n][1][3]));
                dst += (4 - w4) * SC_SIZE + w4 * 8;
                TS(warp == 8 ? 30 : 63);
                if (lane == 0 && f2u(d.x) != SENT) mbar_arrive(B_DF);
                if (w4 & 1) {
                    sts16(SM_RED + 512 + (w4 & 2) * 256 + lane * 16, f2u(d.x), f2u(d.y), f2u(d.z), f2u(d.w));
                    bar_arrive(13 + (w4 >> 1), 64);
                } else {
                    bar_sync(13 + (w4 >> 1), 64);
                    const uint4 o = lds16(SM_RED + 512 + (w4 & 2) * 256 + lane * 16);
                    st_relaxed16(dst, f2u(d.x + u2f(o.x)), f2u(d.y + u2f(o.y)), f2u(d.z + u2f(o.z)), f2u(d.w + u2f(o.w)));
                }
            }
        } else {
            if (t < 4) mbar_arrive(B_GUD);
            if (t < 4) mbar_arrive(B_DF);
            mbar_wait(B_XS, 0);
        }
        TS(warp == 8 ? 51 : 63);
        const uint32_t k1 = lds4(SM_KEY + 16 * 4), k2 = lds4(SM_KEY + 17 * 4);
        const uint32_t mine = (tile >> 1) * 256 + (hg & 1) * 128 + par;
        const bool own1 = (~k1 & 0x781) == mine, own2 = (~k2 & 0x781) == mine;
        if ((own1 || own2) && NFFN) {
            const int rg = min(t / 40, 2), un = (hg >> 1) * 40 + t % 40, up = (hg >> 1) * 80 + min(t, 79);
            mbar_wait(B_RS, 0);
            pace(t_start, Y_T);
            TS(warp == 8 ? 60 : 63);
#pragma unroll 1
            for (int j = !own1; j <= own2; j++) {
                const uint4* p = g_sc + (rg * 5 + 20 + (un >> 5)) * SC_SIZE + SC_Y + j * 32 + (un & 31);
                float y[4];
                bool bad;
                do {
                    uint4 yp[7];
#pragma unroll
                    for (int i = 0; i < 7; i++) yp[i] = i < 6 || rg < 2 ? ld_relaxed16(p + i * 15 * SC_SIZE) : make_uint4(0, 0, 0, 0);
                    y[0] = y[1] = y[2] = y[3] = 0.f;
                    bad = false;
#pragma unroll
                    for (int i = 0; i < 7; i++) {
                        y[0] += u2f(yp[i].x); y[1] += u2f(yp[i].y); y[2] += u2f(yp[i].z); y[3] += u2f(yp[i].w);
                        bad |= yp[i].w == SENT;
                    }
                } while (__any_sync(0xffffffffu, bad));
                TS(warp == 8 ? 53 : 63);
                sts16(SM_SENT + j * 2048 + t * 16, f2u(y[0]), f2u(y[1]), f2u(y[2]), f2u(y[3]));
                bar_sync(4, 128);
                if (w4 < 3) {
                    const uint32_t key = j ? k2 : k1, ya = SM_SENT + j * 2048 + t * 8;
                    const float rs = bf_round(sigmoidf(u2f(((int)key < 0 ? key & 0x7FFFFFFFu : ~key) & 0xFFFF0000u)));
                    const float2 y0 = lds8f(ya), y1 = lds8f(ya + 640), y2 = lds8f(ya + 1280);
                    const uint2* q = reinterpret_cast<const uint2*>(g_sc + (up >> 6) * SC_SIZE + SC_Y + j * 32) + (up & 63);
                    const float sx = y0.x + y1.x + y2.x, sy = y0.y + y1.y + y2.y;
                    uint2 z[4];
                    pace(t_start, Y2_T);
                    do {
#pragma unroll
                        for (int i = 0; i < 4; i++) z[i] = ld_relaxed8(q + i * 10 * SC_SIZE);
                    } while (__any_sync(0xffffffffu, max(max(z[0].y, z[1].y), max(z[2].y, z[3].y)) == SENT));
                    TS(warp == 8 ? 62 : 63);
                    if (t < 80)
                        sts4(SM_U + j * 320 + t * 4, pack2(bf_round(sx + (u2f(z[0].x) + u2f(z[1].x)) + (u2f(z[2].x) + u2f(z[3].x))) * rs,
                                                           bf_round(sy + (u2f(z[0].y) + u2f(z[1].y)) + (u2f(z[2].y) + u2f(z[3].y))) * rs));
                }
            }
            bar_sync(4, 128);
        }
        if (t == 0) mbar_arrive(B_MOD);
        TS(warp == 8 ? 52 : 63);
    } else if (role < 0) {
        const int half = warp >> 3;
        if (!NFFN) {
            if (tid == 0) red_inc<NCTA / NEXTRA>(g_cnt, 0);
            return;
        }
        uint32_t wf[DN_R][5][4], la[5];
        auto rows = [&](uint32_t l) {
#pragma unroll
            for (int i = 0; i < 5; i++) {
                const uint32_t c = (warp & 7) * 10 + 2 * i + (l >> 3 & 1);
                la[i] = SB + half * 20480 + (c >> 3) * 2048 + (l & 7) * 128 + (l >> 4) * 1024 + (((c ^ l) & 7) << 4);
            }
        };
        rows(lane);
        auto fetch = [&](int j, int n, uint32_t bar) {
#pragma unroll 1
            for (int h = 0; h < n; h++) {
                pace(t_start, min(DN_T0 + (j * 20 + h * 10 + warp) * DN_DT, DN_T1 + (j * 20 + h * 10 + warp) * DN_D1));
                tma_2d(SB + (j % 5) * 40960 + h * 20480 + warp * 2048, &P.down, bar, warp * 64, e * 272 + (j + h * 9) * 16);
            }
        };
        if (warp < 10 && elect_one()) {
            if (warp <= DN_R) mbar_expect_tx(B_FULL + warp * 8, warp < DN_R ? 40960 : (17 - 2 * DN_R) * 20480);
#pragma unroll 1
            for (int j = 0; j < 5; j++) fetch(j, 2, B_FULL + j * 8);
        }
        const uint32_t tag = (ukeep(ld_relaxed4(g_cnt)) * 8 + 2048) & 0xF800u;
#pragma unroll
        for (int j = 0; j < DN_R; j++) {
            uint32_t any = 0;
            mbar_wait(B_FULL + j * 8, 0);
#pragma unroll
            for (int i = 0; i < 5; i++) {
                ldsm_t(wf[j][i], la[i] + j * 40960);
                any ^= wf[j][i][3];
            }
            if (j < 4) {
                if (__syncthreads_count(any == 0) == 1000) fault();
                if (warp < 10 && elect_one()) fetch(j + 5, j < 3 ? 2 : 1, B_FULL + DN_R * 8);
                if (j == 0 && tid == 0) red_inc<NCTA / NEXTRA>(g_cnt, tag);
            }
            TSX(warp == 0 && j == 0 ? 0 : warp == 0 && j == 3 ? 1 : 63);
        }
        if (warp < 9) {
            pace(t_start, H_T - 1000);
            uint4 a[4];
            do {
                a[0] = ld_relaxed16(g_cand + lane * 2);
                a[1] = ld_relaxed16(g_cand + lane * 2 + 64);
            } while (__any_sync(0xffffffffu, ((a[0].x ^ tag) | (a[0].z ^ tag) | (a[1].x ^ tag) | (a[1].z ^ tag)) & 0xF800u));
            const int u = min(tid, 271), f = e * 272 + u;
            pace(t_start, H_T);
            TSX(warp == 0 ? 3 : 63);
            poll<4>(a, g_sc + (f >> 6) * 4 * SC_SIZE + SC_GU + (f & 63), SC_SIZE);
            TSX(warp == 0 ? 4 : warp == 8 ? 5 : 63);
            swiglu(a, SM_RED + (u >> 4) * 64 + (u & 6) * 4 + (u & 8) / 2 + (u & 1) * 2, 32);
        }
        rows(keep(lane));
        mbar_wait(B_FULL + DN_R * 8, 0);
        TSX(warp == 15 ? 2 : 63);
        __syncthreads();
        float c[5][4] = {};
#pragma unroll
        for (int j = 0; j < 9; j++) {
            if (j == 8 && half) break;
            const float2 b = lds8f(SM_RED + half * 576 + j * 64 + (lane & 7) * 8);
            if (j == 1) TSX(warp == 0 ? 6 : 63);
#pragma unroll
            for (int i = 0; i < 5; i++) {
                if (j >= DN_R) ldsm_t(wf[j % DN_R][i], la[i] + (j % 5) * 40960);
                mma16(c[i], wf[j % DN_R][i][0], wf[j % DN_R][i][1], wf[j % DN_R][i][2], wf[j % DN_R][i][3], f2u(b.x), f2u(b.y));
            }
        }
        const uint32_t ra = SB + 7 * 20480 + half * 5248 + (lane & 1) * 2624 + (warp & 7) * 320 + (lane & 2) * 16 + (lane >> 2) * 4;
#pragma unroll
        for (int i = 0; i < 5; i++) sts4(ra + i * 64, f2u((lane & 2) ? ((lane & 1) ? c[i][3] : c[i][2]) : ((lane & 1) ? c[i][1] : c[i][0])));
        TSX(warp == 0 ? 7 : 63);
        __syncthreads();
        if (warp < 10) {
            const uint32_t ya = SB + 7 * 20480 + (warp & 1) * 2624 + (warp >> 1) * 512 + lane * 16;
            const uint4 y0 = lds16(ya), y1 = lds16(ya + 5248);
            st_relaxed16(g_sc + (e * 5 + (warp >> 1)) * SC_SIZE + SC_Y + (tid & 63), f2u(u2f(y0.x) + u2f(y1.x)), f2u(u2f(y0.y) + u2f(y1.y)),
                         f2u(u2f(y0.z) + u2f(y1.z)), f2u(u2f(y0.w) + u2f(y1.w)));
        }
    } else {
        asm volatile("setmaxnreg.inc.sync.aligned.u32 192;");
        const int wg = warp >> 2;
        const bool leader = (tid & 127) == 0;
        float am[96], ar[24];
        if (wg == 0) mbar_wait(B_XL0, 0);
        bool rel = false;
        uint32_t nb[40];
        const int odd = (hg >> 1) & 1, kba = ukeep(RES_V && wg != (hg & 1) ? 99 : ((hg >> 1) * 5 + 1) >> 1), kbr = ukeep(kba + 2 - odd * 3);
        const int kbs = wg ? -1 : (20 - SKEW) / 2;
        const uint32_t xrow = keep(SM_X + (warp * 16 + (lane & 15)) * 128 + (((lane >> 4) ^ (lane & 7)) << 4));
#pragma unroll 1
        for (int kb = 0; kb < 10; kb++) {
            const uint32_t fb = B_FULL + (kb & 3) * 16, wo = (kb & 3) * 1920, ph = (kb >> 2) & 1;
            const uint32_t xo = desc_lo(SM_X, 16) + wg * 512 + (kb & 3) * 1024;
#pragma unroll
            for (int h = 0; h < 2; h++) {
                mbar_wait(fb + h * 8, ph);
                if (kb == 0 && h == 0) TS(warp == 0 ? 0 : warp == 4 ? 16 : 63);
                TS2(warp == P2W ? kb * 2 + h : 63);
                if (RES_V == 2) {
                    const uint32_t xa = (xrow ^ h * 64) + (kb & 3) * 16384;
                    if (kb == kba) ldsm2(nb + h * 8, xa);
                    if (kb == kba + 1) ldsm2(nb + 16 + h * 8, xa);
                    if (h == 0 && kb == kbr) ldsm2(nb + 32, xa ^ (odd * 64));
                } else if (h == 0) {
                    const uint32_t xa = xrow + (kb & 3) * 16384;
                    if (kb == kba) { ldsm2(nb, xa); ldsm2(nb + 8, xa ^ 64); }
                    if (kb == kba + 1) { ldsm2(nb + 16, xa); ldsm2(nb + 24, xa ^ 64); }
                    if (kb == kbr) ldsm2(nb + 32, xa ^ (odd * 64));
                }
                wg_wait<1>();
                if (rel && (h == 0 || kb != kbs)) mbar_arrive(B_EMPTY + ((kb * 16 - 16) & 48) + h * 8);
                if (h == 0 && kb == kbs) {
                    wg_wait<0>();
                    if (rel) mbar_arrive(B_EMPTY + ((19 - SKEW) & 7) * 8);
                    bar_sync(5, 256);
                }
                wg_fence();
                wgmma_main(am, xo + h * 4, desc_lo(SM_W + h * 15360, 4096) + wo, h || kb);
                wgmma_rem(ar, xo + h * 4, desc_lo(SM_W + h * 15360 + 12288, 1024) + wo, h || kb);
                wgmma_main(am, xo + h * 4 + 2, desc_lo(SM_W + h * 15360 + 2048, 4096) + wo, 1);
                wgmma_rem(ar, xo + h * 4 + 2, desc_lo(SM_W + h * 15360 + 12288 + 512, 1024) + wo, 1);
                wg_commit();
            }
            rel = leader;
        }
        if (wg == 1) bar_arrive(5, 256);
        mbar_wait(B_XE + 16, 0);
        mbar_wait(B_RG2, 0);
        mbar_wait(B_EMPTY + 5 * 8, 1);
        wg_wait<0>();
        if (leader) mbar_arrive(B_EMPTY + 3 * 8);
        TS(warp == 0 ? 2 : warp == 4 ? 18 : 63);
        TS2(warp == 0 ? 41 : warp == 4 ? 40 : 63);

        uint32_t kl[10], kh[10], vl[10], vh[10], ql[10], qh[10], kp[10], vp[10];
        if (swp) {
            pack_blocks<true, 1, 2>(kh, am, ar);
            pack_blocks<true, 2, 2>(vh, am, ar);
        } else {
            pack_blocks<false, 1, 2>(kh, am, ar);
            pack_blocks<false, 2, 2>(vh, am, ar);
        }
        const int w4 = warp & 3;
        const uint32_t pbuf = (wg ? SM_HALO1 : SM_HALO) + w4 * 2560 + lane * 16;
        const uint32_t hbuf = warp == 3 ? SM_HALO1 + lane * 16 : pbuf + 2560;
        {
            const uint32_t ex[20] = {kh[0], kh[1], kh[3], kh[4], kh[5], kh[6], kh[8], kh[9], kh[2], kh[7],
                                     vh[0], vh[1], vh[2], vh[3], vh[4], vh[5], vh[6], vh[7], vh[8], vh[9]};
            if (warp == 7) {
                uint4* const hp = sc + SC_HALO + lane;
#pragma unroll
                for (int s = 0; s < 5; s++) st_relaxed16(hp + s * 32, ex[4 * s], ex[4 * s + 1], ex[4 * s + 2], ex[4 * s + 3]);
                bar_arrive(12, 64);
            } else {
#pragma unroll
                for (int s = 0; s < 5; s++) sts16(hbuf + s * 512, ex[4 * s], ex[4 * s + 1], ex[4 * s + 2], ex[4 * s + 3]);
            }
        }
        TSA(warp == 7 ? 22 : warp == 3 ? 23 : 63);
        if (warp == 3) bar_arrive(11, 64);
        if (swp) {
            pack_blocks<true, 2, 0>(vl, am, ar);
            pack_blocks<true, 0, 0>(ql, am, ar);
            pack_blocks<true, 0, 2>(qh, am, ar);
            pack_blocks<true, 1, 0>(kl, am, ar);
        } else {
            pack_blocks<false, 2, 0>(vl, am, ar);
            pack_blocks<false, 0, 0>(ql, am, ar);
            pack_blocks<false, 0, 2>(qh, am, ar);
            pack_blocks<false, 1, 0>(kl, am, ar);
        }
#pragma unroll
        for (int t = 0; t < 10; t++) { vl[t] = movm(vl[t]); vh[t] = movm(vh[t]); }
        mbar_wait(B_RS, 0);
        mbar_wait(B_GT, 0);
        const float g0 = bf_hi(lds4(SM_GATE + warp * 64 + (lane & 28))), g1 = bf_hi(lds4(SM_GATE + 32 + warp * 64 + (lane & 28)));

        const int r = lane >> 2, cq = lane & 3;
        const bool no_prev = warp == 0 && tile < 2, low = cq < 2;
        const bool le0 = 2 * cq <= r, le1 = 2 * cq + 1 <= r;
        const uint32_t mle = (le0 ? 0xFFFFu : 0u) | (le1 ? 0xFFFF0000u : 0u);
        const float scl = 0.22360679774997896f * 1.4426950408889634f;
        uint32_t pl[4], ph[4];
        {
            float sl[4][4], sh[4][4], sp[4][4];
            auto exchange = [&]() {
            TSA(warp == 1 ? 26 : 63);
            bar_sync(6 + wg, 128);
            if (w4 == 0) bar_sync(8 + wg * 3, 64);
            {
                const uint4 a = lds16(pbuf), b = lds16(pbuf + 512), c = lds16(pbuf + 1024), d = lds16(pbuf + 1536), e = lds16(pbuf + 2048);
                kp[0] = a.x; kp[1] = a.y; kp[3] = a.z; kp[4] = a.w; kp[5] = b.x; kp[6] = b.y; kp[8] = b.z; kp[9] = b.w;
                kp[2] = c.x; kp[7] = c.y; vp[0] = c.z; vp[1] = c.w; vp[2] = d.x; vp[3] = d.y; vp[4] = d.z; vp[5] = d.w;
                vp[6] = e.x; vp[7] = e.y; vp[8] = e.z; vp[9] = e.w;
            }
            TSA(warp == 0 ? 3 : warp == 4 ? 19 : warp == 5 ? 27 : 63);
            };
            if (EXCH_FIRST) exchange();
#pragma unroll
            for (int h = 0; h < 4; h++) {
                const int ta = (h >> 1) * 5 + (h & 1) * 3, tc = (h >> 1) * 5 + 2;
                const uint32_t ml = low != (h & 1) ? ql[tc] : 0u, mh = low != (h & 1) ? qh[tc] : 0u;
#pragma unroll
                for (int e = 0; e < 4; e++) sl[h][e] = sh[h][e] = sp[h][e] = 0.f;
                mma16(sl[h], ql[ta], qh[ta], ql[ta + 1], qh[ta + 1], kl[ta], kl[ta + 1]);
                mma16(sh[h], ql[ta], qh[ta], ql[ta + 1], qh[ta + 1], kh[ta], kh[ta + 1]);
                mma8(sl[h], ml, mh, kl[tc]);
                mma8(sh[h], ml, mh, kh[tc]);
            }
            if (!EXCH_FIRST) exchange();
#pragma unroll
            for (int h = 0; h < 4; h++) {
                const int ta = (h >> 1) * 5 + (h & 1) * 3, tc = (h >> 1) * 5 + 2;
                mma16(sp[h], ql[ta], qh[ta], ql[ta + 1], qh[ta + 1], kp[ta], kp[ta + 1]);
                mma8(sp[h], low != (h & 1) ? ql[tc] : 0u, low != (h & 1) ? qh[tc] : 0u, kp[tc]);
            }
#pragma unroll
            for (int t = 0; t < 10; t++) vp[t] = movm(vp[t]);
#pragma unroll
            for (int h = 0; h < 4; h++) {
                if (no_prev) sp[h][0] = sp[h][1] = -1e9f / 0.22360679774997896f;
                const float a0 = le0 ? sl[h][0] : sp[h][0], a1 = le1 ? sl[h][1] : sp[h][1];
                const float b0 = le0 ? sh[h][2] : sl[h][2], b1 = le1 ? sh[h][3] : sl[h][3];
                float ma = fmaxf(a0, a1), mb = fmaxf(b0, b1);
                ma = fmaxf(ma, __shfl_xor_sync(0xffffffffu, ma, 1));
                mb = fmaxf(mb, __shfl_xor_sync(0xffffffffu, mb, 1));
                ma = fmaxf(ma, __shfl_xor_sync(0xffffffffu, ma, 2)) * -scl;
                mb = fmaxf(mb, __shfl_xor_sync(0xffffffffu, mb, 2)) * -scl;
                pl[h] = pack2(ex2(fmaf(a0, scl, ma)), ex2(fmaf(a1, scl, ma)));
                ph[h] = pack2(ex2(fmaf(b0, scl, mb)), ex2(fmaf(b1, scl, mb)));
            }
        }
        TSA(warp == 0 ? 4 : warp == 4 ? 20 : warp == 5 ? 28 : 63);
        uint32_t ol[10], oh[10];
        {
            uint32_t* const po = reinterpret_cast<uint32_t*>(sc + SC_O + warp * 160) + lane;
            const uint32_t ONES = 0x3F803F80u;
            float o[12][4];
#pragma unroll
            for (int hp = 0; hp < 2; hp++) {
#pragma unroll
                for (int h = hp * 2; h < hp * 2 + 2; h++) {
                    const int ta = (h >> 1) * 5 + (h & 1) * 3, tc = (h >> 1) * 5 + 2;
                    const bool mine = (lane < 16) != (h & 1);
                    const uint32_t a0 = pl[h] & mle, a1 = ph[h] & ~mle, a3 = ph[h] & mle, ap = pl[h] & ~mle;
#pragma unroll
                    for (int i = 0; i < 3; i++) o[h * 3 + i][0] = o[h * 3 + i][1] = o[h * 3 + i][2] = o[h * 3 + i][3] = 0.f;
                    mma16(o[h * 3 + 2], a0, a1, 0u, a3, mine ? vl[tc] : ONES, mine ? vh[tc] : ONES);
                    mma16(o[h * 3], a0, a1, 0u, a3, vl[ta], vh[ta]);
                    mma16(o[h * 3 + 1], a0, a1, 0u, a3, vl[ta + 1], vh[ta + 1]);
                    mma8(o[h * 3 + 2], ap, 0u, mine ? vp[tc] : ONES);
                    mma8(o[h * 3], ap, 0u, vp[ta]);
                    mma8(o[h * 3 + 1], ap, 0u, vp[ta + 1]);
                }
                if (hp && wg != (hg & 1)) bar_arrive(2, 256);
                const float (&oa)[4] = o[hp * 6 + 2], (&ob)[4] = o[hp * 6 + 5];
                const float hl = rcp(low ? ob[0] : oa[0]) * g0, hh = rcp(low ? ob[2] : oa[2]) * g1;
                const float gl = __shfl_xor_sync(0xffffffffu, hl, 2), gh = __shfl_xor_sync(0xffffffffu, hh, 2);
                const float ial = low ? gl : hl, iah = low ? gh : hh, ibl = low ? hl : gl, ibh = low ? hh : gh;
#pragma unroll
                for (int i = 0; i < 2; i++) {
                    ol[hp * 5 + i] = pack2(o[hp * 6 + i][0] * ial, o[hp * 6 + i][1] * ial);
                    oh[hp * 5 + i] = pack2(o[hp * 6 + i][2] * iah, o[hp * 6 + i][3] * iah);
                    ol[hp * 5 + 3 + i] = pack2(o[hp * 6 + 3 + i][0] * ibl, o[hp * 6 + 3 + i][1] * ibl);
                    oh[hp * 5 + 3 + i] = pack2(o[hp * 6 + 3 + i][2] * ibh, o[hp * 6 + 3 + i][3] * ibh);
                }
                ol[hp * 5 + 2] = pack2((low ? oa[0] : ob[0]) * gl, (low ? oa[1] : ob[1]) * gl);
                oh[hp * 5 + 2] = pack2((low ? oa[2] : ob[2]) * gh, (low ? oa[3] : ob[3]) * gh);
#pragma unroll
                for (int t = hp * 5; t < hp * 5 + 5; t++) {
                    st_relaxed4(po + t * 32, ol[t]);
                    st_relaxed4(po + 320 + t * 32, oh[t]);
                }
            }
        }
        TS(warp == 0 ? 5 : warp == 4 ? 21 : warp == 5 ? 29 : warp == 1 ? 31 : 63);
        const uint4* ow = sc + (SC_O + (hg & 1) * 640 - hg * SC_SIZE);
        if (wg != (hg & 1)) {
            mbar_wait(B_INIT, 0);
            mbar_wait(B_EMPTY + 3 * 8, 0);
            if (w4 < 2) bar_arrive(9, 256); else bar_sync(9, 256);
            if (w4 == 0) TS(wg ? 26 : 27);
            uint32_t ph = 0;
#pragma unroll 1
            for (int i = w4 + 1 + NRS; i < 8; i += 4) {
                const uint4* src = ow + src_of(i, hg) * SC_SIZE;
                const uint32_t buf = o_buf(i), chk = buf + lane * 132;
                if (i < 5 + NRS) {
                    while (__any_sync(0xffffffffu, ld_relaxed4(&src[(lane & 3) * 160 + 159].w) == SENT)) {}
                    if (w4) pace(clock(), w4 * O_DT - O_D);
                } else {
                    mbar_wait(B_OE + (i - 4) * 8, 0);
                }
                if (i == 1 + NRS) TS(wg ? 3 : 4);
                uint32_t c;
                do {
                    if (elect_one()) {
                        mbar_expect_tx(B_OT + w4 * 8, 10240);
                        bulk_load(buf, src, 10240, B_OT + w4 * 8);
                    }
                    mbar_wait(B_OT + w4 * 8, ph);
                    if (i == 1 + NRS && !ph) TS(wg ? 19 : 20);
                    ph ^= 1;
                    c = max(max(lds4(chk), lds4(chk + 4096)), lds4(chk + 6144));
                } while (__any_sync(0xffffffffu, c == SENT));
                if (lane == 0) mbar_arrive(B_G2 + i * 8);
                TS(32 + i);
            }
            return;
        }

        float oc[80];
        bar_arrive(9, 256);
        bar_sync(2, 256);
        mbar_wait(B_G2, 0);
        TS(w4 == 0 ? 6 : 63);
        wg_fence();
#pragma unroll
        for (int s = 0; s < 5; s++)
            wgmma_own(oc, ol[2 * s], oh[2 * s], ol[2 * s + 1], oh[2 * s + 1], desc_lo(wo_buf(0), 10240) + s * 128, s);
        wg_commit();
        mbar_wait(B_XS, 0);
        const int orow = p0 + wg * 64 + w4 * 16;
        const uint32_t tk1 = ~lds4(SM_KEY + 16 * 4) & 2047, tk2 = ~lds4(SM_KEY + 17 * 4) & 2047;
        const uint32_t sel1 = (tk1 & 1) == par ? (tk1 >> 1) - orow : 99, sel2 = (tk2 & 1) == par ? (tk2 >> 1) - orow : 99;
        const uint32_t n0 = pack2(1.f - g0, 1.f - g0), n1 = pack2(1.f - g1, 1.f - g1);
        const uint32_t stg = SM_OUT + w4 * 5120;
        const uint32_t m128 = keep(stg + (lane & 15) * 128 + (((lane >> 4) ^ (lane & 7)) << 4));
        const uint32_t m64 = keep(stg + 4096 + (lane & 15) * 64 + (((lane >> 4) ^ ((lane >> 1) & 3)) << 4));
        const uint32_t l128 = keep(stg + (lane >> 3) * 128 + (((lane & 7) ^ (lane >> 3)) << 4));
        const uint32_t l64 = keep(stg + 4096 + r * 64 + ((cq ^ (lane >> 3)) << 4));
        char* const o128 = reinterpret_cast<char*>(P.op) + keep(((orow + (lane >> 3)) * 2 + par) * 1280 + kba * 128 + (lane & 7) * 16);
        char* const o64 = reinterpret_cast<char*>(P.op) + keep(((orow + r) * 2 + par) * 1280 + kbr * 128 + odd * 64 + cq * 16);
        mbar_wait(B_INIT, 0);
        wg_wait<0>();
        if (leader) mbar_arrive(B_OE);
        {
            uint32_t af[NRS][20];
            uint32_t m;
            do {
#pragma unroll
                for (int i = 0; i < NRS; i++) {
                    const uint32_t* p = reinterpret_cast<const uint32_t*>(ow + src_of(i + 1, hg) * SC_SIZE + w4 * 160) + lane;
#pragma unroll
                    for (int t = 0; t < 20; t++) af[i][t] = ld_relaxed4(p + t * 32);
                }
                m = 0;
#pragma unroll
                for (int i = 0; i < NRS; i++)
#pragma unroll
                    for (int t = 0; t < 20; t++) m = max(m, af[i][t]);
            } while (__any_sync(0xffffffffu, m == SENT));
            mbar_wait(B_DF, 0);
#pragma unroll
            for (int i = 0; i < NRS; i++) {
                mbar_wait(B_G2 + 8 + i * 8, 0);
                TS(w4 == 0 ? (i ? 11 : 7) : 63);
                wg_fence();
#pragma unroll
                for (int s = 0; s < 5; s++)
                    wgmma_own(oc, af[i][2 * s], af[i][10 + 2 * s], af[i][2 * s + 1], af[i][11 + 2 * s], desc_lo(wo_buf(i + 1), 10240) + s * 128, 1);
                wg_commit();
            }
            if (NRS == 2) {
                wg_wait<1>();
                if (leader) mbar_arrive(B_OE + 8);
            }
        }
#pragma unroll 1
        for (int i = 1 + NRS; i < 8; i++) {
            const uint32_t ao = desc_lo(0, 128) + (o_buf(i) >> 4), wo = desc_lo(0, 10240) + (wo_buf(i) >> 4);
            mbar_wait(B_G2 + i * 8, 0);
            TS(w4 == 0 ? (i < 2 ? 6 + i : i < 7 ? 9 + i : 17) : 63);
            wg_fence();
#pragma unroll
            for (int s = 0; s < 5; s++) wgmma_out(oc, ao + s * 16, wo + s * 128, 1);
            wg_commit();
            if (i < 5) {
                wg_wait<1>();
                if (i > 1 && leader) mbar_arrive(B_OE - 8 + i * 8);
            }
        }
        TS(w4 == 0 ? 8 : 63);

        if (min(sel1, sel2) < 16) {
            mbar_wait(B_MOD, 0);
#pragma unroll 1
            for (int j = 0; j < 2; j++) {
                const uint32_t sel = j ? sel2 : sel1;
#pragma unroll
                for (int t = 0; t < 20; t++) {
                    const uint32_t u = lds4(SM_U + j * 320 + cq * 4 + (t < 16 ? odd * 64 + t * 16 : (odd ? 0 : 256) + (t - 16) * 16));
                    if (sel == r) nb[2 * t] = hadd2(nb[2 * t], u);
                    if (sel == r + 8) nb[2 * t + 1] = hadd2(nb[2 * t + 1], u);
                }
            }
        }
        wg_wait<0>();
        TS(w4 == 0 ? 9 : 63);
        const bool nan = oc[0] != oc[0] || oc[2] != oc[2];
#pragma unroll
        for (int part = 0; part < 3; part++) {
            const int s0 = part ? part * 4 - 4 : 8, ns = part ? 4 : 2;
#pragma unroll
            for (int i = 0; i < 4; i++) {
                if (i >= ns) break;
                const int s = s0 + i;
                const uint32_t y0 = hfma2(n0, nb[s * 4], pack2(oc[s * 8 + 0], oc[s * 8 + 1]));
                const uint32_t y1 = hfma2(n1, nb[s * 4 + 1], pack2(oc[s * 8 + 2], oc[s * 8 + 3]));
                const uint32_t y2 = hfma2(n0, nb[s * 4 + 2], pack2(oc[s * 8 + 4], oc[s * 8 + 5]));
                const uint32_t y3 = hfma2(n1, nb[s * 4 + 3], pack2(oc[s * 8 + 6], oc[s * 8 + 7]));
                asm volatile("stmatrix.sync.aligned.m8n8.x4.shared.b16 [%0], {%1,%2,%3,%4};"
                             ::"r"(((s < 8 ? m128 : m64) ^ ((s & 3) * 32)) + (s & 4) * 512 + rk), "r"(y0), "r"(y1), "r"(y2), "r"(y3) : "memory");
            }
            __syncwarp();
            uint4 v[4];
#pragma unroll
            for (int i = 0; i < 4; i++)
                if (i < ns) v[i] = lds16(!part ? l64 + i * 512 : (l128 ^ ((i & 1) * 64)) + i * 512 + s0 * 512);
#pragma unroll
            for (int i = 0; i < 4; i++)
                if (i < ns) *reinterpret_cast<uint4*>(!part ? o64 + i * 8 * 2560 : o128 + i * 4 * 2560 + s0 * 32) = v[i];
            if (part == 0) TS(w4 == 0 ? 1 : 63);
        }
        TS(w4 == 0 ? 10 : 63);
        if (lane == 0) mbar_arrive(B_DONE);
        uint32_t redo;
        asm volatile("{\n.reg .pred p, q;\nsetp.ne.u32 p, %1, 0;\nbar.cta.red.or.pred q, 10, 128, p;\nselp.u32 %0, 1, 0, q;\n}"
                     : "=r"(redo) : "r"((uint32_t)nan) : "memory");
        if (redo) {
            const int cb = hg >> 1;
#pragma unroll 1
            for (int i = 0; i < 8; i++) {
                if (leader) {
                    mbar_expect_tx(B_RE, 25600);
                    tma_3d(SM_W, &P.woa, B_RE, 0, i * 80, (cb * 5 + 1) >> 1);
                    tma_2d(SM_W + 20480, &P.wob, B_RE, cb * 160 + ((cb & 1) ? 0 : 128), i * 80);
                }
#pragma unroll 1
                for (int s = 0; s < 20; s++) {
                    const int w = w4 * 640 + s * 32 + lane;
                    uint32_t v, it = 0;
                    do {
                        v = ld_relaxed4(reinterpret_cast<const uint32_t*>(ow + i * SC_SIZE) + w);
                        if (++it > (1u << 22)) fault();
                    } while ((v >> 16) == 0xFFFFu || (v & 0xFFFFu) == 0xFFFFu);
                    sts4(SM_X + w * 4, v);
                }
                fence_async_smem();
                __syncwarp();
                bar_sync(10, 128);
                mbar_wait(B_RE, i & 1);
                wg_fence();
#pragma unroll
                for (int s = 0; s < 5; s++) wgmma_out(oc, desc_lo(SM_X, 128) + s * 16, desc_lo(SM_W, 10240) + s * 128, s || i);
                wg_commit();
                wg_wait<0>();
                bar_sync(10, 128);
            }
#pragma unroll
            for (int t = 0; t < 40; t++) {
                const int col = (t < 32 ? kba * 64 + (t >> 1) * 8 : kbr * 64 + odd * 32 + ((t - 32) >> 1) * 8) + cq * 2;
                *reinterpret_cast<uint32_t*>(P.op + ((orow + r + (t & 1) * 8) * 2 + par) * 640 + col) =
                    hfma2((t & 1) ? n1 : n0, nb[t], pack2(oc[2 * t], oc[2 * t + 1]));
            }
        }
    }
}

typedef CUresult (*EncodeFn)(CUtensorMap*, CUtensorMapDataType, cuuint32_t, void*, const cuuint64_t*, const cuuint64_t*,
                             const cuuint32_t*, const cuuint32_t*, CUtensorMapInterleave, CUtensorMapSwizzle,
                             CUtensorMapL2promotion, CUtensorMapFloatOOBfill);

void encode(EncodeFn fn, CUtensorMap* m, const void* ptr, int rank, const cuuint64_t* dims, const cuuint64_t* strides,
            const cuuint32_t* box, CUtensorMapSwizzle swz) {
    const cuuint32_t es[4] = {1, 1, 1, 1};
    fn(m, CU_TENSOR_MAP_DATA_TYPE_BFLOAT16, rank, const_cast<void*>(ptr), dims, strides, box, es,
       CU_TENSOR_MAP_INTERLEAVE_NONE, swz, CU_TENSOR_MAP_L2_PROMOTION_L2_128B, CU_TENSOR_MAP_FLOAT_OOB_FILL_NONE);
}

}

extern "C" void kernel_launch(void* const* d_in, const int* in_sizes, int n_in, void* d_out, int out_size) {
    (void)in_sizes; (void)n_in; (void)out_size;
    Params P;
    P.xp = (const __nv_bfloat16*)d_in[0];
    P.wp = (const __nv_bfloat16*)d_in[1];
    P.wop = (const __nv_bfloat16*)d_in[2];
    P.dp = (const __nv_bfloat16*)d_in[7];
    P.upp = (const __nv_bfloat16*)d_in[6];
    P.op = (__nv_bfloat16*)d_out;
    P.w_r = (const __nv_bfloat16*)d_in[4];
    P.gate_w = (const __nv_bfloat16*)d_in[8];

    void* fp = nullptr;
    cudaDriverEntryPointQueryResult st;
    cudaGetDriverEntryPoint("cuTensorMapEncodeTiled", &fp, cudaEnableDefault, &st);
    EncodeFn fn = (EncodeFn)fp;
    const cuuint64_t xd[3] = {640, 2, 1024}, xs[2] = {1280, 2560};
    const cuuint32_t bx[3] = {64, 1, 64}, bx2[3] = {64, 1, 128};
    encode(fn, &P.x2, d_in[0], 3, xd, xs, bx2, CU_TENSOR_MAP_SWIZZLE_128B);
    encode(fn, &P.x, d_in[0], 3, xd, xs, bx, CU_TENSOR_MAP_SWIZZLE_128B);
    const cuuint64_t wd[3] = {640, 640, 3}, ws[2] = {3840, 1280};
    const cuuint32_t bw[3] = {64, 32, 3}, bwr[3] = {16, 32, 3};
    encode(fn, &P.w, d_in[1], 3, wd, ws, bw, CU_TENSOR_MAP_SWIZZLE_128B);
    encode(fn, &P.wr, d_in[1], 3, wd, ws, bwr, CU_TENSOR_MAP_SWIZZLE_32B);
    const cuuint64_t ad[3] = {64, 640, 10}, as[2] = {1280, 128}, bd[2] = {640, 640};
    const cuuint32_t ba[3] = {64, 80, 2}, bb[2] = {32, 80};
    encode(fn, &P.woa, d_in[2], 3, ad, as, ba, CU_TENSOR_MAP_SWIZZLE_128B);
    encode(fn, &P.wob, d_in[2], 2, bd, as, bb, CU_TENSOR_MAP_SWIZZLE_128B);
    const cuuint64_t gd[2] = {1728, 640}, gs[1] = {3456}, dd[2] = {640, 1728};
    const cuuint32_t bg[2] = {64, 20}, bu[2] = {64, 160}, bdn[2] = {64, 16}, bxg[3] = {64, 1, 16};
    encode(fn, &P.xg, d_in[0], 3, xd, xs, bxg, CU_TENSOR_MAP_SWIZZLE_128B);
    encode(fn, &P.gate, d_in[5], 2, gd, gs, bg, CU_TENSOR_MAP_SWIZZLE_128B);
    encode(fn, &P.up, d_in[6], 2, gd, gs, bu, CU_TENSOR_MAP_SWIZZLE_128B);
    encode(fn, &P.down, d_in[7], 2, dd, as, bdn, CU_TENSOR_MAP_SWIZZLE_128B);

    cudaFuncSetAttribute(fused_kernel, cudaFuncAttributeMaxDynamicSharedMemorySize, SM_TOTAL);
    fused_kernel<<<NCTA + (MAPV == 3 ? 0 : NEXTRA), 512, SM_TOTAL, cudaStreamPerThread>>>(P);
}
```

```cpp
#include <cuda_runtime.h>
#include <cuda_bf16.h>
#include <cuda.h>
#include <stdint.h>

namespace {

constexpr int NCTA = 128, NEXTRA = 4;
constexpr int NFFN = 108;
constexpr uint32_t SENT = 0xFFFFFFFFu;

constexpr uint32_t SB = 1024;
constexpr uint32_t SM_W = SB;
constexpr uint32_t SM_X = SB + 122880;
constexpr uint32_t SM_F = SB + 192512;
constexpr uint32_t SM_HALO = SB + 212992;
constexpr uint32_t SM_BAR = SB + 223232;
constexpr uint32_t SM_PROF = SB + 223744;
constexpr uint32_t SM_KEY = SB + 224000;
constexpr uint32_t SM_RED = SB + 224128;
constexpr uint32_t SM_XS = SB + 226688;
constexpr uint32_t SM_SENT = SB + 227328;
constexpr uint32_t SM_U = SM_RED + 1920;
constexpr uint32_t SM_H = SM_RED + 1536;
constexpr uint32_t SM_GATE = SM_RED;
constexpr uint32_t SM_TOTAL = 232448;
constexpr uint32_t SM_HALO1 = SM_X + 32768;
constexpr uint32_t SM_UP = SM_W + 61440;
constexpr uint32_t SM_OUT = SM_W + 61440;

constexpr uint32_t B_XL0 = SM_BAR, B_FULL = SM_BAR + 8, B_GT = SM_BAR + 72, B_RG = SM_BAR + 80, B_RG2 = SM_BAR + 88,
                   B_XS = SM_BAR + 96, B_EMPTY = SM_BAR + 128, B_DONE = SM_BAR + 192, B_XE = SM_BAR + 200,
                   B_GUD = SM_BAR + 224, B_OE = SM_BAR + 232, B_OT = SM_BAR + 264, B_MOD = SM_BAR + 296,
                   B_GU = SM_BAR + 104, B_UP = SM_BAR + 112, B_RS = SM_BAR + 312, B_INIT = SM_BAR + 320,
                   B_RE = SM_BAR + 328, B_PUB = SM_BAR + 304, B_G2 = SM_BAR + 336, B_DF = SM_BAR + 400;

struct Params {
    CUtensorMap x, x2, w, wr, woa, wob, xg, gate, up, down, up2;
    __nv_bfloat16* op;
    const __nv_bfloat16 *xp, *wp, *dp, *upp, *wop, *w_r, *gate_w;
};

constexpr int SC_O = 0;
constexpr int SC_HALO = 1280;
constexpr int SC_GU = 1440;
constexpr int SC_Y = 1504;
constexpr int SC_SIZE = 1600;
__device__ __align__(128) uint4 g_sc[NCTA * SC_SIZE];
__device__ __align__(128) uint2 g_cand[NCTA];
__device__ __align__(16) uint32_t g_gate[2048];
__device__ __align__(128) unsigned g_cnt[64];
#define TS(i) do { } while (0)
#define TS2(i) do { } while (0)
#define TSX(i) do { } while (0)

#define TS5(i) do { } while (0)
__device__ __forceinline__ uint32_t smem_u32(const void* p) { return (uint32_t)__cvta_generic_to_shared(p); }
__device__ __forceinline__ void fault() { asm volatile("st.shared.u32 [%0], %0;" ::"r"(0x100001) : "memory"); }
__device__ __forceinline__ void mbar_init(uint32_t bar, uint32_t cnt) {
    asm volatile("mbarrier.init.shared::cta.b64 [%0], %1;" ::"r"(bar), "r"(cnt) : "memory");
}
__device__ __forceinline__ void mbar_expect_tx(uint32_t bar, uint32_t bytes) {
    asm volatile("mbarrier.arrive.expect_tx.shared::cta.b64 _, [%0], %1;" ::"r"(bar), "r"(bytes) : "memory");
}
__device__ __forceinline__ void mbar_arrive(uint32_t bar) {
    asm volatile("mbarrier.arrive.shared::cta.b64 _, [%0];" ::"r"(bar) : "memory");
}
__device__ __forceinline__ bool mbar_try(uint32_t bar, uint32_t parity) {
    uint32_t ok;
    asm volatile("{\n.reg .pred p;\nmbarrier.try_wait.parity.shared::cta.b64 p, [%1], %2;\nselp.u32 %0, 1, 0, p;\n}"
                 : "=r"(ok) : "r"(bar), "r"(parity) : "memory");
    return ok;
}
__device__ __forceinline__ void mbar_wait(uint32_t bar, uint32_t parity) {
    asm volatile("{\n.reg .pred p;\nAGAIN:\nmbarrier.try_wait.parity.shared::cta.b64 p, [%0], %1;\n@!p bra AGAIN;\n}"
                 ::"r"(bar), "r"(parity) : "memory");
}
__device__ __forceinline__ void tma_2d(uint32_t dst, const CUtensorMap* m, uint32_t bar, int c0, int c1) {
    asm volatile("cp.async.bulk.tensor.2d.shared::cluster.global.mbarrier::complete_tx::bytes [%0], [%1, {%3, %4}], [%2];"
                 ::"r"(dst), "l"(m), "r"(bar), "r"(c0), "r"(c1) : "memory");
}
__device__ __forceinline__ void bulk_load(uint32_t dst, const void* src, uint32_t bytes, uint32_t bar) {
    asm volatile("cp.async.bulk.shared::cluster.global.mbarrier::complete_tx::bytes [%0], [%1], %2, [%3];"
                 ::"r"(dst), "l"(src), "r"(bytes), "r"(bar) : "memory");
}
__device__ __forceinline__ void bulk_store(void* dst, uint32_t src, uint32_t bytes) {
    asm volatile("cp.async.bulk.global.shared::cta.bulk_group [%0], [%1], %2;" ::"l"(dst), "r"(src), "r"(bytes) : "memory");
}
__device__ __forceinline__ void tma_3d(uint32_t dst, const CUtensorMap* m, uint32_t bar, int c0, int c1, int c2) {
    asm volatile("cp.async.bulk.tensor.3d.shared::cluster.global.mbarrier::complete_tx::bytes [%0], [%1, {%3, %4, %5}], [%2];"
                 ::"r"(dst), "l"(m), "r"(bar), "r"(c0), "r"(c1), "r"(c2) : "memory");
}
__device__ __forceinline__ void fence_async_smem() { asm volatile("fence.proxy.async.shared::cta;" ::: "memory"); }
__device__ __forceinline__ void wg_fence() { asm volatile("wgmma.fence.sync.aligned;" ::: "memory"); }
__device__ __forceinline__ void wg_commit() { asm volatile("wgmma.commit_group.sync.aligned;" ::: "memory"); }
template <int N> __device__ __forceinline__ void wg_wait() { asm volatile("wgmma.wait_group.sync.aligned %0;" ::"n"(N) : "memory"); }
__device__ __forceinline__ void bar_sync(int id, int n) { asm volatile("bar.cta.sync %0, %1;" ::"r"(id), "r"(n) : "memory"); }
__device__ __forceinline__ void bar_arrive(int id, int n) { asm volatile("bar.cta.arrive %0, %1;" ::"r"(id), "r"(n) : "memory"); }

__device__ constexpr uint32_t desc_lo(uint32_t addr, uint32_t lbo) { return (addr >> 4) | ((lbo >> 4) << 16); }
__device__ __forceinline__ bool elect_one() {
    uint32_t p;
    asm volatile("{\n.reg .pred p;\nelect.sync _|p, 0xffffffff;\nselp.u32 %0, 1, 0, p;\n}" : "=r"(p));
    return p;
}
__device__ __forceinline__ uint32_t ld_relaxed4(const void* p) {
    uint32_t v;
    asm volatile("ld.relaxed.gpu.global.u32 %0, [%1];" : "=r"(v) : "l"(p) : "memory");
    return v;
}
__device__ __forceinline__ void st_relaxed4(void* p, uint32_t v) {
    asm volatile("st.relaxed.gpu.global.u32 [%0], %1;" ::"l"(p), "r"(v) : "memory");
}
template <int N = 1>
__device__ __forceinline__ void red_inc(unsigned* p, unsigned after) {
    asm volatile("red.relaxed.gpu.global.add.u32 [%0], %2;" ::"l"(p), "r"(after), "n"(N) : "memory");
}
__device__ __forceinline__ uint32_t lds4(uint32_t a) {
    uint32_t v;
    asm volatile("ld.shared.u32 %0, [%1];" : "=r"(v) : "r"(a) : "memory");
    return v;
}
__device__ __forceinline__ float2 lds8f(uint32_t a) {
    float2 v;
    asm volatile("ld.shared.v2.f32 {%0, %1}, [%2];" : "=f"(v.x), "=f"(v.y) : "r"(a) : "memory");
    return v;
}
__device__ __forceinline__ void sts4(uint32_t a, uint32_t v) { asm volatile("st.shared.u32 [%0], %1;" ::"r"(a), "r"(v) : "memory"); }
__device__ __forceinline__ uint32_t hmul2(uint32_t a, uint32_t b) {
    uint32_t d;
    asm("mul.rn.bf16x2 %0, %1, %2;" : "=r"(d) : "r"(a), "r"(b));
    return d;
}
__device__ __forceinline__ uint32_t hadd2(uint32_t a, uint32_t b) {
    uint32_t d;
    asm("add.rn.bf16x2 %0, %1, %2;" : "=r"(d) : "r"(a), "r"(b));
    return d;
}
__device__ __forceinline__ uint32_t hfma2(uint32_t a, uint32_t b, uint32_t c) {
    uint32_t d;
    asm("fma.rn.bf16x2 %0, %1, %2, %3;" : "=r"(d) : "r"(a), "r"(b), "r"(c));
    return d;
}
__device__ __forceinline__ uint4 ld_relaxed16(const void* p) {
    uint4 v;
    asm volatile("{\n.reg .b128 t;\n.reg .b64 lo, hi;\nld.relaxed.gpu.global.b128 t, [%4];\nmov.b128 {lo, hi}, t;\n"
                 "mov.b64 {%0, %1}, lo;\nmov.b64 {%2, %3}, hi;\n}" : "=r"(v.x), "=r"(v.y), "=r"(v.z), "=r"(v.w) : "l"(p) : "memory");
    return v;
}
__device__ __forceinline__ void st_relaxed16(void* p, uint32_t a, uint32_t b, uint32_t c, uint32_t d) {
    uint64_t lo = (uint64_t)a | ((uint64_t)b << 32), hi = (uint64_t)c | ((uint64_t)d << 32);
    asm volatile("{\n.reg .b128 t;\nmov.b128 t, {%1, %2};\nst.relaxed.gpu.global.b128 [%0], t;\n}" ::"l"(p), "l"(lo), "l"(hi) : "memory");
}
__device__ __forceinline__ void st_relaxed8(void* p, uint32_t a, uint32_t b) {
    asm volatile("{\n.reg .b64 t;\nmov.b64 t, {%1, %2};\nst.relaxed.gpu.global.b64 [%0], t;\n}" ::"l"(p), "r"(a), "r"(b) : "memory");
}
__device__ __forceinline__ uint2 ld_relaxed8(const void* p) {
    uint2 v;
    asm volatile("{\n.reg .b64 t;\nld.relaxed.gpu.global.b64 t, [%2];\nmov.b64 {%0, %1}, t;\n}" : "=r"(v.x), "=r"(v.y) : "l"(p) : "memory");
    return v;
}
__device__ __forceinline__ uint4 ld_nc16(const void* p) {
    uint4 v;
    asm volatile("ld.global.L1::no_allocate.v4.u32 {%0, %1, %2, %3}, [%4];" : "=r"(v.x), "=r"(v.y), "=r"(v.z), "=r"(v.w) : "l"(p) : "memory");
    return v;
}
__device__ __forceinline__ uint2 ld_nc8(const void* p) {
    uint2 v;
    asm volatile("ld.global.nc.L1::no_allocate.v2.u32 {%0, %1}, [%2];" : "=r"(v.x), "=r"(v.y) : "l"(p));
    return v;
}
__device__ __forceinline__ uint4 lds16(uint32_t a) {
    uint4 v;
    asm volatile("ld.shared.v4.u32 {%0, %1, %2, %3}, [%4];" : "=r"(v.x), "=r"(v.y), "=r"(v.z), "=r"(v.w) : "r"(a) : "memory");
    return v;
}
__device__ __forceinline__ void sts16(uint32_t a, uint32_t x, uint32_t y, uint32_t z, uint32_t w) {
    asm volatile("st.shared.v4.u32 [%0], {%1, %2, %3, %4};" ::"r"(a), "r"(x), "r"(y), "r"(z), "r"(w) : "memory");
}
__device__ __forceinline__ uint32_t pack2(float lo, float hi) {
    uint32_t r;
    asm("cvt.rn.bf16x2.f32 %0, %1, %2;" : "=r"(r) : "f"(hi), "f"(lo));
    return r;
}
__device__ __forceinline__ uint32_t pack2v(float lo, float hi) {
    uint32_t r;
    asm volatile("cvt.rn.bf16x2.f32 %0, %1, %2;" : "=r"(r) : "f"(hi), "f"(lo));
    return r;
}
__device__ __forceinline__ float bf_lo(uint32_t u) { return __uint_as_float(u << 16); }
__device__ __forceinline__ float bf_hi(uint32_t u) { return __uint_as_float(u & 0xFFFF0000u); }
__device__ __forceinline__ float bf_round(float f) { return __bfloat162float(__float2bfloat16_rn(f)); }
__device__ __forceinline__ uint32_t prmt(uint32_t a, uint32_t sel) {
    uint32_t d;
    asm("prmt.b32 %0, %1, 0, %2;" : "=r"(d) : "r"(a), "r"(sel));
    return d;
}
__device__ __forceinline__ uint32_t movm(uint32_t a) {
    uint32_t d;
    asm volatile("movmatrix.sync.aligned.m8n8.trans.b16 %0, %1;" : "=r"(d) : "r"(a));
    return d;
}
__device__ __forceinline__ void mma16(float (&c)[4], uint32_t a0, uint32_t a1, uint32_t a2, uint32_t a3, uint32_t b0, uint32_t b1) {
    asm volatile("mma.sync.aligned.m16n8k16.row.col.f32.bf16.bf16.f32 {%0,%1,%2,%3}, {%4,%5,%6,%7}, {%8,%9}, {%0,%1,%2,%3};"
                 : "+f"(c[0]), "+f"(c[1]), "+f"(c[2]), "+f"(c[3]) : "r"(a0), "r"(a1), "r"(a2), "r"(a3), "r"(b0), "r"(b1));
}
__device__ __forceinline__ void mma8(float (&c)[4], uint32_t a0, uint32_t a1, uint32_t b0) {
    asm volatile("mma.sync.aligned.m16n8k8.row.col.f32.bf16.bf16.f32 {%0,%1,%2,%3}, {%4,%5}, {%6}, {%0,%1,%2,%3};"
                 : "+f"(c[0]), "+f"(c[1]), "+f"(c[2]), "+f"(c[3]) : "r"(a0), "r"(a1), "r"(b0));
}
__device__ __forceinline__ float ex2(float x) { float y; asm("ex2.approx.ftz.f32 %0, %1;" : "=f"(y) : "f"(x)); return y; }
__device__ __forceinline__ float rcp(float x) { float y; asm("rcp.approx.ftz.f32 %0, %1;" : "=f"(y) : "f"(x)); return y; }
__device__ __forceinline__ float sigmoidf(float z) { return rcp(1.0f + ex2(z * -1.4426950408889634f)); }
__device__ __forceinline__ float u2f(uint32_t u) { return __uint_as_float(u); }
__device__ __forceinline__ uint32_t f2u(float f) { return __float_as_uint(f); }

__device__ __forceinline__ void wgmma_main(float (&d)[96], uint32_t a, uint32_t b, int scale_d) {
    asm volatile("{\n.reg .pred p;\n.reg .b64 da, db;\nsetp.ne.b32 p, %98, 0;\n"
        "mov.b64 da, {%96, 0x40000040};\nmov.b64 db, {%97, 0x40000040};\n"
        "wgmma.mma_async.sync.aligned.m64n192k16.f32.bf16.bf16 "
        "{%0, %1, %2, %3, %4, %5, %6, %7, %8, %9, %10, %11, %12, %13, %14, %15, "
        "%16, %17, %18, %19, %20, %21, %22, %23, %24, %25, %26, %27, %28, %29, %30, %31, "
        "%32, %33, %34, %35, %36, %37, %38, %39, %40, %41, %42, %43, %44, %45, %46, %47, "
        "%48, %49, %50, %51, %52, %53, %54, %55, %56, %57, %58, %59, %60, %61, %62, %63, "
        "%64, %65, %66, %67, %68, %69, %70, %71, %72, %73, %74, %75, %76, %77, %78, %79, "
        "%80, %81, %82, %83, %84, %85, %86, %87, %88, %89, %90, %91, %92, %93, %94, %95}, "
        "da, db, p, 1, 1, 0, 1;\n}\n"
        : "+f"(d[0]), "+f"(d[1]), "+f"(d[2]), "+f"(d[3]), "+f"(d[4]), "+f"(d[5]), "+f"(d[6]), "+f"(d[7]),
          "+f"(d[8]), "+f"(d[9]), "+f"(d[10]), "+f"(d[11]), "+f"(d[12]), "+f"(d[13]), "+f"(d[14]), "+f"(d[15]),
          "+f"(d[16]), "+f"(d[17]), "+f"(d[18]), "+f"(d[19]), "+f"(d[20]), "+f"(d[21]), "+f"(d[22]), "+f"(d[23]),
          "+f"(d[24]), "+f"(d[25]), "+f"(d[26]), "+f"(d[27]), "+f"(d[28]), "+f"(d[29]), "+f"(d[30]), "+f"(d[31]),
          "+f"(d[32]), "+f"(d[33]), "+f"(d[34]), "+f"(d[35]), "+f"(d[36]), "+f"(d[37]), "+f"(d[38]), "+f"(d[39]),
          "+f"(d[40]), "+f"(d[41]), "+f"(d[42]), "+f"(d[43]), "+f"(d[44]), "+f"(d[45]), "+f"(d[46]), "+f"(d[47]),
          "+f"(d[48]), "+f"(d[49]), "+f"(d[50]), "+f"(d[51]), "+f"(d[52]), "+f"(d[53]), "+f"(d[54]), "+f"(d[55]),
          "+f"(d[56]), "+f"(d[57]), "+f"(d[58]), "+f"(d[59]), "+f"(d[60]), "+f"(d[61]), "+f"(d[62]), "+f"(d[63]),
          "+f"(d[64]), "+f"(d[65]), "+f"(d[66]), "+f"(d[67]), "+f"(d[68]), "+f"(d[69]), "+f"(d[70]), "+f"(d[71]),
          "+f"(d[72]), "+f"(d[73]), "+f"(d[74]), "+f"(d[75]), "+f"(d[76]), "+f"(d[77]), "+f"(d[78]), "+f"(d[79]),
          "+f"(d[80]), "+f"(d[81]), "+f"(d[82]), "+f"(d[83]), "+f"(d[84]), "+f"(d[85]), "+f"(d[86]), "+f"(d[87]),
          "+f"(d[88]), "+f"(d[89]), "+f"(d[90]), "+f"(d[91]), "+f"(d[92]), "+f"(d[93]), "+f"(d[94]), "+f"(d[95])
        : "r"(a), "r"(b), "r"(scale_d));
}

__device__ __forceinline__ void wgmma_rem(float (&d)[24], uint32_t a, uint32_t b, int scale_d) {
    asm volatile("{\n.reg .pred p;\n.reg .b64 da, db;\nsetp.ne.b32 p, %26, 0;\n"
        "mov.b64 da, {%24, 0x40000040};\nmov.b64 db, {%25, 0xC0000010};\n"
        "wgmma.mma_async.sync.aligned.m64n48k16.f32.bf16.bf16 "
        "{%0, %1, %2, %3, %4, %5, %6, %7, %8, %9, %10, %11, %12, %13, %14, %15, "
        "%16, %17, %18, %19, %20, %21, %22, %23}, "
        "da, db, p, 1, 1, 0, 1;\n}\n"
        : "+f"(d[0]), "+f"(d[1]), "+f"(d[2]), "+f"(d[3]), "+f"(d[4]), "+f"(d[5]), "+f"(d[6]), "+f"(d[7]),
          "+f"(d[8]), "+f"(d[9]), "+f"(d[10]), "+f"(d[11]), "+f"(d[12]), "+f"(d[13]), "+f"(d[14]), "+f"(d[15]),
          "+f"(d[16]), "+f"(d[17]), "+f"(d[18]), "+f"(d[19]), "+f"(d[20]), "+f"(d[21]), "+f"(d[22]), "+f"(d[23])
        : "r"(a), "r"(b), "r"(scale_d));
}

__device__ __forceinline__ void wgmma_out(float (&d)[80], uint32_t a, uint32_t b, int scale_d) {
    asm volatile("{\n.reg .pred p;\n.reg .b64 da, db;\nsetp.ne.b32 p, %82, 0;\n"
        "mov.b64 da, {%80, 0x50};\nmov.b64 db, {%81, 0x40000040};\n"
        "wgmma.mma_async.sync.aligned.m64n160k16.f32.bf16.bf16 "
        "{%0, %1, %2, %3, %4, %5, %6, %7, %8, %9, %10, %11, %12, %13, %14, %15, "
        "%16, %17, %18, %19, %20, %21, %22, %23, %24, %25, %26, %27, %28, %29, %30, %31, "
        "%32, %33, %34, %35, %36, %37, %38, %39, %40, %41, %42, %43, %44, %45, %46, %47, "
        "%48, %49, %50, %51, %52, %53, %54, %55, %56, %57, %58, %59, %60, %61, %62, %63, "
        "%64, %65, %66, %67, %68, %69, %70, %71, %72, %73, %74, %75, %76, %77, %78, %79}, "
        "da, db, p, 1, 1, 0, 1;\n}\n"
        : "+f"(d[0]), "+f"(d[1]), "+f"(d[2]), "+f"(d[3]), "+f"(d[4]), "+f"(d[5]), "+f"(d[6]), "+f"(d[7]),
          "+f"(d[8]), "+f"(d[9]), "+f"(d[10]), "+f"(d[11]), "+f"(d[12]), "+f"(d[13]), "+f"(d[14]), "+f"(d[15]),
          "+f"(d[16]), "+f"(d[17]), "+f"(d[18]), "+f"(d[19]), "+f"(d[20]), "+f"(d[21]), "+f"(d[22]), "+f"(d[23]),
          "+f"(d[24]), "+f"(d[25]), "+f"(d[26]), "+f"(d[27]), "+f"(d[28]), "+f"(d[29]), "+f"(d[30]), "+f"(d[31]),
          "+f"(d[32]), "+f"(d[33]), "+f"(d[34]), "+f"(d[35]), "+f"(d[36]), "+f"(d[37]), "+f"(d[38]), "+f"(d[39]),
          "+f"(d[40]), "+f"(d[41]), "+f"(d[42]), "+f"(d[43]), "+f"(d[44]), "+f"(d[45]), "+f"(d[46]), "+f"(d[47]),
          "+f"(d[48]), "+f"(d[49]), "+f"(d[50]), "+f"(d[51]), "+f"(d[52]), "+f"(d[53]), "+f"(d[54]), "+f"(d[55]),
          "+f"(d[56]), "+f"(d[57]), "+f"(d[58]), "+f"(d[59]), "+f"(d[60]), "+f"(d[61]), "+f"(d[62]), "+f"(d[63]),
          "+f"(d[64]), "+f"(d[65]), "+f"(d[66]), "+f"(d[67]), "+f"(d[68]), "+f"(d[69]), "+f"(d[70]), "+f"(d[71]),
          "+f"(d[72]), "+f"(d[73]), "+f"(d[74]), "+f"(d[75]), "+f"(d[76]), "+f"(d[77]), "+f"(d[78]), "+f"(d[79])
        : "r"(a), "r"(b), "r"(scale_d));
}

__device__ __forceinline__ void wgmma_own(float (&d)[80], uint32_t a0, uint32_t a1, uint32_t a2, uint32_t a3, uint32_t b, int scale_d) {
    asm volatile("{\n.reg .pred p;\n.reg .b64 db;\nsetp.ne.b32 p, %85, 0;\nmov.b64 db, {%84, 0x40000040};\n"
        "wgmma.mma_async.sync.aligned.m64n160k16.f32.bf16.bf16 "
        "{%0, %1, %2, %3, %4, %5, %6, %7, %8, %9, %10, %11, %12, %13, %14, %15, "
        "%16, %17, %18, %19, %20, %21, %22, %23, %24, %25, %26, %27, %28, %29, %30, %31, "
        "%32, %33, %34, %35, %36, %37, %38, %39, %40, %41, %42, %43, %44, %45, %46, %47, "
        "%48, %49, %50, %51, %52, %53, %54, %55, %56, %57, %58, %59, %60, %61, %62, %63, "
        "%64, %65, %66, %67, %68, %69, %70, %71, %72, %73, %74, %75, %76, %77, %78, %79}, "
        "{%80, %81, %82, %83}, db, p, 1, 1, 1;\n}\n"
        : "+f"(d[0]), "+f"(d[1]), "+f"(d[2]), "+f"(d[3]), "+f"(d[4]), "+f"(d[5]), "+f"(d[6]), "+f"(d[7]),
          "+f"(d[8]), "+f"(d[9]), "+f"(d[10]), "+f"(d[11]), "+f"(d[12]), "+f"(d[13]), "+f"(d[14]), "+f"(d[15]),
          "+f"(d[16]), "+f"(d[17]), "+f"(d[18]), "+f"(d[19]), "+f"(d[20]), "+f"(d[21]), "+f"(d[22]), "+f"(d[23]),
          "+f"(d[24]), "+f"(d[25]), "+f"(d[26]), "+f"(d[27]), "+f"(d[28]), "+f"(d[29]), "+f"(d[30]), "+f"(d[31]),
          "+f"(d[32]), "+f"(d[33]), "+f"(d[34]), "+f"(d[35]), "+f"(d[36]), "+f"(d[37]), "+f"(d[38]), "+f"(d[39]),
          "+f"(d[40]), "+f"(d[41]), "+f"(d[42]), "+f"(d[43]), "+f"(d[44]), "+f"(d[45]), "+f"(d[46]), "+f"(d[47]),
          "+f"(d[48]), "+f"(d[49]), "+f"(d[50]), "+f"(d[51]), "+f"(d[52]), "+f"(d[53]), "+f"(d[54]), "+f"(d[55]),
          "+f"(d[56]), "+f"(d[57]), "+f"(d[58]), "+f"(d[59]), "+f"(d[60]), "+f"(d[61]), "+f"(d[62]), "+f"(d[63]),
          "+f"(d[64]), "+f"(d[65]), "+f"(d[66]), "+f"(d[67]), "+f"(d[68]), "+f"(d[69]), "+f"(d[70]), "+f"(d[71]),
          "+f"(d[72]), "+f"(d[73]), "+f"(d[74]), "+f"(d[75]), "+f"(d[76]), "+f"(d[77]), "+f"(d[78]), "+f"(d[79])
        : "r"(a0), "r"(a1), "r"(a2), "r"(a3), "r"(b), "r"(scale_d));
}

__device__ __forceinline__ void wgmma_vec(float (&d)[8], uint32_t a, uint32_t b, int scale_d) {
    asm volatile("{\n.reg .pred p;\n.reg .b64 da, db;\nsetp.ne.b32 p, %10, 0;\n"
        "mov.b64 da, {%8, 0x40000040};\nmov.b64 db, {%9, 0x14};\n"
        "wgmma.mma_async.sync.aligned.m64n16k16.f32.bf16.bf16 {%0, %1, %2, %3, %4, %5, %6, %7}, da, db, p, 1, 1, 1, 0;\n}\n"
        : "+f"(d[0]), "+f"(d[1]), "+f"(d[2]), "+f"(d[3]), "+f"(d[4]), "+f"(d[5]), "+f"(d[6]), "+f"(d[7])
        : "r"(a), "r"(b), "r"(scale_d));
}

#define TSA(i) do { } while (0)
#define MAP_TILE(b) ((((b) >> 1) & 14) | ((b) & 1))
#define MAP_HG(b) (((b) >> 4 & 14) | ((b) >> 1 & 1))
#define SRCV 3
#define L1_D 300
#define L0_D 300
#define F1_D 0
#define F0_D 450
#define HALFV 0
#define HALF (int)(HALFV == 0 ? bid >> 1 & 1 : HALFV == 1 ? (bid >> 1 ^ bid) & 1 : (bid >> 1 ^ bid >> 4) & 1)
#define FFV 2
#define DFV 0
#define OEV 1
#define B_OFF 0
#define W_S0 2
#define E_V 0
#define MAPV 4
#define GW 0
#define GU_DS (GU_DT * 7 / 11)
#define GU_ST 90
#define X_OFF 350
#define RW_REG 0
#define P2W 4
#define RES_V 2
#define Y2_T 17000
#define ENT_V 0
#define TPF 1
#define SKEW 4
#define PACE 500
#define PACE_W0 (-600)
#define PACE_A 250
#define PACE_B 450
#define RG_ORDER 0x24130
#define GU_T0 3600
#define GU_DT 750
#define RS_T0 9000
#define RS_DT 120
#define EXCH_FIRST 1
#define HALO_D 450
#define PF_UP 4200
#define O_D 0
#define O_DT 300
#define PF_DN 4200
#define PF_DT 450
#define GX_NS 200
#define NRS 1
#define C5_D 0
#define C6_D 100
#define PF_N 4
#define PF_0 4
#define EPF_N 15
#define EPF_M 15
#define EPF_T 900
#define RG1_T0 1700
#define RG1_DT 200
#define RW1_T 0
#define Y_T 15800
#define GL_T 0
#define DN_T0 500
#define DN_DT 68
#define DN_T1 100000
#define DN_D1 45
#define DN_R 5
#define H_T 13500
#define HS_T 13500
#define GL_N 16
#define C1_T 0
#define C0_T 0
#define RS_N 10
#define SP_W 1
#define PF2_N 0
#define C2_T 0
#define C3_T 0
#define C4_T 0
#define EPF_G 0
#define EPF_H 0
#define UPF 0
#define UPF_D 700
#define UPF_T 3200
#define UPF_S 90
#define RS_E 0
#define RS_D 0
#define GL15 1
#define RS_S 0
#define CAND_T 9000

__device__ __forceinline__ uint32_t keep(uint32_t v) { return __shfl_xor_sync(0xffffffffu, v, 0); }
__device__ __forceinline__ uint32_t ukeep(uint32_t v) { return __shfl_sync(0xffffffffu, v, 0); }
__device__ __forceinline__ void ldsm2(uint32_t* d, uint32_t a) {
    asm volatile("ldmatrix.sync.aligned.m8n8.x4.shared.b16 {%0,%1,%2,%3}, [%8];\nldmatrix.sync.aligned.m8n8.x4.shared.b16 {%4,%5,%6,%7}, [%9];"
                 : "=r"(d[0]), "=r"(d[1]), "=r"(d[2]), "=r"(d[3]), "=r"(d[4]), "=r"(d[5]), "=r"(d[6]), "=r"(d[7])
                 : "r"(a), "r"(a ^ 32) : "memory");
}
__device__ __forceinline__ void ldsm_t(uint32_t (&d)[4], uint32_t a) {
    asm volatile("ldmatrix.sync.aligned.m8n8.x4.trans.shared.b16 {%0,%1,%2,%3}, [%4];"
                 : "=r"(d[0]), "=r"(d[1]), "=r"(d[2]), "=r"(d[3]) : "r"(a) : "memory");
}
template <bool SWP, int SEG, int E>
__device__ __forceinline__ void pack_blocks(uint32_t (&d)[10], const float (&am)[96], const float (&ar)[24]) {
#pragma unroll
    for (int t = 0; t < 10; t++) {
        const float* p = (SWP ? t < 2 : t >= 8) ? ar + (SEG * 2 + (t & 1)) * 4 + E : am + (SEG * 8 + t - (SWP ? 2 : 0)) * 4 + E;
        d[t] = pack2v(p[0], p[1]);
    }
}
__device__ __forceinline__ int src_of(int i, int hg) { return i == 0 ? hg : i > 3 ? 2 * i - 7 - (hg & 1) : 2 * (i - (i <= (hg >> 1))) + (hg & 1); }

__device__ __forceinline__ uint32_t o_buf(int i) { return __byte_perm(0xD199ADA3u, 0xC7BDu, i - 1 - NRS | 0x7770) << 10; }
__device__ constexpr uint32_t wo_buf(int i) { return SM_W + ((0x10342103u >> i * 4) & 7) * 30720; }

template <int N>
__device__ __forceinline__ void poll(uint4 (&a)[N], const uint4* p, int stride) {
    bool bad;
    do {
        bad = false;
#pragma unroll
        for (int s = 0; s < N; s++) a[s] = ld_relaxed16(p + s * stride);
#pragma unroll
        for (int s = 0; s < N; s++) bad |= a[s].w == SENT;
    } while (__any_sync(0xffffffffu, bad));
}
__device__ __forceinline__ void pace(unsigned t0, int t) {
    asm volatile("{\n.reg .pred p;\n.reg .s32 d;\nAGAIN:\nmov.u32 d, %%clock;\nsub.s32 d, d, %0;\nsetp.lt.s32 p, d, 0;\n"
                 "@p nanosleep.u32 20;\n@p bra AGAIN;\n}" ::"r"(t0 + t) : "memory");
}
__device__ __forceinline__ void l2_prefetch(const void* p) { asm volatile("prefetch.global.L2 [%0];" ::"l"(p) : "memory"); }

template <int N>
__device__ __forceinline__ bool landed(const uint4* w, int lane) {
    uint32_t a = 0;
#pragma unroll
    for (int i = 0; i < N; i++) a ^= w[i].w;
    return __ballot_sync(0xffffffffu, lane == 0 || a == 0) && lane == 0;
}
__device__ __forceinline__ void swiglu(const uint4 (&a)[4], uint32_t dst, uint32_t stride) {
    const float g0 = bf_round((u2f(a[0].x) + u2f(a[1].x)) + (u2f(a[2].x) + u2f(a[3].x)));
    const float g1 = bf_round((u2f(a[0].y) + u2f(a[1].y)) + (u2f(a[2].y) + u2f(a[3].y)));
    const float u0 = bf_round((u2f(a[0].z) + u2f(a[1].z)) + (u2f(a[2].z) + u2f(a[3].z)));
    const float u1 = bf_round((u2f(a[0].w) + u2f(a[1].w)) + (u2f(a[2].w) + u2f(a[3].w)));
    const uint32_t h = pack2(bf_round(g0 * sigmoidf(g0)) * u0, bf_round(g1 * sigmoidf(g1)) * u1);
    asm volatile("st.shared.u16 [%0], %2;\nst.shared.u16 [%1], %3;" ::"r"(dst), "r"(dst + stride), "h"((uint16_t)h), "h"((uint16_t)(h >> 16)) : "memory");
}
template <int N>
__device__ __forceinline__ float4 vec_mma(const uint4 (&w)[N], const uint32_t* x, uint32_t sel) {
    float c[4][4] = {};
    const uint32_t s[4] = {sel, sel >> 16, sel + ((sel & 0x10101010u) >> 3) * 17, (sel + ((sel & 0x10101010u) >> 3) * 17) >> 16};
#pragma unroll
    for (int i = 0; i < N; i++)
        mma16(c[i & 3], w[i].x, w[i].y, w[i].z, w[i].w, prmt(x[i >> 1], s[(i & 1) * 2]), prmt(x[i >> 1], s[(i & 1) * 2 + 1]));
    return make_float4((c[0][0] + c[1][0]) + (c[2][0] + c[3][0]), (c[0][1] + c[1][1]) + (c[2][1] + c[3][1]),
                       (c[0][2] + c[1][2]) + (c[2][2] + c[3][2]), (c[0][3] + c[1][3]) + (c[2][3] + c[3][3]));
}

__global__ void __launch_bounds__(512, 1) fused_kernel(const __grid_constant__ Params P) {
    extern __shared__ __align__(1024) uint8_t smem_raw[];
    const unsigned t_start = clock();
    const int tid = threadIdx.x, lane = tid & 31;
    unsigned sm, bid;
    asm("mov.u32 %0, %%smid;" : "=r"(sm));
    const CUtensorMap* mx = &P.x;
    asm volatile("" : "+l"(mx));
    if ((unsigned)(tid - 480) < EPF_N) l2_prefetch(P.wp + (tid * 132 + sm) * 64 - 480 * 132 * 64);
    const int warp = __shfl_sync(0xffffffffu, threadIdx.x >> 5, 0);
    constexpr uint32_t rk = 0;
    asm("{\n.reg .pred p;\n.reg .b32 t, u;\nshr.u32 t, %1, 1;\nmad.lo.s32 u, t, 14, -928;\nmad.lo.s32 t, t, 37, -925;\nmax.s32 t, t, 0;\n"
        "shr.u32 t, t, 7;\nand.b32 t, t, 14;\nsetp.ge.u32 p, %1, 124;\nselp.b32 t, u, t, p;\nadd.s32 %0, %1, t;\n}" : "=r"(bid) : "r"(sm));
    const int hg = MAP_HG(bid), par = bid & 1, p0 = (MAP_TILE(bid) >> 1) * 128;
    const bool swp = (hg & 3) == 3;
    const int wcm = hg * 80 + (swp ? 16 : 0), wcr = hg * 80 + (swp ? 0 : 64);
    if (warp == 0) {
        if (elect_one()) {
#pragma unroll
            for (int i = 0; i < 4; i++) mbar_init(SM_BAR + i * 8, 1);
            asm volatile("fence.mbarrier_init.release.cluster;" ::: "memory");
            if (bid < NCTA) {
                mbar_expect_tx(B_FULL, 15360 + 8192);
                tma_3d(SM_X + 8192, mx, B_FULL, 0, par, p0 + 64);
                tma_3d(SM_W, mx + 2, B_FULL, wcm, 0, 0);
                tma_3d(SM_W + 12288, mx + 3, B_FULL, wcr, 0, 0);
                TS(40);
                mbar_expect_tx(B_XL0, 8192);
                tma_3d(SM_X, mx, B_XL0, 0, par, p0);
                mbar_expect_tx(B_FULL + 8, 15360);
                tma_3d(SM_W + 15360, mx + 2, B_FULL + 8, wcm, 32, 0);
                tma_3d(SM_W + 15360 + 12288, mx + 3, B_FULL + 8, wcr, 32, 0);
            }
        }
    }
    if ((unsigned)(warp - 1) < 6 && elect_one()) {
#pragma unroll
        for (int i = 0; i < 4; i++) mbar_init(SM_BAR + warp * 32 + i * 8, warp < 4 ? 1 : warp < 6 ? 2 : 4);
        asm volatile("fence.mbarrier_init.release.cluster;" ::: "memory");
    }
    asm volatile("" : "+r"(bid));
    const int role = bid >= NCTA ? -1 : warp, e = (bid + 2) & 3;
    const int tile = MAP_TILE(bid), cid = tile * 8 + hg;
    uint4* const sc = g_sc + cid * SC_SIZE;
    __syncthreads();

    if (role < 0) {
        const int half = warp >> 3;
        if (!NFFN) {
            if (tid == 0) red_inc<NCTA / NEXTRA>(g_cnt, 0);
            return;
        }
        uint32_t wf[DN_R][5][4], la[5];
        auto rows = [&](uint32_t l) {
#pragma unroll
            for (int i = 0; i < 5; i++) {
                const uint32_t c = (warp & 7) * 10 + 2 * i + (l >> 3 & 1);
                la[i] = SB + half * 20480 + (c >> 3) * 2048 + (l & 7) * 128 + (l >> 4) * 1024 + (((c ^ l) & 7) << 4);
            }
        };
        rows(lane);
        auto fetch = [&](int j, int n, uint32_t bar) {
#pragma unroll 1
            for (int h = 0; h < n; h++) {
                pace(t_start, min(DN_T0 + (j * 20 + h * 10 + warp) * DN_DT, DN_T1 + (j * 20 + h * 10 + warp) * DN_D1));
                tma_2d(SB + (j % 5) * 40960 + h * 20480 + warp * 2048, &P.down, bar, warp * 64, e * 272 + (j + h * 9) * 16);
            }
        };
        if (warp < 10 && elect_one()) {
            if (warp <= DN_R) mbar_expect_tx(B_FULL + warp * 8, warp < DN_R ? 40960 : (17 - 2 * DN_R) * 20480);
#pragma unroll 1
            for (int j = 0; j < 5; j++) fetch(j, 2, B_FULL + j * 8);
        }
        const uint32_t tag = (ukeep(ld_relaxed4(g_cnt)) * 8 + 2048) & 0xF800u;
#pragma unroll
        for (int j = 0; j < DN_R; j++) {
            uint32_t any = 0;
            mbar_wait(B_FULL + j * 8, 0);
#pragma unroll
            for (int i = 0; i < 5; i++) {
                ldsm_t(wf[j][i], la[i] + j * 40960);
                any ^= wf[j][i][3];
            }
            if (j < 4) {
                if (__syncthreads_count(any == 0) == 1000) fault();
                if (warp < 10 && elect_one()) fetch(j + 5, j < 3 ? 2 : 1, B_FULL + DN_R * 8);
                if (j == 0 && tid == 0) red_inc<NCTA / NEXTRA>(g_cnt, tag);
            }
            TSX(warp == 0 && j == 0 ? 0 : warp == 0 && j == 3 ? 1 : 63);
        }
        if (warp < 9) {
            pace(t_start, H_T - 1000);
            uint4 a[4];
            do {
                a[0] = ld_relaxed16(g_cand + lane * 2);
                a[1] = ld_relaxed16(g_cand + lane * 2 + 64);
            } while (__any_sync(0xffffffffu, ((a[0].x ^ tag) | (a[0].z ^ tag) | (a[1].x ^ tag) | (a[1].z ^ tag)) & 0xF800u));
            const int u = min(tid, 271), f = e * 272 + u;
            pace(t_start, H_T);
            TSX(warp == 0 ? 3 : 63);
            poll<4>(a, g_sc + (f >> 6) * 4 * SC_SIZE + SC_GU + (f & 63), SC_SIZE);
            TSX(warp == 0 ? 4 : warp == 8 ? 5 : 63);
            swiglu(a, SM_RED + (u >> 4) * 64 + (u & 6) * 4 + (u & 8) / 2 + (u & 1) * 2, 32);
        }
        rows(keep(lane));
        mbar_wait(B_FULL + DN_R * 8, 0);
        TSX(warp == 15 ? 2 : 63);
        __syncthreads();
        float c[5][4] = {};
#pragma unroll
        for (int j = 0; j < 9; j++) {
            if (j == 8 && half) break;
            const float2 b = lds8f(SM_RED + half * 576 + j * 64 + (lane & 7) * 8);
            if (j == 1) TSX(warp == 0 ? 6 : 63);
#pragma unroll
            for (int i = 0; i < 5; i++) {
                if (j >= DN_R) ldsm_t(wf[j % DN_R][i], la[i] + (j % 5) * 40960);
                mma16(c[i], wf[j % DN_R][i][0], wf[j % DN_R][i][1], wf[j % DN_R][i][2], wf[j % DN_R][i][3], f2u(b.x), f2u(b.y));
            }
        }
        const uint32_t ra = SB + 7 * 20480 + half * 5248 + (lane & 1) * 2624 + (warp & 7) * 320 + (lane & 2) * 16 + (lane >> 2) * 4;
#pragma unroll
        for (int i = 0; i < 5; i++) sts4(ra + i * 64, f2u((lane & 2) ? ((lane & 1) ? c[i][3] : c[i][2]) : ((lane & 1) ? c[i][1] : c[i][0])));
        TSX(warp == 0 ? 7 : 63);
        __syncthreads();
        if (warp < 10) {
            const uint32_t ya = SB + 7 * 20480 + (warp & 1) * 2624 + (warp >> 1) * 512 + lane * 16;
            const uint4 y0 = lds16(ya), y1 = lds16(ya + 5248);
            st_relaxed16(g_sc + (e * 5 + (warp >> 1)) * SC_SIZE + SC_Y + (tid & 63), f2u(u2f(y0.x) + u2f(y1.x)), f2u(u2f(y0.y) + u2f(y1.y)),
                         f2u(u2f(y0.z) + u2f(y1.z)), f2u(u2f(y0.w) + u2f(y1.w)));
        }
    } else if (role < 8) {
        asm volatile("setmaxnreg.inc.sync.aligned.u32 192;");
        const int wg = warp >> 2;
        const bool leader = (tid & 127) == 0;
        float am[96], ar[24];
        if (wg == 0) mbar_wait(B_XL0, 0);
        bool rel = false;
        uint32_t nb[40];
        const int odd = (hg >> 1) & 1, kba = ukeep(RES_V && wg != HALF ? 99 : ((hg >> 1) * 5 + 1) >> 1), kbr = ukeep(kba + 2 - odd * 3);
        const int kbs = wg ? -1 : (20 - SKEW) / 2;
        const uint32_t xrow = keep(SM_X + (warp * 16 + (lane & 15)) * 128 + (((lane >> 4) ^ (lane & 7)) << 4));
#pragma unroll 1
        for (int kb = 0; kb < 10; kb++) {
            const uint32_t fb = B_FULL + (kb & 3) * 16, wo = (kb & 3) * 1920, ph = (kb >> 2) & 1;
            const uint32_t xo = desc_lo(SM_X, 16) + wg * 512 + (kb & 3) * 1024;
#pragma unroll
            for (int h = 0; h < 2; h++) {
                mbar_wait(fb + h * 8, ph);
                if (kb == 0 && h == 0) TS(warp == 0 ? 0 : warp == 4 ? 16 : 63);
                TS2(warp == P2W ? kb * 2 + h : 63);
                if (RES_V == 2) {
                    const uint32_t xa = (xrow ^ h * 64) + (kb & 3) * 16384;
                    if (kb == kba) ldsm2(nb + h * 8, xa);
                    if (kb == kba + 1) ldsm2(nb + 16 + h * 8, xa);
                    if (h == 0 && kb == kbr) ldsm2(nb + 32, xa ^ (odd * 64));
                } else if (h == 0) {
                    const uint32_t xa = xrow + (kb & 3) * 16384;
                    if (kb == kba) { ldsm2(nb, xa); ldsm2(nb + 8, xa ^ 64); }
                    if (kb == kba + 1) { ldsm2(nb + 16, xa); ldsm2(nb + 24, xa ^ 64); }
                    if (kb == kbr) ldsm2(nb + 32, xa ^ (odd * 64));
                }
                wg_wait<1>();
                if (rel && (h == 0 || kb != kbs)) mbar_arrive(B_EMPTY + ((kb * 16 - 16) & 48) + h * 8);
                if (h == 0 && kb == kbs) {
                    wg_wait<0>();
                    if (rel) mbar_arrive(B_EMPTY + ((19 - SKEW) & 7) * 8);
                    bar_sync(5, 256);
                }
                wg_fence();
                wgmma_main(am, xo + h * 4, desc_lo(SM_W + h * 15360, 4096) + wo, h || kb);
                wgmma_rem(ar, xo + h * 4, desc_lo(SM_W + h * 15360 + 12288, 1024) + wo, h || kb);
                wgmma_main(am, xo + h * 4 + 2, desc_lo(SM_W + h * 15360 + 2048, 4096) + wo, 1);
                wgmma_rem(ar, xo + h * 4 + 2, desc_lo(SM_W + h * 15360 + 12288 + 512, 1024) + wo, 1);
                wg_commit();
            }
            rel = leader;
        }
        if (wg == 1) bar_arrive(5, 256);
        mbar_wait(B_XE + 16, 0);
        mbar_wait(B_RG2, 0);
        mbar_wait(B_EMPTY + 5 * 8, 1);
        wg_wait<0>();
        if (leader) mbar_arrive(B_EMPTY + 3 * 8);
        TS(warp == 0 ? 2 : warp == 4 ? 18 : 63);
        TS2(warp == 0 ? 41 : warp == 4 ? 40 : 63);

        uint32_t kl[10], kh[10], vl[10], vh[10], ql[10], qh[10], kp[10], vp[10];
        if (swp) {
            pack_blocks<true, 1, 2>(kh, am, ar);
            pack_blocks<true, 2, 2>(vh, am, ar);
        } else {
            pack_blocks<false, 1, 2>(kh, am, ar);
            pack_blocks<false, 2, 2>(vh, am, ar);
        }
        const int w4 = warp & 3;
        const uint32_t pbuf = (wg ? SM_HALO1 : SM_HALO) + w4 * 2560 + lane * 16;
        const uint32_t hbuf = warp == 3 ? SM_HALO1 + lane * 16 : pbuf + 2560;
        {
            const uint32_t ex[20] = {kh[0], kh[1], kh[3], kh[4], kh[5], kh[6], kh[8], kh[9], kh[2], kh[7],
                                     vh[0], vh[1], vh[2], vh[3], vh[4], vh[5], vh[6], vh[7], vh[8], vh[9]};
            if (warp == 7) {
                uint4* const hp = sc + SC_HALO + lane;
#pragma unroll
                for (int s = 0; s < 5; s++) st_relaxed16(hp + s * 32, ex[4 * s], ex[4 * s + 1], ex[4 * s + 2], ex[4 * s + 3]);
                bar_arrive(12, 64);
            } else {
#pragma unroll
                for (int s = 0; s < 5; s++) sts16(hbuf + s * 512, ex[4 * s], ex[4 * s + 1], ex[4 * s + 2], ex[4 * s + 3]);
            }
        }
        TS(warp == 7 ? 22 : warp == 3 ? 23 : 63);
        if (warp == 3) bar_arrive(11, 64);
        if (swp) {
            pack_blocks<true, 2, 0>(vl, am, ar);
            pack_blocks<true, 0, 0>(ql, am, ar);
            pack_blocks<true, 0, 2>(qh, am, ar);
            pack_blocks<true, 1, 0>(kl, am, ar);
        } else {
            pack_blocks<false, 2, 0>(vl, am, ar);
            pack_blocks<false, 0, 0>(ql, am, ar);
            pack_blocks<false, 0, 2>(qh, am, ar);
            pack_blocks<false, 1, 0>(kl, am, ar);
        }
#pragma unroll
        for (int t = 0; t < 10; t++) { vl[t] = movm(vl[t]); vh[t] = movm(vh[t]); }
        mbar_wait(B_RS, 0);
        mbar_wait(B_GT, 0);
        const float g0 = bf_hi(lds4(SM_GATE + warp * 64 + (lane & 28))), g1 = bf_hi(lds4(SM_GATE + 32 + warp * 64 + (lane & 28)));

        const int r = lane >> 2, cq = lane & 3;
        const bool no_prev = warp == 0 && tile < 2, low = cq < 2;
        const bool le0 = 2 * cq <= r, le1 = 2 * cq + 1 <= r;
        const uint32_t mle = (le0 ? 0xFFFFu : 0u) | (le1 ? 0xFFFF0000u : 0u);
        const float scl = 0.22360679774997896f * 1.4426950408889634f;
        uint32_t pl[4], ph[4];
        {
            float sl[4][4], sh[4][4], sp[4][4];
            auto exchange = [&]() {
            TSA(warp == 1 ? 26 : 63);
            bar_sync(6 + wg, 128);
            if (w4 == 0) bar_sync(8 + wg * 3, 64);
            {
                const uint4 a = lds16(pbuf), b = lds16(pbuf + 512), c = lds16(pbuf + 1024), d = lds16(pbuf + 1536), e = lds16(pbuf + 2048);
                kp[0] = a.x; kp[1] = a.y; kp[3] = a.z; kp[4] = a.w; kp[5] = b.x; kp[6] = b.y; kp[8] = b.z; kp[9] = b.w;
                kp[2] = c.x; kp[7] = c.y; vp[0] = c.z; vp[1] = c.w; vp[2] = d.x; vp[3] = d.y; vp[4] = d.z; vp[5] = d.w;
                vp[6] = e.x; vp[7] = e.y; vp[8] = e.z; vp[9] = e.w;
            }
            TSA(warp == 0 ? 3 : warp == 4 ? 19 : warp == 5 ? 27 : 63);
            };
            if (EXCH_FIRST) exchange();
#pragma unroll
            for (int h = 0; h < 4; h++) {
                const int ta = (h >> 1) * 5 + (h & 1) * 3, tc = (h >> 1) * 5 + 2;
                const uint32_t ml = low != (h & 1) ? ql[tc] : 0u, mh = low != (h & 1) ? qh[tc] : 0u;
#pragma unroll
                for (int e = 0; e < 4; e++) sl[h][e] = sh[h][e] = sp[h][e] = 0.f;
                mma16(sl[h], ql[ta], qh[ta], ql[ta + 1], qh[ta + 1], kl[ta], kl[ta + 1]);
                mma16(sh[h], ql[ta], qh[ta], ql[ta + 1], qh[ta + 1], kh[ta], kh[ta + 1]);
                mma8(sl[h], ml, mh, kl[tc]);
                mma8(sh[h], ml, mh, kh[tc]);
            }
            if (!EXCH_FIRST) exchange();
#pragma unroll
            for (int h = 0; h < 4; h++) {
                const int ta = (h >> 1) * 5 + (h & 1) * 3, tc = (h >> 1) * 5 + 2;
                mma16(sp[h], ql[ta], qh[ta], ql[ta + 1], qh[ta + 1], kp[ta], kp[ta + 1]);
                mma8(sp[h], low != (h & 1) ? ql[tc] : 0u, low != (h & 1) ? qh[tc] : 0u, kp[tc]);
            }
#pragma unroll
            for (int t = 0; t < 10; t++) vp[t] = movm(vp[t]);
#pragma unroll
            for (int h = 0; h < 4; h++) {
                if (no_prev) sp[h][0] = sp[h][1] = -1e9f / 0.22360679774997896f;
                const float a0 = le0 ? sl[h][0] : sp[h][0], a1 = le1 ? sl[h][1] : sp[h][1];
                const float b0 = le0 ? sh[h][2] : sl[h][2], b1 = le1 ? sh[h][3] : sl[h][3];
                float ma = fmaxf(a0, a1), mb = fmaxf(b0, b1);
                ma = fmaxf(ma, __shfl_xor_sync(0xffffffffu, ma, 1));
                mb = fmaxf(mb, __shfl_xor_sync(0xffffffffu, mb, 1));
                ma = fmaxf(ma, __shfl_xor_sync(0xffffffffu, ma, 2)) * -scl;
                mb = fmaxf(mb, __shfl_xor_sync(0xffffffffu, mb, 2)) * -scl;
                pl[h] = pack2(ex2(fmaf(a0, scl, ma)), ex2(fmaf(a1, scl, ma)));
                ph[h] = pack2(ex2(fmaf(b0, scl, mb)), ex2(fmaf(b1, scl, mb)));
            }
        }
        TSA(warp == 0 ? 4 : warp == 4 ? 20 : warp == 5 ? 28 : 63);
        uint32_t ol[10], oh[10];
        {
            uint32_t* const po = reinterpret_cast<uint32_t*>(sc + SC_O + warp * 160) + lane;
            const uint32_t ONES = 0x3F803F80u;
            float o[12][4];
#pragma unroll
            for (int hp = 0; hp < 2; hp++) {
#pragma unroll
                for (int h = hp * 2; h < hp * 2 + 2; h++) {
                    const int ta = (h >> 1) * 5 + (h & 1) * 3, tc = (h >> 1) * 5 + 2;
                    const bool mine = (lane < 16) != (h & 1);
                    const uint32_t a0 = pl[h] & mle, a1 = ph[h] & ~mle, a3 = ph[h] & mle, ap = pl[h] & ~mle;
#pragma unroll
                    for (int i = 0; i < 3; i++) o[h * 3 + i][0] = o[h * 3 + i][1] = o[h * 3 + i][2] = o[h * 3 + i][3] = 0.f;
                    mma16(o[h * 3 + 2], a0, a1, 0u, a3, mine ? vl[tc] : ONES, mine ? vh[tc] : ONES);
                    mma16(o[h * 3], a0, a1, 0u, a3, vl[ta], vh[ta]);
                    mma16(o[h * 3 + 1], a0, a1, 0u, a3, vl[ta + 1], vh[ta + 1]);
                    mma8(o[h * 3 + 2], ap, 0u, mine ? vp[tc] : ONES);
                    mma8(o[h * 3], ap, 0u, vp[ta]);
                    mma8(o[h * 3 + 1], ap, 0u, vp[ta + 1]);
                }
                if (hp && wg != HALF) bar_arrive(2, 256);
                const float (&oa)[4] = o[hp * 6 + 2], (&ob)[4] = o[hp * 6 + 5];
                const float hl = rcp(low ? ob[0] : oa[0]) * g0, hh = rcp(low ? ob[2] : oa[2]) * g1;
                const float gl = __shfl_xor_sync(0xffffffffu, hl, 2), gh = __shfl_xor_sync(0xffffffffu, hh, 2);
                const float ial = low ? gl : hl, iah = low ? gh : hh, ibl = low ? hl : gl, ibh = low ? hh : gh;
#pragma unroll
                for (int i = 0; i < 2; i++) {
                    ol[hp * 5 + i] = pack2(o[hp * 6 + i][0] * ial, o[hp * 6 + i][1] * ial);
                    oh[hp * 5 + i] = pack2(o[hp * 6 + i][2] * iah, o[hp * 6 + i][3] * iah);
                    ol[hp * 5 + 3 + i] = pack2(o[hp * 6 + 3 + i][0] * ibl, o[hp * 6 + 3 + i][1] * ibl);
                    oh[hp * 5 + 3 + i] = pack2(o[hp * 6 + 3 + i][2] * ibh, o[hp * 6 + 3 + i][3] * ibh);
                }
                ol[hp * 5 + 2] = pack2((low ? oa[0] : ob[0]) * gl, (low ? oa[1] : ob[1]) * gl);
                oh[hp * 5 + 2] = pack2((low ? oa[2] : ob[2]) * gh, (low ? oa[3] : ob[3]) * gh);
#pragma unroll
                for (int t = hp * 5; t < hp * 5 + 5; t++) {
                    st_relaxed4(po + t * 32, ol[t]);
                    st_relaxed4(po + 320 + t * 32, oh[t]);
                }
            }
        }
        TS(warp == 0 ? 5 : warp == 4 ? 21 : warp == 5 ? 29 : warp == 1 ? 31 : 63);
        const unsigned t_pub = clock();
        if (lane == 0) mbar_arrive(B_PUB);
        const uint4* ow = sc + (SC_O + HALF * 640 - hg * SC_SIZE);
        mbar_wait(B_INIT, 0);
        if (wg != HALF) {
            mbar_wait(B_PUB, 0);
            const unsigned t0 = clock() + (wg ? F0_D : F1_D);
            uint32_t ph = 0;
#pragma unroll 1
            for (int i = w4 + 1 + NRS; i < 8; i += 4) {
                const uint4* src = ow + src_of(i, hg) * SC_SIZE;
                const uint32_t buf = o_buf(i), chk = buf + lane * 132;
                pace(t0, (i - 2) * O_DT);
                if (i > 4 + NRS) mbar_wait(B_DF, 0);
                if (i == 1 + NRS) TS(wg ? 3 : 4);
                uint32_t c;
                do {
                    if (elect_one()) {
                        mbar_expect_tx(B_OT + w4 * 8, 10240);
                        bulk_load(buf, src, 10240, B_OT + w4 * 8);
                    }
                    mbar_wait(B_OT + w4 * 8, ph);
                    if (i == 1 + NRS && !ph) TS(wg ? 19 : 20);
                    ph ^= 1;
                    c = max(max(lds4(chk), lds4(chk + 4096)), lds4(chk + 6144));
                } while (__any_sync(0xffffffffu, c == SENT));
                if (lane == 0) mbar_arrive(B_G2 + i * 8);
                TS(i == 2 ? 33 : 32 + i);
            }
            return;
        }

        float oc[80];
        uint32_t af[20];
        auto fetch = [&]() {
            const uint32_t* p = reinterpret_cast<const uint32_t*>(ow + src_of(1, hg) * SC_SIZE + w4 * 160) + lane;
#pragma unroll
            for (int t = 0; t < 20; t++) af[t] = ld_relaxed4(p + t * 32);
        };
        mbar_wait(B_XS, 0);
        const int orow = p0 + wg * 64 + w4 * 16;
        const uint32_t tk1 = ~lds4(SM_KEY + 16 * 4) & 2047, tk2 = ~lds4(SM_KEY + 17 * 4) & 2047;
        const uint32_t sel1 = (tk1 & 1) == par ? (tk1 >> 1) - orow : 99, sel2 = (tk2 & 1) == par ? (tk2 >> 1) - orow : 99;
        const uint32_t n0 = pack2(1.f - g0, 1.f - g0), n1 = pack2(1.f - g1, 1.f - g1);
        const uint32_t stg = SM_OUT + w4 * 5120;
        const uint32_t m128 = keep(stg + (lane & 15) * 128 + (((lane >> 4) ^ (lane & 7)) << 4));
        const uint32_t m64 = keep(stg + 4096 + (lane & 15) * 64 + (((lane >> 4) ^ ((lane >> 1) & 3)) << 4));
        const uint32_t l128 = keep(stg + (lane >> 3) * 128 + (((lane & 7) ^ (lane >> 3)) << 4));
        const uint32_t l64 = keep(stg + 4096 + r * 64 + ((cq ^ (lane >> 3)) << 4));
        char* const o128 = reinterpret_cast<char*>(P.op) + keep(((orow + (lane >> 3)) * 2 + par) * 1280 + kba * 128 + (lane & 7) * 16);
        char* const o64 = reinterpret_cast<char*>(P.op) + keep(((orow + r) * 2 + par) * 1280 + kbr * 128 + odd * 64 + cq * 16);
        mbar_wait(B_G2, 0);
        mbar_wait(B_G2 + 8, 0);
        const bool ff = FFV == 1 || (FFV == 2 && cid < NFFN) || (FFV == 3 && wg) || (FFV == 4 && (cid < NFFN || wg));
        if (ff) {
            pace(t_pub, wg ? L1_D : L0_D);
            fetch();
        }
        bar_sync(2, 256);
        TS(w4 == 0 ? 6 : 63);
        wg_fence();
#pragma unroll
        for (int s = 0; s < 5; s++)
            wgmma_own(oc, ol[2 * s], oh[2 * s], ol[2 * s + 1], oh[2 * s + 1], desc_lo(wo_buf(0), 10240) + s * 128, s);
        wg_commit();
        if (!ff) fetch();
        TS(w4 == 0 ? 28 : 63);
        if (DFV == 0) mbar_wait(B_DF, 0);
        for (;;) {
            uint32_t m = 0;
#pragma unroll
            for (int t = 0; t < 20; t++) m = max(m, af[t]);
            if (!__any_sync(0xffffffffu, m == SENT)) break;
            fetch();
        }
        TS(w4 == 0 ? 7 : 63);
        if (OEV == 0) {
            wg_wait<0>();
            if (leader) mbar_arrive(B_OE);
        }
        wg_fence();
#pragma unroll
        for (int s = 0; s < 5; s++)
            wgmma_own(oc, af[2 * s], af[10 + 2 * s], af[2 * s + 1], af[11 + 2 * s], desc_lo(wo_buf(1), 10240) + s * 128, 1);
        wg_commit();
        if (OEV == 1) {
            wg_wait<1>();
            if (leader) mbar_arrive(B_OE);
        }
        if (DFV == 1) mbar_wait(B_DF, 0);
#pragma unroll 1
        for (int i = 1 + NRS; i < 8; i++) {
            const uint32_t ao = desc_lo(0, 128) + (o_buf(i) >> 4), wo = desc_lo(0, 10240) + (wo_buf(i) >> 4);
            mbar_wait(B_G2 + i * 8, 0);
            TS(w4 == 0 ? (i < 2 ? 6 + i : i < 7 ? 9 + i : 17) : 63);
            wg_fence();
#pragma unroll
            for (int s = 0; s < 5; s++) wgmma_out(oc, ao + s * 16, wo + s * 128, 1);
            wg_commit();
            if (i < 4) {
                wg_wait<1>();
                if (i > 1 && leader) mbar_arrive(B_OE - 8 + i * 8);
            }
        }
        TS(w4 == 0 ? 8 : 63);

        if (min(sel1, sel2) < 16) {
            mbar_wait(B_MOD, 0);
#pragma unroll 1
            for (int j = 0; j < 2; j++) {
                const uint32_t sel = j ? sel2 : sel1;
#pragma unroll
                for (int t = 0; t < 20; t++) {
                    const uint32_t u = lds4(SM_U + j * 320 + cq * 4 + (t < 16 ? odd * 64 + t * 16 : (odd ? 0 : 256) + (t - 16) * 16));
                    if (sel == r) nb[2 * t] = hadd2(nb[2 * t], u);
                    if (sel == r + 8) nb[2 * t + 1] = hadd2(nb[2 * t + 1], u);
                }
            }
        }
        wg_wait<0>();
        TS(w4 == 0 ? 9 : 63);
        const bool nan = oc[0] != oc[0] || oc[2] != oc[2];
#pragma unroll
        for (int part = 0; part < 3; part++) {
            const int s0 = part ? part * 4 - 4 : 8, ns = part ? 4 : 2;
#pragma unroll
            for (int i = 0; i < 4; i++) {
                if (i >= ns) break;
                const int s = s0 + i;
                const uint32_t y0 = hfma2(n0, nb[s * 4], pack2(oc[s * 8 + 0], oc[s * 8 + 1]));
                const uint32_t y1 = hfma2(n1, nb[s * 4 + 1], pack2(oc[s * 8 + 2], oc[s * 8 + 3]));
                const uint32_t y2 = hfma2(n0, nb[s * 4 + 2], pack2(oc[s * 8 + 4], oc[s * 8 + 5]));
                const uint32_t y3 = hfma2(n1, nb[s * 4 + 3], pack2(oc[s * 8 + 6], oc[s * 8 + 7]));
                asm volatile("stmatrix.sync.aligned.m8n8.x4.shared.b16 [%0], {%1,%2,%3,%4};"
                             ::"r"(((s < 8 ? m128 : m64) ^ ((s & 3) * 32)) + (s & 4) * 512 + rk), "r"(y0), "r"(y1), "r"(y2), "r"(y3) : "memory");
            }
            __syncwarp();
            uint4 v[4];
#pragma unroll
            for (int i = 0; i < 4; i++)
                if (i < ns) v[i] = lds16(!part ? l64 + i * 512 : (l128 ^ ((i & 1) * 64)) + i * 512 + s0 * 512);
#pragma unroll
            for (int i = 0; i < 4; i++)
                if (i < ns) *reinterpret_cast<uint4*>(!part ? o64 + i * 8 * 2560 : o128 + i * 4 * 2560 + s0 * 32) = v[i];
            if (part == 0) TS(w4 == 0 ? 1 : 63);
        }
        TS(w4 == 0 ? 10 : 63);
        if (lane == 0) mbar_arrive(B_DONE);
        uint32_t redo;
        asm volatile("{\n.reg .pred p, q;\nsetp.ne.u32 p, %1, 0;\nbar.cta.red.or.pred q, 10, 128, p;\nselp.u32 %0, 1, 0, q;\n}"
                     : "=r"(redo) : "r"((uint32_t)nan) : "memory");
        if (redo) {
            const int cb = hg >> 1;
#pragma unroll 1
            for (int i = 0; i < 8; i++) {
                if (leader) {
                    mbar_expect_tx(B_RE, 25600);
                    tma_3d(SM_W, &P.woa, B_RE, 0, i * 80, (cb * 5 + 1) >> 1);
                    tma_2d(SM_W + 20480, &P.wob, B_RE, cb * 160 + ((cb & 1) ? 0 : 128), i * 80);
                }
#pragma unroll 1
                for (int s = 0; s < 20; s++) {
                    const int w = w4 * 640 + s * 32 + lane;
                    uint32_t v, it = 0;
                    do {
                        v = ld_relaxed4(reinterpret_cast<const uint32_t*>(ow + i * SC_SIZE) + w);
                        if (++it > (1u << 22)) fault();
                    } while ((v >> 16) == 0xFFFFu || (v & 0xFFFFu) == 0xFFFFu);
                    sts4(SM_X + w * 4, v);
                }
                fence_async_smem();
                __syncwarp();
                bar_sync(10, 128);
                mbar_wait(B_RE, i & 1);
                wg_fence();
#pragma unroll
                for (int s = 0; s < 5; s++) wgmma_out(oc, desc_lo(SM_X, 128) + s * 16, desc_lo(SM_W, 10240) + s * 128, s || i);
                wg_commit();
                wg_wait<0>();
                bar_sync(10, 128);
            }
#pragma unroll
            for (int t = 0; t < 40; t++) {
                const int col = (t < 32 ? kba * 64 + (t >> 1) * 8 : kbr * 64 + odd * 32 + ((t - 32) >> 1) * 8) + cq * 2;
                *reinterpret_cast<uint32_t*>(P.op + ((orow + r + (t & 1) * 8) * 2 + par) * 640 + col) =
                    hfma2((t & 1) ? n1 : n0, nb[t], pack2(oc[2 * t], oc[2 * t + 1]));
            }
        }
    } else if (role < 12) {
        asm volatile("setmaxnreg.dec.sync.aligned.u32 96;");
        const int t = tid - 256;
        uint32_t tag = ld_relaxed4(g_cnt);
        float gv = 0.f;
        int grow = hg * 16 + (t >> 3);
        mbar_wait(B_RG, 0);
        TS(warp == 8 ? 48 : 63);
        {
            float r0 = 0.f, r1 = 0.f, g0 = 0.f, g1 = 0.f;
            const uint32_t sw = (t >> 4) * 128 + (((t ^ (t >> 4)) & 7) << 4), hi = (t >> 3) & 1;
            mbar_wait(B_XL0, 0);
            tag = (tag * 8 + 2048) & 0xF800u;
            sts4(SM_KEY + 20 * 4, tag);
#pragma unroll 1
            for (int i = 0; i < 5; i++) {
                const int p = (RG_ORDER >> (i * 4)) & 7, kb = 2 * p + hi;
                mbar_wait(p < 3 ? B_FULL + (p & 1) * 32 : B_RG2, p == 2);
                if (p < 2) mbar_wait(B_FULL + p * 32 + 16, 0);
                const uint32_t xa = sw + (kb < 5 ? SM_X + (kb & 3) * 16384 + hg * 2048 : SM_HALO - 5 * 2048 + kb * 2048);
                const uint4 a = lds16(xa), b = lds16(xa + 1024);
                const uint4 w = lds16(SM_RED + p * 256 + (t & 15) * 16), v = lds16(SM_RED + 1280 + p * 256 + (t & 15) * 16);
                if (__ballot_sync(0xffffffffu, lane == 0 || a.w == b.w) && lane == 0 && p < 3) mbar_arrive(B_XE + p * 8);
                TS5(warp == 8 ? 51 + i : 63);
                const uint32_t as[4] = {a.x, a.y, a.z, a.w}, bs[4] = {b.x, b.y, b.z, b.w};
                const uint32_t ws[4] = {w.x, w.y, w.z, w.w}, vs[4] = {v.x, v.y, v.z, v.w};
#pragma unroll
                for (int e = 0; e < 4; e++) {
                    r0 = fmaf(bf_lo(as[e]), bf_lo(ws[e]), r0);
                    r1 = fmaf(bf_lo(bs[e]), bf_lo(ws[e]), r1);
                    g0 = fmaf(bf_lo(as[e]), bf_lo(vs[e]), g0);
                    g1 = fmaf(bf_lo(bs[e]), bf_lo(vs[e]), g1);
                    r0 = fmaf(bf_hi(as[e]), bf_hi(ws[e]), r0);
                    r1 = fmaf(bf_hi(bs[e]), bf_hi(ws[e]), r1);
                    g0 = fmaf(bf_hi(as[e]), bf_hi(vs[e]), g0);
                    g1 = fmaf(bf_hi(bs[e]), bf_hi(vs[e]), g1);
                }
            }
            const bool up = lane & 4;
            r0 = (hi ? r1 : r0) + __shfl_xor_sync(0xffffffffu, hi ? r0 : r1, 8);
            g0 = (hi ? g1 : g0) + __shfl_xor_sync(0xffffffffu, hi ? g0 : g1, 8);
            float r = (up ? g0 : r0) + __shfl_xor_sync(0xffffffffu, up ? r0 : g0, 4);
            r += __shfl_xor_sync(0xffffffffu, r, 2);
            r = bf_round(r + __shfl_xor_sync(0xffffffffu, r, 1));
            const int row = hg * 16 + (t >> 4) + hi * 8;
            const uint32_t u = f2u(r);
            if (!up) sts4(SM_KEY + (t >> 3) * 4, (((int)u < 0 ? ~u : u | 0x80000000u) & 0xFFFF0000u) | (2047 - (p0 + row) * 2 - par));
            gv = r;
            grow = row;
        }
        TS(warp == 8 ? 63 : 63);
        mbar_wait(B_RG2, 0);
        bar_sync(4, 128);
        if (warp == 8) {
            const uint32_t key = lds4(SM_KEY + (lane & 15) * 4);
            uint32_t k1 = __reduce_max_sync(0xffffffffu, key);
            uint32_t k2 = __reduce_max_sync(0xffffffffu, key == k1 ? 0u : key);
            if (elect_one()) {
                st_relaxed8(g_cand + cid, k1 | tag, k2 | tag);
                red_inc<MAPV == 3 ? 2 : 1>(g_cnt, tag);
            }
            TS(49);
        }
        if ((lane & 7) == 4) st_relaxed4(g_gate + tile * 128 + grow, f2u(bf_round(sigmoidf(gv))) | tag);
        const int cq = lane & 3, w4 = warp & 3;
        const uint32_t la = keep(cq * 256 + (((lane >> 2) ^ cq * 2) << 4));
        const uint32_t sel = keep(0x44444444u ^ (0x54u << (lane >> 2 & 1) * 8 + (lane & 16)));
        if (NFFN) {
            float4 d;
            uint4* dst;
            if (cid < NFFN) {
                float dg[8], du[8];
                mbar_wait(B_GU, 0);
                mbar_wait(B_XS, 0);
                TS(warp == 8 ? 50 : 63);
                if (GW & 1) mbar_wait(B_EMPTY + 3 * 8, 0);
                wg_fence();
#pragma unroll
                for (int i = 0; i < 10; i++) wgmma_vec(dg, desc_lo(SM_F + i * 2048, 16), desc_lo(SM_XS + i * 32, 16), i);
                wg_commit();
                mbar_wait(B_UP, 0);
                TS(warp == 10 ? 58 : 63);
                if (GW & 2) mbar_wait(B_EMPTY + 3 * 8, 0);
                wg_fence();
#pragma unroll
                for (int i = 0; i < 10; i++) wgmma_vec(du, desc_lo(SM_UP + i * 2048, 16), desc_lo(SM_XS + i * 32, 16), i);
                wg_commit();
                wg_wait<0>();
                if (lane == 0) mbar_arrive(B_GUD), mbar_arrive(B_DF);
                TS(warp == 8 ? 54 : warp == 10 ? 59 : 63);
                if (cq == 0) {
                    st_relaxed16(sc + SC_GU + w4 * 16 + (lane >> 2), f2u(dg[0]), f2u(dg[4]), f2u(du[0]), f2u(du[4]));
                    st_relaxed16(sc + SC_GU + w4 * 16 + 8 + (lane >> 2), f2u(dg[2]), f2u(dg[6]), f2u(du[2]), f2u(du[6]));
                }
            } else {
                uint4 wv[2][8], wr[4];
                mbar_wait(B_UP, 0);
                TS(warp == 10 ? 58 : 63);
                if (SP_W) mbar_wait(B_EMPTY + 3 * 8, 0);
#pragma unroll
                for (int i = 0; i < 8; i++) wv[i >> 2][4 + (i & 3)] = lds16((la ^ (i & 1) * 144) + SM_UP + w4 * 4096 + (i >> 1) * 1024);
                if (landed<4>(wv[0] + 4, lane) & landed<4>(wv[1] + 4, lane)) mbar_arrive(B_GUD);
                TS(warp == 8 ? 54 : 63);
                mbar_wait(B_GU, 0);
#pragma unroll
                for (int i = 0; i < 4; i++) wr[i] = lds16((la ^ (i & 1) * 144) + SM_F + 12288 + w4 * 2048 + (i >> 1) * 1024);
                mbar_wait(B_XS, 0);
                if (w4 == 0) {
                    uint4 pq[4];
                    pace(t_start, HS_T);
                    poll<4>(pq, g_sc + ((cid >> 1) * 4 - 148) * SC_SIZE + SC_GU + (cid & 1) * 32 + lane, SC_SIZE);
                    TS(warp == 8 ? 55 : 63);
                    swiglu(pq, SM_H + (lane & 6) * 8 + (lane >> 3) * 4 + (lane & 1) * 2, 64);
                }
                bar_sync(4, 128);
                TS(warp == 8 ? 57 : 63);
                const uint4 h = lds16(SM_H + (lane & 8) * 8 + cq * 16);
                const uint32_t hv[4] = {h.x, h.y, h.z, h.w}, hr[2] = {(w4 & 1) ? h.z : h.x, (w4 & 1) ? h.w : h.y};
                d = vec_mma<4>(wr, hr, sel);
                dst = g_sc + (cid * 5 - 520 + w4) * SC_SIZE + SC_Y + (lane & 1) * 32 + (lane >> 1);
                float c[2][2][4] = {};
                const uint32_t s2 = sel + ((sel & 0x10101010u) >> 3) * 17;
#pragma unroll
                for (int i = 7; i >= 0; i--) {
                    const uint32_t x0 = prmt(hv[i >> 1], (i & 1) ? s2 : sel), x1 = prmt(hv[i >> 1], ((i & 1) ? s2 : sel) >> 16);
#pragma unroll
                    for (int n = 0; n < 2; n++) {
                        if (i >= 4) wv[n][i - 4] = lds16((la ^ (i & 1) * 144) + SM_F - 6144 + w4 * 4096 + n * 2048 + (i >> 1) * 1024);
                        mma16(c[n][i & 1], wv[n][i].x, wv[n][i].y, wv[n][i].z, wv[n][i].w, x0, x1);
                    }
                }
#pragma unroll
                for (int n = 0; n < 2; n++)
                    st_relaxed16(dst + n * 16, f2u(c[n][0][0] + c[n][1][0]), f2u(c[n][0][1] + c[n][1][1]), f2u(c[n][0][2] + c[n][1][2]),
                                 f2u(c[n][0][3] + c[n][1][3]));
                dst += (4 - w4) * SC_SIZE + w4 * 8;
                TS(warp == 8 ? 30 : 63);
                if (lane == 0 && f2u(d.x) != SENT) mbar_arrive(B_DF);
                if (w4 & 1) {
                    sts16(SM_RED + 512 + (w4 & 2) * 256 + lane * 16, f2u(d.x), f2u(d.y), f2u(d.z), f2u(d.w));
                    bar_arrive(13 + (w4 >> 1), 64);
                } else {
                    bar_sync(13 + (w4 >> 1), 64);
                    const uint4 o = lds16(SM_RED + 512 + (w4 & 2) * 256 + lane * 16);
                    st_relaxed16(dst, f2u(d.x + u2f(o.x)), f2u(d.y + u2f(o.y)), f2u(d.z + u2f(o.z)), f2u(d.w + u2f(o.w)));
                }
            }
        } else {
            if (t < 4) mbar_arrive(B_GUD);
            if (t < 4) mbar_arrive(B_DF);
            mbar_wait(B_XS, 0);
        }
        TS(warp == 8 ? 51 : 63);
        const uint32_t k1 = lds4(SM_KEY + 16 * 4), k2 = lds4(SM_KEY + 17 * 4);
        const uint32_t mine = (tile >> 1) * 256 + HALF * 128 + par;
        const bool own1 = (~k1 & 0x781) == mine, own2 = (~k2 & 0x781) == mine;
        if ((own1 || own2) && NFFN) {
            const int rg = min(t / 40, 2), un = (hg >> 1) * 40 + t % 40, up = (hg >> 1) * 80 + min(t, 79);
            mbar_wait(B_RS, 0);
            pace(t_start, Y_T);
            TS(warp == 8 ? 60 : 63);
#pragma unroll 1
            for (int j = !own1; j <= own2; j++) {
                const uint4* p = g_sc + (rg * 5 + 20 + (un >> 5)) * SC_SIZE + SC_Y + j * 32 + (un & 31);
                float y[4];
                bool bad;
                do {
                    uint4 yp[7];
#pragma unroll
                    for (int i = 0; i < 7; i++) yp[i] = i < 6 || rg < 2 ? ld_relaxed16(p + i * 15 * SC_SIZE) : make_uint4(0, 0, 0, 0);
                    y[0] = y[1] = y[2] = y[3] = 0.f;
                    bad = false;
#pragma unroll
                    for (int i = 0; i < 7; i++) {
                        y[0] += u2f(yp[i].x); y[1] += u2f(yp[i].y); y[2] += u2f(yp[i].z); y[3] += u2f(yp[i].w);
                        bad |= yp[i].w == SENT;
                    }
                } while (__any_sync(0xffffffffu, bad));
                TS(warp == 8 ? 53 : 63);
                sts16(SM_SENT + j * 2048 + t * 16, f2u(y[0]), f2u(y[1]), f2u(y[2]), f2u(y[3]));
                bar_sync(4, 128);
                if (w4 < 3) {
                    const uint32_t key = j ? k2 : k1, ya = SM_SENT + j * 2048 + t * 8;
                    const float rs = bf_round(sigmoidf(u2f(((int)key < 0 ? key & 0x7FFFFFFFu : ~key) & 0xFFFF0000u)));
                    const float2 y0 = lds8f(ya), y1 = lds8f(ya + 640), y2 = lds8f(ya + 1280);
                    const uint2* q = reinterpret_cast<const uint2*>(g_sc + (up >> 6) * SC_SIZE + SC_Y + j * 32) + (up & 63);
                    const float sx = y0.x + y1.x + y2.x, sy = y0.y + y1.y + y2.y;
                    uint2 z[4];
                    pace(t_start, Y2_T);
                    do {
#pragma unroll
                        for (int i = 0; i < 4; i++) z[i] = ld_relaxed8(q + i * 10 * SC_SIZE);
                    } while (__any_sync(0xffffffffu, max(max(z[0].y, z[1].y), max(z[2].y, z[3].y)) == SENT));
                    TS(warp == 8 ? 62 : 63);
                    if (t < 80)
                        sts4(SM_U + j * 320 + t * 4, pack2(bf_round(sx + (u2f(z[0].x) + u2f(z[1].x)) + (u2f(z[2].x) + u2f(z[3].x))) * rs,
                                                           bf_round(sy + (u2f(z[0].y) + u2f(z[1].y)) + (u2f(z[2].y) + u2f(z[3].y))) * rs));
                }
            }
            bar_sync(4, 128);
        }
        if (t == 0) mbar_arrive(B_MOD);
        TS(warp == 8 ? 52 : 63);
    } else {
        asm volatile("setmaxnreg.dec.sync.aligned.u32 32;");
        if (warp == 15) {
            if (EPF_M) {
                pace(t_start, EPF_T);
                if (lane < (EPF_M << EPF_H)) l2_prefetch(P.wp + (EPF_N * 132 + (lane >> EPF_H) * 128 + bid) * 64 + (lane & EPF_H) * 32);
            }
#pragma unroll 1
            for (int i = PF_0; i < PF_N; i++) {
                pace(t_start, (i < 6 ? PF_UP : PF_DN) + i * PF_DT);
                const int ln = (i * 128 + cid) * 32 + lane;
                l2_prefetch((ln < 17280 ? P.upp : ln < 23680 ? P.wop - 17280 * 64 : P.dp - 23680 * 64) + ln * 64);
            }
            if (elect_one()) {
#pragma unroll 1
                for (int i = 0; i < (!NFFN ? 0 : cid < NFFN ? 8 : 12); i++) {
                    pace(t_start, GU_T0 + i * (cid < NFFN ? GU_DT : GU_DS) + (cid & 7) * GU_ST);
                    if (cid < NFFN) tma_2d(SM_F + i * 2560, &P.gate, B_GU, (cid >> 2) * 64, (cid & 3) * 160 + i * 20);
                    else tma_2d(SM_F - 4096 + i * 2048, &P.down, B_GU, min(i, 4 + (i >> 1)) * 64, cid * 32 - 2368 + (i > 8 ? (i & 1) * 16 : 0));
                }
            }
            __syncwarp();
            int it = (smem_u32(smem_raw) & 0xFFFFFF) == SB ? 0 : 1 << 20;
            while (!mbar_try(B_DONE, 0) || !mbar_try(B_MOD, 0))
                if (++it > (1 << 20)) fault();
        } else if (warp == 13) {
#pragma unroll 1
            for (int i = 0; i < 10; i++) sts16(SM_SENT + i * 512 + lane * 16, SENT, SENT, SENT, SENT);
            fence_async_smem();
            __syncwarp();
            if (elect_one()) {
                if (!RW_REG) mbar_expect_tx(B_RG, 2560);
                mbar_expect_tx(B_GU, cid < NFFN ? 20480 : 24576);
                asm volatile("mbarrier.expect_tx.relaxed.cta.shared::cta.b64 [%0], 10240;" ::"r"(B_RG2 + rk) : "memory");
                pace(t_start, RW1_T);
                bulk_load(SM_RED, P.w_r, 1280, B_RG);
                bulk_load(SM_RED + 1280, P.gate_w, 1280, B_RG);
#pragma unroll 1
                for (int i = 0; i < 5; i++) {
                    pace(t_start, RG1_T0 + i * RG1_DT);
                    tma_3d(SM_HALO + i * 2048, &P.xg, B_RG2, 320 + i * 64, par, p0 + hg * 16);
                }
#pragma unroll
                for (int i = 0; i < 23; i++) mbar_init(B_GUD + i * 8, i == 10 ? 8 : i == 22 || !i ? 4 : i < 16 ? 1 : 2);
                bulk_store(sc + SC_HALO, SM_SENT, 5120);
                asm volatile("cp.async.bulk.commit_group;\ncp.async.bulk.wait_group 0;" ::: "memory");
                mbar_arrive(B_RG2);
                TS(43);
                const unsigned goal = (ld_relaxed4(g_cnt + 32) | (NCTA - 1)) + 1;
#pragma unroll 1
                for (int i = RS_E; i < RS_N; i++) {
                    pace(t_start, RS_T0 + (i - RS_E) * RS_DT + (cid & 7) * RS_S);
                    bulk_store(sc + i * (1280 / RS_N), SM_SENT, 20480 / RS_N);
                }
                asm volatile("cp.async.bulk.commit_group;\ncp.async.bulk.wait_group 0;" ::: "memory");
                red_inc(g_cnt + 32, goal);
                mbar_arrive(B_RS);
                TS(44);
                while (ld_relaxed4(g_cnt + 32) - goal > 0x80000000u) {}
                mbar_arrive(B_INIT);
                TS(45);
            }
        } else if (warp == 14) {
            if (elect_one()) {
#pragma unroll 1
                for (int kb = 1; kb < 10; kb++) {
                    const uint32_t fb = B_FULL + (kb & 3) * 16, dst = SM_X + (kb & 3) * 16384;
                    mbar_wait(fb + (B_EMPTY - B_FULL + 8), ~(kb >> 2) & 1);
                    if (kb >= 4) mbar_wait(B_XE + (kb - 4 >> 1) * 8, 0);
                    pace(t_start, max(PACE_A - PACE_B / 2 + 2 * kb * PACE_B, PACE_W0 - X_OFF + (2 * kb + 1) * PACE));
                    tma_3d(dst, &P.x2, fb, kb * 64, par, p0);
                    TS5(41 + kb);
                }
            }
            __syncwarp();
            pace(t_start, CAND_T);
            {
                const uint32_t tag = lds4(SM_KEY + 20 * 4);
                uint4 c[2], v;
                do {
                    c[0] = ld_relaxed16(g_cand + lane * 2);
                    c[1] = ld_relaxed16(g_cand + lane * 2 + 64);
                    v = ld_relaxed16(g_gate + tile * 128 + lane * 4);
                } while (__any_sync(0xffffffffu, ((c[0].x ^ tag) | (c[0].z ^ tag) | (c[1].x ^ tag) | (c[1].z ^ tag) | (v.x ^ tag) |
                                                  (v.y ^ tag) | (v.z ^ tag) | (v.w ^ tag)) & 0xF800u));
                const uint32_t a1 = max(c[0].x, c[0].z), b1 = max(c[1].x, c[1].z), l1 = max(a1, b1);
                const uint32_t l2 = max(max(max(c[0].y, c[0].w), max(c[1].y, c[1].w)),
                                        max(max(min(c[0].x, c[0].z), min(c[1].x, c[1].z)), min(a1, b1)));
                const uint32_t k1 = __reduce_max_sync(0xffffffffu, l1);
                const uint32_t k2 = __reduce_max_sync(0xffffffffu, l1 == k1 ? l2 : l1);
                sts16(SM_GATE + lane * 16, v.x, v.y, v.z, v.w);
                __syncwarp();
                if (elect_one()) {
                    bulk_load(SM_XS, P.xp + (~k1 & 2047) * 640 + (cid & 3) * 160, 320, B_XS);
                    bulk_load(SM_XS + 320, P.xp + (~k2 & 2047) * 640 + (cid & 3) * 160, 320, B_XS);
                    sts16(SM_KEY + 16 * 4, k1, k2, 0, 0);
                    mbar_expect_tx(B_XS, 640);
                    mbar_arrive(B_GT);
                    TS(56);
                }
            }
            bar_sync(12, 64);
            pace(t_start, 0);
            pace(clock(), HALO_D);
            TS(24);
            uint4 hv[5];
            poll<5>(hv, sc + (SC_HALO - (tile < 2 ? 0 : 16 * SC_SIZE) + lane), 32);
#pragma unroll
            for (int s = 0; s < 5; s++) sts16(SM_HALO + s * 512 + lane * 16, hv[s].x, hv[s].y, hv[s].z, hv[s].w);
            bar_arrive(8, 64);
            TS(25);
        } else {
            if (elect_one()) {
#pragma unroll 1
                for (int s = W_S0; s < 20; s++) {
                    const uint32_t fb = B_FULL + (s & 7) * 8, dst = SM_W + (s & 7) * 15360;
                    mbar_wait(fb + (B_EMPTY - B_FULL), ~(s >> 3) & 1);
                    pace(t_start, max(PACE_A + s * PACE_B, PACE_W0 + s * PACE));
                    mbar_expect_tx(fb, (s & 1) ? 15360 : 15360 + 16384);
                    tma_3d(dst, &P.w, fb, wcm, s * 32, 0);
                    tma_3d(dst + 12288, &P.wr, fb, wcr, s * 32, 0);
                    TS2(20 + s);
                    if (s == W_S0) TS(41);
                }
                mbar_wait(B_RG2, 0);
                if (NFFN) {
                    mbar_wait(B_EMPTY + 5 * 8, 1);
                    mbar_expect_tx(B_UP, cid < NFFN ? 20480 : 16384);
                    TS(46);
                    if (cid < NFFN) tma_2d(SM_UP, &P.up, B_UP, (cid >> 2) * 64, (cid & 3) * 160);
                    else
#pragma unroll 1
                        for (int i = 0; i < 8; i++) tma_2d(SM_UP + i * 2048, &P.down, B_UP, i * 64, cid * 32 - 2352);
                }
                const int cb = hg >> 1, ca = (cb * 5 + 1) >> 1, cr = cb * 160 + ((cb & 1) ? 0 : 128);
#pragma unroll 1
                for (int j = 0; j < 8; j++) {
                    const int i = j ^ (j == 3 || j == 4 ? 7 : 0);
                    if (j != 3) mbar_wait(j < 3 ? B_EMPTY + ((2 * j + 7) & 7) * 8 : B_GUD + (j - 4) * 8, j == 0);
                    if (j >= 5) pace(clock(), j == 5 ? C5_D : C6_D);
                    if (C0_T | C1_T | C2_T | C3_T | C4_T) pace(t_start, j == 0 ? C0_T : j == 1 ? C1_T : j == 2 ? C2_T : j == 3 ? C3_T : C4_T);
                    const uint32_t dst = wo_buf(i), gb = B_G2 + i * 8;
                    mbar_expect_tx(gb, 25600);
                    tma_3d(dst, &P.woa, gb, 0, src_of(i, hg) * 80, ca);
                    tma_2d(dst + 20480, &P.wob, gb, cr, src_of(i, hg) * 80);
                }
            }
        }
    }
}

typedef CUresult (*EncodeFn)(CUtensorMap*, CUtensorMapDataType, cuuint32_t, void*, const cuuint64_t*, const cuuint64_t*,
                             const cuuint32_t*, const cuuint32_t*, CUtensorMapInterleave, CUtensorMapSwizzle,
                             CUtensorMapL2promotion, CUtensorMapFloatOOBfill);

void encode(EncodeFn fn, CUtensorMap* m, const void* ptr, int rank, const cuuint64_t* dims, const cuuint64_t* strides,
            const cuuint32_t* box, CUtensorMapSwizzle swz) {
    const cuuint32_t es[4] = {1, 1, 1, 1};
    fn(m, CU_TENSOR_MAP_DATA_TYPE_BFLOAT16, rank, const_cast<void*>(ptr), dims, strides, box, es,
       CU_TENSOR_MAP_INTERLEAVE_NONE, swz, CU_TENSOR_MAP_L2_PROMOTION_L2_128B, CU_TENSOR_MAP_FLOAT_OOB_FILL_NONE);
}

}

extern "C" void kernel_launch(void* const* d_in, const int* in_sizes, int n_in, void* d_out, int out_size) {
    (void)in_sizes; (void)n_in; (void)out_size;
    Params P;
    P.xp = (const __nv_bfloat16*)d_in[0];
    P.wp = (const __nv_bfloat16*)d_in[1];
    P.wop = (const __nv_bfloat16*)d_in[2];
    P.dp = (const __nv_bfloat16*)d_in[7];
    P.upp = (const __nv_bfloat16*)d_in[6];
    P.op = (__nv_bfloat16*)d_out;
    P.w_r = (const __nv_bfloat16*)d_in[4];
    P.gate_w = (const __nv_bfloat16*)d_in[8];

    void* fp = nullptr;
    cudaDriverEntryPointQueryResult st;
    cudaGetDriverEntryPoint("cuTensorMapEncodeTiled", &fp, cudaEnableDefault, &st);
    EncodeFn fn = (EncodeFn)fp;
    const cuuint64_t xd[3] = {640, 2, 1024}, xs[2] = {1280, 2560};
    const cuuint32_t bx[3] = {64, 1, 64}, bx2[3] = {64, 1, 128};
    encode(fn, &P.x2, d_in[0], 3, xd, xs, bx2, CU_TENSOR_MAP_SWIZZLE_128B);
    encode(fn, &P.x, d_in[0], 3, xd, xs, bx, CU_TENSOR_MAP_SWIZZLE_128B);
    const cuuint64_t wd[3] = {640, 640, 3}, ws[2] = {3840, 1280};
    const cuuint32_t bw[3] = {64, 32, 3}, bwr[3] = {16, 32, 3};
    encode(fn, &P.w, d_in[1], 3, wd, ws, bw, CU_TENSOR_MAP_SWIZZLE_128B);
    encode(fn, &P.wr, d_in[1], 3, wd, ws, bwr, CU_TENSOR_MAP_SWIZZLE_32B);
    const cuuint64_t ad[3] = {64, 640, 10}, as[2] = {1280, 128}, bd[2] = {640, 640};
    const cuuint32_t ba[3] = {64, 80, 2}, bb[2] = {32, 80};
    encode(fn, &P.woa, d_in[2], 3, ad, as, ba, CU_TENSOR_MAP_SWIZZLE_128B);
    encode(fn, &P.wob, d_in[2], 2, bd, as, bb, CU_TENSOR_MAP_SWIZZLE_128B);
    const cuuint64_t gd[2] = {1728, 640}, gs[1] = {3456}, dd[2] = {640, 1728};
    const cuuint32_t bg[2] = {64, 20}, bu[2] = {64, 160}, bdn[2] = {64, 16}, bxg[3] = {64, 1, 16};
    encode(fn, &P.xg, d_in[0], 3, xd, xs, bxg, CU_TENSOR_MAP_SWIZZLE_128B);
    encode(fn, &P.gate, d_in[5], 2, gd, gs, bg, CU_TENSOR_MAP_SWIZZLE_128B);
    encode(fn, &P.up, d_in[6], 2, gd, gs, bu, CU_TENSOR_MAP_SWIZZLE_128B);
    encode(fn, &P.up2, d_in[6], 2, gd, gs, bg, CU_TENSOR_MAP_SWIZZLE_128B);
    encode(fn, &P.down, d_in[7], 2, dd, as, bdn, CU_TENSOR_MAP_SWIZZLE_128B);

    cudaFuncSetAttribute(fused_kernel, cudaFuncAttributeMaxDynamicSharedMemorySize, SM_TOTAL);
    fused_kernel<<<NCTA + (MAPV == 3 ? 0 : NEXTRA), 512, SM_TOTAL, cudaStreamPerThread>>>(P);
}
```

```cpp
#include <cuda_runtime.h>
#include <cuda_bf16.h>
#include <cuda.h>
#include <stdint.h>

namespace {

constexpr int NCTA = 128, NEXTRA = 4;
constexpr int NFFN = 108;
constexpr uint32_t SENT = 0xFFFFFFFFu;

constexpr uint32_t SB = 1024;
constexpr uint32_t SM_W = SB;
constexpr uint32_t SM_X = SB + 122880;
constexpr uint32_t SM_F = SB + 192512;
constexpr uint32_t SM_HALO = SB + 212992;
constexpr uint32_t SM_BAR = SB + 223232;
constexpr uint32_t SM_PROF = SB + 223744;
constexpr uint32_t SM_KEY = SB + 224000;
constexpr uint32_t SM_RED = SB + 224128;
constexpr uint32_t SM_XS = SB + 226688;
constexpr uint32_t SM_SENT = SB + 227328;
constexpr uint32_t SM_U = SM_RED + 1920;
constexpr uint32_t SM_H = SM_RED + 1536;
constexpr uint32_t SM_GATE = SM_RED;
constexpr uint32_t SM_TOTAL = 232448;
constexpr uint32_t SM_HALO1 = SM_X + 32768;
constexpr uint32_t SM_UP = SM_W + 61440;
constexpr uint32_t SM_OUT = SM_W + 61440;

constexpr uint32_t B_XL0 = SM_BAR, B_FULL = SM_BAR + 8, B_GT = SM_BAR + 72, B_RG = SM_BAR + 80, B_RG2 = SM_BAR + 88,
                   B_XS = SM_BAR + 96, B_EMPTY = SM_BAR + 128, B_DONE = SM_BAR + 192, B_XE = SM_BAR + 200,
                   B_GUD = SM_BAR + 224, B_OE = SM_BAR + 232, B_OT = SM_BAR + 264, B_MOD = SM_BAR + 296,
                   B_GU = SM_BAR + 104, B_UP = SM_BAR + 112, B_RS = SM_BAR + 312, B_INIT = SM_BAR + 320,
                   B_RE = SM_BAR + 328, B_PUB = SM_BAR + 304, B_G2 = SM_BAR + 336, B_DF = SM_BAR + 400;

struct Params {
    CUtensorMap x, x2, w, wr, woa, wob, xg, gate, up, down, up2;
    __nv_bfloat16* op;
    const __nv_bfloat16 *xp, *wp, *dp, *upp, *wop, *w_r, *gate_w;
};

constexpr int SC_O = 0;
constexpr int SC_HALO = 1280;
constexpr int SC_GU = 1440;
constexpr int SC_Y = 1504;
constexpr int SC_SIZE = 1600;
__device__ __align__(128) uint4 g_sc[NCTA * SC_SIZE];
__device__ __align__(128) uint2 g_cand[NCTA];
__device__ __align__(16) uint32_t g_gate[2048];
__device__ __align__(128) unsigned g_cnt[64];
#define TS(i) do { } while (0)
#define TS2(i) do { } while (0)
#define TSX(i) do { } while (0)

#define TS5(i) do { } while (0)
__device__ __forceinline__ uint32_t smem_u32(const void* p) { return (uint32_t)__cvta_generic_to_shared(p); }
__device__ __forceinline__ void fault() { asm volatile("st.shared.u32 [%0], %0;" ::"r"(0x100001) : "memory"); }
__device__ __forceinline__ void mbar_init(uint32_t bar, uint32_t cnt) {
    asm volatile("mbarrier.init.shared::cta.b64 [%0], %1;" ::"r"(bar), "r"(cnt) : "memory");
}
__device__ __forceinline__ void mbar_expect_tx(uint32_t bar, uint32_t bytes) {
    asm volatile("mbarrier.arrive.expect_tx.shared::cta.b64 _, [%0], %1;" ::"r"(bar), "r"(bytes) : "memory");
}
__device__ __forceinline__ void mbar_arrive(uint32_t bar) {
    asm volatile("mbarrier.arrive.shared::cta.b64 _, [%0];" ::"r"(bar) : "memory");
}
__device__ __forceinline__ bool mbar_try(uint32_t bar, uint32_t parity) {
    uint32_t ok;
    asm volatile("{\n.reg .pred p;\nmbarrier.try_wait.parity.shared::cta.b64 p, [%1], %2;\nselp.u32 %0, 1, 0, p;\n}"
                 : "=r"(ok) : "r"(bar), "r"(parity) : "memory");
    return ok;
}
__device__ __forceinline__ void mbar_wait(uint32_t bar, uint32_t parity) {
    asm volatile("{\n.reg .pred p;\nAGAIN:\nmbarrier.try_wait.parity.shared::cta.b64 p, [%0], %1;\n@!p bra AGAIN;\n}"
                 ::"r"(bar), "r"(parity) : "memory");
}
__device__ __forceinline__ void tma_2d(uint32_t dst, const CUtensorMap* m, uint32_t bar, int c0, int c1) {
    asm volatile("cp.async.bulk.tensor.2d.shared::cluster.global.mbarrier::complete_tx::bytes [%0], [%1, {%3, %4}], [%2];"
                 ::"r"(dst), "l"(m), "r"(bar), "r"(c0), "r"(c1) : "memory");
}
__device__ __forceinline__ void bulk_load(uint32_t dst, const void* src, uint32_t bytes, uint32_t bar) {
    asm volatile("cp.async.bulk.shared::cluster.global.mbarrier::complete_tx::bytes [%0], [%1], %2, [%3];"
                 ::"r"(dst), "l"(src), "r"(bytes), "r"(bar) : "memory");
}
__device__ __forceinline__ void bulk_store(void* dst, uint32_t src, uint32_t bytes) {
    asm volatile("cp.async.bulk.global.shared::cta.bulk_group [%0], [%1], %2;" ::"l"(dst), "r"(src), "r"(bytes) : "memory");
}
__device__ __forceinline__ void tma_3d(uint32_t dst, const CUtensorMap* m, uint32_t bar, int c0, int c1, int c2) {
    asm volatile("cp.async.bulk.tensor.3d.shared::cluster.global.mbarrier::complete_tx::bytes [%0], [%1, {%3, %4, %5}], [%2];"
                 ::"r"(dst), "l"(m), "r"(bar), "r"(c0), "r"(c1), "r"(c2) : "memory");
}
__device__ __forceinline__ void fence_async_smem() { asm volatile("fence.proxy.async.shared::cta;" ::: "memory"); }
__device__ __forceinline__ void wg_fence() { asm volatile("wgmma.fence.sync.aligned;" ::: "memory"); }
__device__ __forceinline__ void wg_commit() { asm volatile("wgmma.commit_group.sync.aligned;" ::: "memory"); }
template <int N> __device__ __forceinline__ void wg_wait() { asm volatile("wgmma.wait_group.sync.aligned %0;" ::"n"(N) : "memory"); }
__device__ __forceinline__ void bar_sync(int id, int n) { asm volatile("bar.cta.sync %0, %1;" ::"r"(id), "r"(n) : "memory"); }
__device__ __forceinline__ void bar_arrive(int id, int n) { asm volatile("bar.cta.arrive %0, %1;" ::"r"(id), "r"(n) : "memory"); }

__device__ constexpr uint32_t desc_lo(uint32_t addr, uint32_t lbo) { return (addr >> 4) | ((lbo >> 4) << 16); }
__device__ __forceinline__ bool elect_one() {
    uint32_t p;
    asm volatile("{\n.reg .pred p;\nelect.sync _|p, 0xffffffff;\nselp.u32 %0, 1, 0, p;\n}" : "=r"(p));
    return p;
}
__device__ __forceinline__ uint32_t ld_relaxed4(const void* p) {
    uint32_t v;
    asm volatile("ld.relaxed.gpu.global.u32 %0, [%1];" : "=r"(v) : "l"(p) : "memory");
    return v;
}
__device__ __forceinline__ void st_relaxed4(void* p, uint32_t v) {
    asm volatile("st.relaxed.gpu.global.u32 [%0], %1;" ::"l"(p), "r"(v) : "memory");
}
template <int N = 1>
__device__ __forceinline__ void red_inc(unsigned* p, unsigned after) {
    asm volatile("red.relaxed.gpu.global.add.u32 [%0], %2;" ::"l"(p), "r"(after), "n"(N) : "memory");
}
__device__ __forceinline__ uint32_t lds4(uint32_t a) {
    uint32_t v;
    asm volatile("ld.shared.u32 %0, [%1];" : "=r"(v) : "r"(a) : "memory");
    return v;
}
__device__ __forceinline__ float2 lds8f(uint32_t a) {
    float2 v;
    asm volatile("ld.shared.v2.f32 {%0, %1}, [%2];" : "=f"(v.x), "=f"(v.y) : "r"(a) : "memory");
    return v;
}
__device__ __forceinline__ void sts4(uint32_t a, uint32_t v) { asm volatile("st.shared.u32 [%0], %1;" ::"r"(a), "r"(v) : "memory"); }
__device__ __forceinline__ uint32_t hmul2(uint32_t a, uint32_t b) {
    uint32_t d;
    asm("mul.rn.bf16x2 %0, %1, %2;" : "=r"(d) : "r"(a), "r"(b));
    return d;
}
__device__ __forceinline__ uint32_t hadd2(uint32_t a, uint32_t b) {
    uint32_t d;
    asm("add.rn.bf16x2 %0, %1, %2;" : "=r"(d) : "r"(a), "r"(b));
    return d;
}
__device__ __forceinline__ uint32_t hfma2(uint32_t a, uint32_t b, uint32_t c) {
    uint32_t d;
    asm("fma.rn.bf16x2 %0, %1, %2, %3;" : "=r"(d) : "r"(a), "r"(b), "r"(c));
    return d;
}
__device__ __forceinline__ uint4 ld_relaxed16(const void* p) {
    uint4 v;
    asm volatile("{\n.reg .b128 t;\n.reg .b64 lo, hi;\nld.relaxed.gpu.global.b128 t, [%4];\nmov.b128 {lo, hi}, t;\n"
                 "mov.b64 {%0, %1}, lo;\nmov.b64 {%2, %3}, hi;\n}" : "=r"(v.x), "=r"(v.y), "=r"(v.z), "=r"(v.w) : "l"(p) : "memory");
    return v;
}
__device__ __forceinline__ void st_relaxed16(void* p, uint32_t a, uint32_t b, uint32_t c, uint32_t d) {
    uint64_t lo = (uint64_t)a | ((uint64_t)b << 32), hi = (uint64_t)c | ((uint64_t)d << 32);
    asm volatile("{\n.reg .b128 t;\nmov.b128 t, {%1, %2};\nst.relaxed.gpu.global.b128 [%0], t;\n}" ::"l"(p), "l"(lo), "l"(hi) : "memory");
}
__device__ __forceinline__ void st_relaxed8(void* p, uint32_t a, uint32_t b) {
    asm volatile("{\n.reg .b64 t;\nmov.b64 t, {%1, %2};\nst.relaxed.gpu.global.b64 [%0], t;\n}" ::"l"(p), "r"(a), "r"(b) : "memory");
}
__device__ __forceinline__ uint2 ld_relaxed8(const void* p) {
    uint2 v;
    asm volatile("{\n.reg .b64 t;\nld.relaxed.gpu.global.b64 t, [%2];\nmov.b64 {%0, %1}, t;\n}" : "=r"(v.x), "=r"(v.y) : "l"(p) : "memory");
    return v;
}
__device__ __forceinline__ uint4 ld_nc16(const void* p) {
    uint4 v;
    asm volatile("ld.global.L1::no_allocate.v4.u32 {%0, %1, %2, %3}, [%4];" : "=r"(v.x), "=r"(v.y), "=r"(v.z), "=r"(v.w) : "l"(p) : "memory");
    return v;
}
__device__ __forceinline__ uint2 ld_nc8(const void* p) {
    uint2 v;
    asm volatile("ld.global.nc.L1::no_allocate.v2.u32 {%0, %1}, [%2];" : "=r"(v.x), "=r"(v.y) : "l"(p));
    return v;
}
__device__ __forceinline__ uint4 lds16(uint32_t a) {
    uint4 v;
    asm volatile("ld.shared.v4.u32 {%0, %1, %2, %3}, [%4];" : "=r"(v.x), "=r"(v.y), "=r"(v.z), "=r"(v.w) : "r"(a) : "memory");
    return v;
}
__device__ __forceinline__ void sts16(uint32_t a, uint32_t x, uint32_t y, uint32_t z, uint32_t w) {
    asm volatile("st.shared.v4.u32 [%0], {%1, %2, %3, %4};" ::"r"(a), "r"(x), "r"(y), "r"(z), "r"(w) : "memory");
}
__device__ __forceinline__ uint32_t pack2(float lo, float hi) {
    uint32_t r;
    asm("cvt.rn.bf16x2.f32 %0, %1, %2;" : "=r"(r) : "f"(hi), "f"(lo));
    return r;
}
__device__ __forceinline__ uint32_t pack2v(float lo, float hi) {
    uint32_t r;
    asm volatile("cvt.rn.bf16x2.f32 %0, %1, %2;" : "=r"(r) : "f"(hi), "f"(lo));
    return r;
}
__device__ __forceinline__ float bf_lo(uint32_t u) { return __uint_as_float(u << 16); }
__device__ __forceinline__ float bf_hi(uint32_t u) { return __uint_as_float(u & 0xFFFF0000u); }
__device__ __forceinline__ float bf_round(float f) { return __bfloat162float(__float2bfloat16_rn(f)); }
__device__ __forceinline__ uint32_t prmt(uint32_t a, uint32_t sel) {
    uint32_t d;
    asm("prmt.b32 %0, %1, 0, %2;" : "=r"(d) : "r"(a), "r"(sel));
    return d;
}
__device__ __forceinline__ uint32_t movm(uint32_t a) {
    uint32_t d;
    asm volatile("movmatrix.sync.aligned.m8n8.trans.b16 %0, %1;" : "=r"(d) : "r"(a));
    return d;
}
__device__ __forceinline__ void mma16(float (&c)[4], uint32_t a0, uint32_t a1, uint32_t a2, uint32_t a3, uint32_t b0, uint32_t b1) {
    asm volatile("mma.sync.aligned.m16n8k16.row.col.f32.bf16.bf16.f32 {%0,%1,%2,%3}, {%4,%5,%6,%7}, {%8,%9}, {%0,%1,%2,%3};"
                 : "+f"(c[0]), "+f"(c[1]), "+f"(c[2]), "+f"(c[3]) : "r"(a0), "r"(a1), "r"(a2), "r"(a3), "r"(b0), "r"(b1));
}
__device__ __forceinline__ void mma8(float (&c)[4], uint32_t a0, uint32_t a1, uint32_t b0) {
    asm volatile("mma.sync.aligned.m16n8k8.row.col.f32.bf16.bf16.f32 {%0,%1,%2,%3}, {%4,%5}, {%6}, {%0,%1,%2,%3};"
                 : "+f"(c[0]), "+f"(c[1]), "+f"(c[2]), "+f"(c[3]) : "r"(a0), "r"(a1), "r"(b0));
}
__device__ __forceinline__ float ex2(float x) { float y; asm("ex2.approx.ftz.f32 %0, %1;" : "=f"(y) : "f"(x)); return y; }
__device__ __forceinline__ float rcp(float x) { float y; asm("rcp.approx.ftz.f32 %0, %1;" : "=f"(y) : "f"(x)); return y; }
__device__ __forceinline__ float sigmoidf(float z) { return rcp(1.0f + ex2(z * -1.4426950408889634f)); }
__device__ __forceinline__ float u2f(uint32_t u) { return __uint_as_float(u); }
__device__ __forceinline__ uint32_t f2u(float f) { return __float_as_uint(f); }

__device__ __forceinline__ void wgmma_main(float (&d)[96], uint32_t a, uint32_t b, int scale_d) {
    asm volatile("{\n.reg .pred p;\n.reg .b64 da, db;\nsetp.ne.b32 p, %98, 0;\n"
        "mov.b64 da, {%96, 0x40000040};\nmov.b64 db, {%97, 0x40000040};\n"
        "wgmma.mma_async.sync.aligned.m64n192k16.f32.bf16.bf16 "
        "{%0, %1, %2, %3, %4, %5, %6, %7, %8, %9, %10, %11, %12, %13, %14, %15, "
        "%16, %17, %18, %19, %20, %21, %22, %23, %24, %25, %26, %27, %28, %29, %30, %31, "
        "%32, %33, %34, %35, %36, %37, %38, %39, %40, %41, %42, %43, %44, %45, %46, %47, "
        "%48, %49, %50, %51, %52, %53, %54, %55, %56, %57, %58, %59, %60, %61, %62, %63, "
        "%64, %65, %66, %67, %68, %69, %70, %71, %72, %73, %74, %75, %76, %77, %78, %79, "
        "%80, %81, %82, %83, %84, %85, %86, %87, %88, %89, %90, %91, %92, %93, %94, %95}, "
        "da, db, p, 1, 1, 0, 1;\n}\n"
        : "+f"(d[0]), "+f"(d[1]), "+f"(d[2]), "+f"(d[3]), "+f"(d[4]), "+f"(d[5]), "+f"(d[6]), "+f"(d[7]),
          "+f"(d[8]), "+f"(d[9]), "+f"(d[10]), "+f"(d[11]), "+f"(d[12]), "+f"(d[13]), "+f"(d[14]), "+f"(d[15]),
          "+f"(d[16]), "+f"(d[17]), "+f"(d[18]), "+f"(d[19]), "+f"(d[20]), "+f"(d[21]), "+f"(d[22]), "+f"(d[23]),
          "+f"(d[24]), "+f"(d[25]), "+f"(d[26]), "+f"(d[27]), "+f"(d[28]), "+f"(d[29]), "+f"(d[30]), "+f"(d[31]),
          "+f"(d[32]), "+f"(d[33]), "+f"(d[34]), "+f"(d[35]), "+f"(d[36]), "+f"(d[37]), "+f"(d[38]), "+f"(d[39]),
          "+f"(d[40]), "+f"(d[41]), "+f"(d[42]), "+f"(d[43]), "+f"(d[44]), "+f"(d[45]), "+f"(d[46]), "+f"(d[47]),
          "+f"(d[48]), "+f"(d[49]), "+f"(d[50]), "+f"(d[51]), "+f"(d[52]), "+f"(d[53]), "+f"(d[54]), "+f"(d[55]),
          "+f"(d[56]), "+f"(d[57]), "+f"(d[58]), "+f"(d[59]), "+f"(d[60]), "+f"(d[61]), "+f"(d[62]), "+f"(d[63]),
          "+f"(d[64]), "+f"(d[65]), "+f"(d[66]), "+f"(d[67]), "+f"(d[68]), "+f"(d[69]), "+f"(d[70]), "+f"(d[71]),
          "+f"(d[72]), "+f"(d[73]), "+f"(d[74]), "+f"(d[75]), "+f"(d[76]), "+f"(d[77]), "+f"(d[78]), "+f"(d[79]),
          "+f"(d[80]), "+f"(d[81]), "+f"(d[82]), "+f"(d[83]), "+f"(d[84]), "+f"(d[85]), "+f"(d[86]), "+f"(d[87]),
          "+f"(d[88]), "+f"(d[89]), "+f"(d[90]), "+f"(d[91]), "+f"(d[92]), "+f"(d[93]), "+f"(d[94]), "+f"(d[95])
        : "r"(a), "r"(b), "r"(scale_d));
}

__device__ __forceinline__ void wgmma_rem(float (&d)[24], uint32_t a, uint32_t b, int scale_d) {
    asm volatile("{\n.reg .pred p;\n.reg .b64 da, db;\nsetp.ne.b32 p, %26, 0;\n"
        "mov.b64 da, {%24, 0x40000040};\nmov.b64 db, {%25, 0xC0000010};\n"
        "wgmma.mma_async.sync.aligned.m64n48k16.f32.bf16.bf16 "
        "{%0, %1, %2, %3, %4, %5, %6, %7, %8, %9, %10, %11, %12, %13, %14, %15, "
        "%16, %17, %18, %19, %20, %21, %22, %23}, "
        "da, db, p, 1, 1, 0, 1;\n}\n"
        : "+f"(d[0]), "+f"(d[1]), "+f"(d[2]), "+f"(d[3]), "+f"(d[4]), "+f"(d[5]), "+f"(d[6]), "+f"(d[7]),
          "+f"(d[8]), "+f"(d[9]), "+f"(d[10]), "+f"(d[11]), "+f"(d[12]), "+f"(d[13]), "+f"(d[14]), "+f"(d[15]),
          "+f"(d[16]), "+f"(d[17]), "+f"(d[18]), "+f"(d[19]), "+f"(d[20]), "+f"(d[21]), "+f"(d[22]), "+f"(d[23])
        : "r"(a), "r"(b), "r"(scale_d));
}

__device__ __forceinline__ void wgmma_out(float (&d)[80], uint32_t a, uint32_t b, int scale_d) {
    asm volatile("{\n.reg .pred p;\n.reg .b64 da, db;\nsetp.ne.b32 p, %82, 0;\n"
        "mov.b64 da, {%80, 0x50};\nmov.b64 db, {%81, 0x40000040};\n"
        "wgmma.mma_async.sync.aligned.m64n160k16.f32.bf16.bf16 "
        "{%0, %1, %2, %3, %4, %5, %6, %7, %8, %9, %10, %11, %12, %13, %14, %15, "
        "%16, %17, %18, %19, %20, %21, %22, %23, %24, %25, %26, %27, %28, %29, %30, %31, "
        "%32, %33, %34, %35, %36, %37, %38, %39, %40, %41, %42, %43, %44, %45, %46, %47, "
        "%48, %49, %50, %51, %52, %53, %54, %55, %56, %57, %58, %59, %60, %61, %62, %63, "
        "%64, %65, %66, %67, %68, %69, %70, %71, %72, %73, %74, %75, %76, %77, %78, %79}, "
        "da, db, p, 1, 1, 0, 1;\n}\n"
        : "+f"(d[0]), "+f"(d[1]), "+f"(d[2]), "+f"(d[3]), "+f"(d[4]), "+f"(d[5]), "+f"(d[6]), "+f"(d[7]),
          "+f"(d[8]), "+f"(d[9]), "+f"(d[10]), "+f"(d[11]), "+f"(d[12]), "+f"(d[13]), "+f"(d[14]), "+f"(d[15]),
          "+f"(d[16]), "+f"(d[17]), "+f"(d[18]), "+f"(d[19]), "+f"(d[20]), "+f"(d[21]), "+f"(d[22]), "+f"(d[23]),
          "+f"(d[24]), "+f"(d[25]), "+f"(d[26]), "+f"(d[27]), "+f"(d[28]), "+f"(d[29]), "+f"(d[30]), "+f"(d[31]),
          "+f"(d[32]), "+f"(d[33]), "+f"(d[34]), "+f"(d[35]), "+f"(d[36]), "+f"(d[37]), "+f"(d[38]), "+f"(d[39]),
          "+f"(d[40]), "+f"(d[41]), "+f"(d[42]), "+f"(d[43]), "+f"(d[44]), "+f"(d[45]), "+f"(d[46]), "+f"(d[47]),
          "+f"(d[48]), "+f"(d[49]), "+f"(d[50]), "+f"(d[51]), "+f"(d[52]), "+f"(d[53]), "+f"(d[54]), "+f"(d[55]),
          "+f"(d[56]), "+f"(d[57]), "+f"(d[58]), "+f"(d[59]), "+f"(d[60]), "+f"(d[61]), "+f"(d[62]), "+f"(d[63]),
          "+f"(d[64]), "+f"(d[65]), "+f"(d[66]), "+f"(d[67]), "+f"(d[68]), "+f"(d[69]), "+f"(d[70]), "+f"(d[71]),
          "+f"(d[72]), "+f"(d[73]), "+f"(d[74]), "+f"(d[75]), "+f"(d[76]), "+f"(d[77]), "+f"(d[78]), "+f"(d[79])
        : "r"(a), "r"(b), "r"(scale_d));
}

__device__ __forceinline__ void wgmma_own(float (&d)[80], uint32_t a0, uint32_t a1, uint32_t a2, uint32_t a3, uint32_t b, int scale_d) {
    asm volatile("{\n.reg .pred p;\n.reg .b64 db;\nsetp.ne.b32 p, %85, 0;\nmov.b64 db, {%84, 0x40000040};\n"
        "wgmma.mma_async.sync.aligned.m64n160k16.f32.bf16.bf16 "
        "{%0, %1, %2, %3, %4, %5, %6, %7, %8, %9, %10, %11, %12, %13, %14, %15, "
        "%16, %17, %18, %19, %20, %21, %22, %23, %24, %25, %26, %27, %28, %29, %30, %31, "
        "%32, %33, %34, %35, %36, %37, %38, %39, %40, %41, %42, %43, %44, %45, %46, %47, "
        "%48, %49, %50, %51, %52, %53, %54, %55, %56, %57, %58, %59, %60, %61, %62, %63, "
        "%64, %65, %66, %67, %68, %69, %70, %71, %72, %73, %74, %75, %76, %77, %78, %79}, "
        "{%80, %81, %82, %83}, db, p, 1, 1, 1;\n}\n"
        : "+f"(d[0]), "+f"(d[1]), "+f"(d[2]), "+f"(d[3]), "+f"(d[4]), "+f"(d[5]), "+f"(d[6]), "+f"(d[7]),
          "+f"(d[8]), "+f"(d[9]), "+f"(d[10]), "+f"(d[11]), "+f"(d[12]), "+f"(d[13]), "+f"(d[14]), "+f"(d[15]),
          "+f"(d[16]), "+f"(d[17]), "+f"(d[18]), "+f"(d[19]), "+f"(d[20]), "+f"(d[21]), "+f"(d[22]), "+f"(d[23]),
          "+f"(d[24]), "+f"(d[25]), "+f"(d[26]), "+f"(d[27]), "+f"(d[28]), "+f"(d[29]), "+f"(d[30]), "+f"(d[31]),
          "+f"(d[32]), "+f"(d[33]), "+f"(d[34]), "+f"(d[35]), "+f"(d[36]), "+f"(d[37]), "+f"(d[38]), "+f"(d[39]),
          "+f"(d[40]), "+f"(d[41]), "+f"(d[42]), "+f"(d[43]), "+f"(d[44]), "+f"(d[45]), "+f"(d[46]), "+f"(d[47]),
          "+f"(d[48]), "+f"(d[49]), "+f"(d[50]), "+f"(d[51]), "+f"(d[52]), "+f"(d[53]), "+f"(d[54]), "+f"(d[55]),
          "+f"(d[56]), "+f"(d[57]), "+f"(d[58]), "+f"(d[59]), "+f"(d[60]), "+f"(d[61]), "+f"(d[62]), "+f"(d[63]),
          "+f"(d[64]), "+f"(d[65]), "+f"(d[66]), "+f"(d[67]), "+f"(d[68]), "+f"(d[69]), "+f"(d[70]), "+f"(d[71]),
          "+f"(d[72]), "+f"(d[73]), "+f"(d[74]), "+f"(d[75]), "+f"(d[76]), "+f"(d[77]), "+f"(d[78]), "+f"(d[79])
        : "r"(a0), "r"(a1), "r"(a2), "r"(a3), "r"(b), "r"(scale_d));
}

__device__ __forceinline__ void wgmma_vec(float (&d)[8], uint32_t a, uint32_t b, int scale_d) {
    asm volatile("{\n.reg .pred p;\n.reg .b64 da, db;\nsetp.ne.b32 p, %10, 0;\n"
        "mov.b64 da, {%8, 0x40000040};\nmov.b64 db, {%9, 0x14};\n"
        "wgmma.mma_async.sync.aligned.m64n16k16.f32.bf16.bf16 {%0, %1, %2, %3, %4, %5, %6, %7}, da, db, p, 1, 1, 1, 0;\n}\n"
        : "+f"(d[0]), "+f"(d[1]), "+f"(d[2]), "+f"(d[3]), "+f"(d[4]), "+f"(d[5]), "+f"(d[6]), "+f"(d[7])
        : "r"(a), "r"(b), "r"(scale_d));
}

#define TSA(i) do { } while (0)
#define MAP_TILE(b) ((((b) >> 1) & 14) | ((b) & 1))
#define MAP_HG(b) (((b) >> 4 & 14) | ((b) >> 1 & 1))
#define SRCV 3
#define L1_D 300
#define L0_D 300
#define F1_D 0
#define F0_D 200
#define HALFV 0
#define HALF (int)(HALFV == 0 ? bid >> 1 & 1 : HALFV == 1 ? (bid >> 1 ^ bid) & 1 : (bid >> 1 ^ bid >> 4) & 1)
#define SETL 0
#define L0_T 14350
#define L1_T (L0_T - 300)
#define F0_T 14550
#define F1_T 14300
#define C5_T 0
#define C6_T (C5_T + 450)
#define C7_T (C6_T + 400)
#define C_O 250
#define FFV 2
#define DFV 0
#define OEV 1
#define B_OFF 0
#define W_S0 2
#define E_V 0
#define MAPV 4
#define GW 0
#define GU_DS (GU_DT * 7 / 11)
#define GU_ST 90
#define X_OFF 350
#define RW_REG 0
#define P2W 4
#define RES_V 2
#define Y2_T 17000
#define ENT_V 0
#define TPF 1
#define SKEW 4
#define PACE 500
#define PACE_W0 (-600)
#define PACE_A 250
#define PACE_B 450
#define RG_ORDER 0x24130
#define GU_T0 3600
#define GU_DT 750
#define RS_T0 9000
#define RS_DT 120
#define EXCH_FIRST 1
#define HALO_D 450
#define PF_UP 4200
#define O_D 0
#define O_DT 300
#define PF_DN 4200
#define PF_DT 450
#define GX_NS 200
#define NRS 1
#define C5_D 0
#define C6_D 100
#define PF_N 4
#define PF_0 4
#define EPF_N 15
#define EPF_M 15
#define EPF_T 900
#define RG1_T0 1700
#define RG1_DT 200
#define RW1_T 0
#define Y_T 15800
#define GL_T 0
#define DN_T0 500
#define DN_DT 68
#define DN_T1 100000
#define DN_D1 45
#define DN_R 5
#define H_T 13500
#define HS_T 13500
#define GL_N 16
#define C1_T 0
#define C0_T 0
#define RS_N 10
#define SP_W 1
#define PF2_N 0
#define C2_T 0
#define C3_T 0
#define C4_T 0
#define EPF_G 0
#define EPF_H 0
#define UPF 0
#define UPF_D 700
#define UPF_T 3200
#define UPF_S 90
#define RS_E 0
#define RS_D 0
#define GL15 1
#define RS_S 0
#define CAND_T 9000

__device__ __forceinline__ uint32_t keep(uint32_t v) { return __shfl_xor_sync(0xffffffffu, v, 0); }
__device__ __forceinline__ uint32_t ukeep(uint32_t v) { return __shfl_sync(0xffffffffu, v, 0); }
__device__ __forceinline__ void ldsm2(uint32_t* d, uint32_t a) {
    asm volatile("ldmatrix.sync.aligned.m8n8.x4.shared.b16 {%0,%1,%2,%3}, [%8];\nldmatrix.sync.aligned.m8n8.x4.shared.b16 {%4,%5,%6,%7}, [%9];"
                 : "=r"(d[0]), "=r"(d[1]), "=r"(d[2]), "=r"(d[3]), "=r"(d[4]), "=r"(d[5]), "=r"(d[6]), "=r"(d[7])
                 : "r"(a), "r"(a ^ 32) : "memory");
}
__device__ __forceinline__ void ldsm_t(uint32_t (&d)[4], uint32_t a) {
    asm volatile("ldmatrix.sync.aligned.m8n8.x4.trans.shared.b16 {%0,%1,%2,%3}, [%4];"
                 : "=r"(d[0]), "=r"(d[1]), "=r"(d[2]), "=r"(d[3]) : "r"(a) : "memory");
}
template <bool SWP, int SEG, int E>
__device__ __forceinline__ void pack_blocks(uint32_t (&d)[10], const float (&am)[96], const float (&ar)[24]) {
#pragma unroll
    for (int t = 0; t < 10; t++) {
        const float* p = (SWP ? t < 2 : t >= 8) ? ar + (SEG * 2 + (t & 1)) * 4 + E : am + (SEG * 8 + t - (SWP ? 2 : 0)) * 4 + E;
        d[t] = pack2v(p[0], p[1]);
    }
}
__device__ __forceinline__ int src_of(int i, int hg) { return i == 0 ? hg : i > 3 ? 2 * i - 7 - (hg & 1) : 2 * (i - (i <= (hg >> 1))) + (hg & 1); }

__device__ __forceinline__ uint32_t o_buf(int i) { return __byte_perm(0xD199ADA3u, 0xC7BDu, i - 1 - NRS | 0x7770) << 10; }
__device__ constexpr uint32_t wo_buf(int i) { return SM_W + ((0x10342103u >> i * 4) & 7) * 30720; }

template <int N>
__device__ __forceinline__ void poll(uint4 (&a)[N], const uint4* p, int stride) {
    bool bad;
    do {
        bad = false;
#pragma unroll
        for (int s = 0; s < N; s++) a[s] = ld_relaxed16(p + s * stride);
#pragma unroll
        for (int s = 0; s < N; s++) bad |= a[s].w == SENT;
    } while (__any_sync(0xffffffffu, bad));
}
__device__ __forceinline__ void pace(unsigned t0, int t) {
    asm volatile("{\n.reg .pred p;\n.reg .s32 d;\nAGAIN:\nmov.u32 d, %%clock;\nsub.s32 d, d, %0;\nsetp.lt.s32 p, d, 0;\n"
                 "@p nanosleep.u32 20;\n@p bra AGAIN;\n}" ::"r"(t0 + t) : "memory");
}
__device__ __forceinline__ void l2_prefetch(const void* p) { asm volatile("prefetch.global.L2 [%0];" ::"l"(p) : "memory"); }

template <int N>
__device__ __forceinline__ bool landed(const uint4* w, int lane) {
    uint32_t a = 0;
#pragma unroll
    for (int i = 0; i < N; i++) a ^= w[i].w;
    return __ballot_sync(0xffffffffu, lane == 0 || a == 0) && lane == 0;
}
__device__ __forceinline__ void swiglu(const uint4 (&a)[4], uint32_t dst, uint32_t stride) {
    const float g0 = bf_round((u2f(a[0].x) + u2f(a[1].x)) + (u2f(a[2].x) + u2f(a[3].x)));
    const float g1 = bf_round((u2f(a[0].y) + u2f(a[1].y)) + (u2f(a[2].y) + u2f(a[3].y)));
    const float u0 = bf_round((u2f(a[0].z) + u2f(a[1].z)) + (u2f(a[2].z) + u2f(a[3].z)));
    const float u1 = bf_round((u2f(a[0].w) + u2f(a[1].w)) + (u2f(a[2].w) + u2f(a[3].w)));
    const uint32_t h = pack2(bf_round(g0 * sigmoidf(g0)) * u0, bf_round(g1 * sigmoidf(g1)) * u1);
    asm volatile("st.shared.u16 [%0], %2;\nst.shared.u16 [%1], %3;" ::"r"(dst), "r"(dst + stride), "h"((uint16_t)h), "h"((uint16_t)(h >> 16)) : "memory");
}
template <int N>
__device__ __forceinline__ float4 vec_mma(const uint4 (&w)[N], const uint32_t* x, uint32_t sel) {
    float c[4][4] = {};
    const uint32_t s[4] = {sel, sel >> 16, sel + ((sel & 0x10101010u) >> 3) * 17, (sel + ((sel & 0x10101010u) >> 3) * 17) >> 16};
#pragma unroll
    for (int i = 0; i < N; i++)
        mma16(c[i & 3], w[i].x, w[i].y, w[i].z, w[i].w, prmt(x[i >> 1], s[(i & 1) * 2]), prmt(x[i >> 1], s[(i & 1) * 2 + 1]));
    return make_float4((c[0][0] + c[1][0]) + (c[2][0] + c[3][0]), (c[0][1] + c[1][1]) + (c[2][1] + c[3][1]),
                       (c[0][2] + c[1][2]) + (c[2][2] + c[3][2]), (c[0][3] + c[1][3]) + (c[2][3] + c[3][3]));
}

__global__ void __launch_bounds__(512, 1) fused_kernel(const __grid_constant__ Params P) {
    extern __shared__ __align__(1024) uint8_t smem_raw[];
    const unsigned t_start = clock();
    const int tid = threadIdx.x, lane = tid & 31;
    unsigned sm, bid;
    asm("mov.u32 %0, %%smid;" : "=r"(sm));
    const CUtensorMap* mx = &P.x;
    asm volatile("" : "+l"(mx));
    if ((unsigned)(tid - 480) < EPF_N) l2_prefetch(P.wp + (tid * 132 + sm) * 64 - 480 * 132 * 64);
    const int warp = __shfl_sync(0xffffffffu, threadIdx.x >> 5, 0);
    constexpr uint32_t rk = 0;
    asm("{\n.reg .pred p;\n.reg .b32 t, u;\nshr.u32 t, %1, 1;\nmad.lo.s32 u, t, 14, -928;\nmad.lo.s32 t, t, 37, -925;\nmax.s32 t, t, 0;\n"
        "shr.u32 t, t, 7;\nand.b32 t, t, 14;\nsetp.ge.u32 p, %1, 124;\nselp.b32 t, u, t, p;\nadd.s32 %0, %1, t;\n}" : "=r"(bid) : "r"(sm));
    const int hg = MAP_HG(bid), par = bid & 1, p0 = (MAP_TILE(bid) >> 1) * 128;
    const bool swp = (hg & 3) == 3;
    const int wcm = hg * 80 + (swp ? 16 : 0), wcr = hg * 80 + (swp ? 0 : 64);
    if (warp == 0) {
        if (elect_one()) {
#pragma unroll
            for (int i = 0; i < 4; i++) mbar_init(SM_BAR + i * 8, 1);
            asm volatile("fence.mbarrier_init.release.cluster;" ::: "memory");
            if (bid < NCTA) {
                mbar_expect_tx(B_FULL, 15360 + 8192);
                tma_3d(SM_X + 8192, mx, B_FULL, 0, par, p0 + 64);
                tma_3d(SM_W, mx + 2, B_FULL, wcm, 0, 0);
                tma_3d(SM_W + 12288, mx + 3, B_FULL, wcr, 0, 0);
                TS(40);
                mbar_expect_tx(B_XL0, 8192);
                tma_3d(SM_X, mx, B_XL0, 0, par, p0);
                mbar_expect_tx(B_FULL + 8, 15360);
                tma_3d(SM_W + 15360, mx + 2, B_FULL + 8, wcm, 32, 0);
                tma_3d(SM_W + 15360 + 12288, mx + 3, B_FULL + 8, wcr, 32, 0);
            }
        }
    }
    if ((unsigned)(warp - 1) < 6 && elect_one()) {
#pragma unroll
        for (int i = 0; i < 4; i++) mbar_init(SM_BAR + warp * 32 + i * 8, warp < 4 ? 1 : warp < 6 ? 2 : 4);
        asm volatile("fence.mbarrier_init.release.cluster;" ::: "memory");
    }
    asm volatile("" : "+r"(bid));
    const int role = bid >= NCTA ? -1 : warp, e = (bid + 2) & 3;
    const int tile = MAP_TILE(bid), cid = tile * 8 + hg;
    uint4* const sc = g_sc + cid * SC_SIZE;
    __syncthreads();

    if (role < 0) {
        const int half = warp >> 3;
        if (!NFFN) {
            if (tid == 0) red_inc<NCTA / NEXTRA>(g_cnt, 0);
            return;
        }
        uint32_t wf[DN_R][5][4], la[5];
        auto rows = [&](uint32_t l) {
#pragma unroll
            for (int i = 0; i < 5; i++) {
                const uint32_t c = (warp & 7) * 10 + 2 * i + (l >> 3 & 1);
                la[i] = SB + half * 20480 + (c >> 3) * 2048 + (l & 7) * 128 + (l >> 4) * 1024 + (((c ^ l) & 7) << 4);
            }
        };
        rows(lane);
        auto fetch = [&](int j, int n, uint32_t bar) {
#pragma unroll 1
            for (int h = 0; h < n; h++) {
                pace(t_start, min(DN_T0 + (j * 20 + h * 10 + warp) * DN_DT, DN_T1 + (j * 20 + h * 10 + warp) * DN_D1));
                tma_2d(SB + (j % 5) * 40960 + h * 20480 + warp * 2048, &P.down, bar, warp * 64, e * 272 + (j + h * 9) * 16);
            }
        };
        if (warp < 10 && elect_one()) {
            if (warp <= DN_R) mbar_expect_tx(B_FULL + warp * 8, warp < DN_R ? 40960 : (17 - 2 * DN_R) * 20480);
#pragma unroll 1
            for (int j = 0; j < 5; j++) fetch(j, 2, B_FULL + j * 8);
        }
        const uint32_t tag = (ukeep(ld_relaxed4(g_cnt)) * 8 + 2048) & 0xF800u;
#pragma unroll
        for (int j = 0; j < DN_R; j++) {
            uint32_t any = 0;
            mbar_wait(B_FULL + j * 8, 0);
#pragma unroll
            for (int i = 0; i < 5; i++) {
                ldsm_t(wf[j][i], la[i] + j * 40960);
                any ^= wf[j][i][3];
            }
            if (j < 4) {
                if (__syncthreads_count(any == 0) == 1000) fault();
                if (warp < 10 && elect_one()) fetch(j + 5, j < 3 ? 2 : 1, B_FULL + DN_R * 8);
                if (j == 0 && tid == 0) red_inc<NCTA / NEXTRA>(g_cnt, tag);
            }
            TSX(warp == 0 && j == 0 ? 0 : warp == 0 && j == 3 ? 1 : 63);
        }
        if (warp < 9) {
            pace(t_start, H_T - 1000);
            uint4 a[4];
            do {
                a[0] = ld_relaxed16(g_cand + lane * 2);
                a[1] = ld_relaxed16(g_cand + lane * 2 + 64);
            } while (__any_sync(0xffffffffu, ((a[0].x ^ tag) | (a[0].z ^ tag) | (a[1].x ^ tag) | (a[1].z ^ tag)) & 0xF800u));
            const int u = min(tid, 271), f = e * 272 + u;
            pace(t_start, H_T);
            TSX(warp == 0 ? 3 : 63);
            poll<4>(a, g_sc + (f >> 6) * 4 * SC_SIZE + SC_GU + (f & 63), SC_SIZE);
            TSX(warp == 0 ? 4 : warp == 8 ? 5 : 63);
            swiglu(a, SM_RED + (u >> 4) * 64 + (u & 6) * 4 + (u & 8) / 2 + (u & 1) * 2, 32);
        }
        rows(keep(lane));
        mbar_wait(B_FULL + DN_R * 8, 0);
        TSX(warp == 15 ? 2 : 63);
        __syncthreads();
        float c[5][4] = {};
#pragma unroll
        for (int j = 0; j < 9; j++) {
            if (j == 8 && half) break;
            const float2 b = lds8f(SM_RED + half * 576 + j * 64 + (lane & 7) * 8);
            if (j == 1) TSX(warp == 0 ? 6 : 63);
#pragma unroll
            for (int i = 0; i < 5; i++) {
                if (j >= DN_R) ldsm_t(wf[j % DN_R][i], la[i] + (j % 5) * 40960);
                mma16(c[i], wf[j % DN_R][i][0], wf[j % DN_R][i][1], wf[j % DN_R][i][2], wf[j % DN_R][i][3], f2u(b.x), f2u(b.y));
            }
        }
        const uint32_t ra = SB + 7 * 20480 + half * 5248 + (lane & 1) * 2624 + (warp & 7) * 320 + (lane & 2) * 16 + (lane >> 2) * 4;
#pragma unroll
        for (int i = 0; i < 5; i++) sts4(ra + i * 64, f2u((lane & 2) ? ((lane & 1) ? c[i][3] : c[i][2]) : ((lane & 1) ? c[i][1] : c[i][0])));
        TSX(warp == 0 ? 7 : 63);
        __syncthreads();
        if (warp < 10) {
            const uint32_t ya = SB + 7 * 20480 + (warp & 1) * 2624 + (warp >> 1) * 512 + lane * 16;
            const uint4 y0 = lds16(ya), y1 = lds16(ya + 5248);
            st_relaxed16(g_sc + (e * 5 + (warp >> 1)) * SC_SIZE + SC_Y + (tid & 63), f2u(u2f(y0.x) + u2f(y1.x)), f2u(u2f(y0.y) + u2f(y1.y)),
                         f2u(u2f(y0.z) + u2f(y1.z)), f2u(u2f(y0.w) + u2f(y1.w)));
        }
    } else if (role < 8) {
        asm volatile("setmaxnreg.inc.sync.aligned.u32 192;");
        const int wg = warp >> 2;
        const bool leader = (tid & 127) == 0;
        float am[96], ar[24];
        if (wg == 0) mbar_wait(B_XL0, 0);
        bool rel = false;
        uint32_t nb[40];
        const int odd = (hg >> 1) & 1, kba = ukeep(RES_V && wg != HALF ? 99 : ((hg >> 1) * 5 + 1) >> 1), kbr = ukeep(kba + 2 - odd * 3);
        const int kbs = wg ? -1 : (20 - SKEW) / 2;
        const uint32_t xrow = keep(SM_X + (warp * 16 + (lane & 15)) * 128 + (((lane >> 4) ^ (lane & 7)) << 4));
#pragma unroll 1
        for (int kb = 0; kb < 10; kb++) {
            const uint32_t fb = B_FULL + (kb & 3) * 16, wo = (kb & 3) * 1920, ph = (kb >> 2) & 1;
            const uint32_t xo = desc_lo(SM_X, 16) + wg * 512 + (kb & 3) * 1024;
#pragma unroll
            for (int h = 0; h < 2; h++) {
                mbar_wait(fb + h * 8, ph);
                if (kb == 0 && h == 0) TS(warp == 0 ? 0 : warp == 4 ? 16 : 63);
                TS2(warp == P2W ? kb * 2 + h : 63);
                if (RES_V == 2) {
                    const uint32_t xa = (xrow ^ h * 64) + (kb & 3) * 16384;
                    if (kb == kba) ldsm2(nb + h * 8, xa);
                    if (kb == kba + 1) ldsm2(nb + 16 + h * 8, xa);
                    if (h == 0 && kb == kbr) ldsm2(nb + 32, xa ^ (odd * 64));
                } else if (h == 0) {
                    const uint32_t xa = xrow + (kb & 3) * 16384;
                    if (kb == kba) { ldsm2(nb, xa); ldsm2(nb + 8, xa ^ 64); }
                    if (kb == kba + 1) { ldsm2(nb + 16, xa); ldsm2(nb + 24, xa ^ 64); }
                    if (kb == kbr) ldsm2(nb + 32, xa ^ (odd * 64));
                }
                wg_wait<1>();
                if (rel && (h == 0 || kb != kbs)) mbar_arrive(B_EMPTY + ((kb * 16 - 16) & 48) + h * 8);
                if (h == 0 && kb == kbs) {
                    wg_wait<0>();
                    if (rel) mbar_arrive(B_EMPTY + ((19 - SKEW) & 7) * 8);
                    bar_sync(5, 256);
                }
                wg_fence();
                wgmma_main(am, xo + h * 4, desc_lo(SM_W + h * 15360, 4096) + wo, h || kb);
                wgmma_rem(ar, xo + h * 4, desc_lo(SM_W + h * 15360 + 12288, 1024) + wo, h || kb);
                wgmma_main(am, xo + h * 4 + 2, desc_lo(SM_W + h * 15360 + 2048, 4096) + wo, 1);
                wgmma_rem(ar, xo + h * 4 + 2, desc_lo(SM_W + h * 15360 + 12288 + 512, 1024) + wo, 1);
                wg_commit();
            }
            rel = leader;
        }
        if (wg == 1) bar_arrive(5, 256);
        mbar_wait(B_XE + 16, 0);
        mbar_wait(B_RG2, 0);
        mbar_wait(B_EMPTY + 5 * 8, 1);
        wg_wait<0>();
        if (leader) mbar_arrive(B_EMPTY + 3 * 8);
        TS(warp == 0 ? 2 : warp == 4 ? 18 : 63);
        TS2(warp == 0 ? 41 : warp == 4 ? 40 : 63);

        uint32_t kl[10], kh[10], vl[10], vh[10], ql[10], qh[10], kp[10], vp[10];
        if (swp) {
            pack_blocks<true, 1, 2>(kh, am, ar);
            pack_blocks<true, 2, 2>(vh, am, ar);
        } else {
            pack_blocks<false, 1, 2>(kh, am, ar);
            pack_blocks<false, 2, 2>(vh, am, ar);
        }
        const int w4 = warp & 3;
        const uint32_t pbuf = (wg ? SM_HALO1 : SM_HALO) + w4 * 2560 + lane * 16;
        const uint32_t hbuf = warp == 3 ? SM_HALO1 + lane * 16 : pbuf + 2560;
        {
            const uint32_t ex[20] = {kh[0], kh[1], kh[3], kh[4], kh[5], kh[6], kh[8], kh[9], kh[2], kh[7],
                                     vh[0], vh[1], vh[2], vh[3], vh[4], vh[5], vh[6], vh[7], vh[8], vh[9]};
            if (warp == 7) {
                uint4* const hp = sc + SC_HALO + lane;
#pragma unroll
                for (int s = 0; s < 5; s++) st_relaxed16(hp + s * 32, ex[4 * s], ex[4 * s + 1], ex[4 * s + 2], ex[4 * s + 3]);
                bar_arrive(12, 64);
            } else {
#pragma unroll
                for (int s = 0; s < 5; s++) sts16(hbuf + s * 512, ex[4 * s], ex[4 * s + 1], ex[4 * s + 2], ex[4 * s + 3]);
            }
        }
        TS(warp == 7 ? 22 : warp == 3 ? 23 : 63);
        if (warp == 3) bar_arrive(11, 64);
        if (swp) {
            pack_blocks<true, 2, 0>(vl, am, ar);
            pack_blocks<true, 0, 0>(ql, am, ar);
            pack_blocks<true, 0, 2>(qh, am, ar);
            pack_blocks<true, 1, 0>(kl, am, ar);
        } else {
            pack_blocks<false, 2, 0>(vl, am, ar);
            pack_blocks<false, 0, 0>(ql, am, ar);
            pack_blocks<false, 0, 2>(qh, am, ar);
            pack_blocks<false, 1, 0>(kl, am, ar);
        }
#pragma unroll
        for (int t = 0; t < 10; t++) { vl[t] = movm(vl[t]); vh[t] = movm(vh[t]); }
        mbar_wait(B_RS, 0);
        mbar_wait(B_GT, 0);
        const float g0 = bf_hi(lds4(SM_GATE + warp * 64 + (lane & 28))), g1 = bf_hi(lds4(SM_GATE + 32 + warp * 64 + (lane & 28)));

        const int r = lane >> 2, cq = lane & 3;
        const bool no_prev = warp == 0 && tile < 2, low = cq < 2;
        const bool le0 = 2 * cq <= r, le1 = 2 * cq + 1 <= r;
        const uint32_t mle = (le0 ? 0xFFFFu : 0u) | (le1 ? 0xFFFF0000u : 0u);
        const float scl = 0.22360679774997896f * 1.4426950408889634f;
        uint32_t pl[4], ph[4];
        {
            float sl[4][4], sh[4][4], sp[4][4];
            auto exchange = [&]() {
            TSA(warp == 1 ? 26 : 63);
            bar_sync(6 + wg, 128);
            if (w4 == 0) bar_sync(8 + wg * 3, 64);
            {
                const uint4 a = lds16(pbuf), b = lds16(pbuf + 512), c = lds16(pbuf + 1024), d = lds16(pbuf + 1536), e = lds16(pbuf + 2048);
                kp[0] = a.x; kp[1] = a.y; kp[3] = a.z; kp[4] = a.w; kp[5] = b.x; kp[6] = b.y; kp[8] = b.z; kp[9] = b.w;
                kp[2] = c.x; kp[7] = c.y; vp[0] = c.z; vp[1] = c.w; vp[2] = d.x; vp[3] = d.y; vp[4] = d.z; vp[5] = d.w;
                vp[6] = e.x; vp[7] = e.y; vp[8] = e.z; vp[9] = e.w;
            }
            TSA(warp == 0 ? 3 : warp == 4 ? 19 : warp == 5 ? 27 : 63);
            };
            if (EXCH_FIRST) exchange();
#pragma unroll
            for (int h = 0; h < 4; h++) {
                const int ta = (h >> 1) * 5 + (h & 1) * 3, tc = (h >> 1) * 5 + 2;
                const uint32_t ml = low != (h & 1) ? ql[tc] : 0u, mh = low != (h & 1) ? qh[tc] : 0u;
#pragma unroll
                for (int e = 0; e < 4; e++) sl[h][e] = sh[h][e] = sp[h][e] = 0.f;
                mma16(sl[h], ql[ta], qh[ta], ql[ta + 1], qh[ta + 1], kl[ta], kl[ta + 1]);
                mma16(sh[h], ql[ta], qh[ta], ql[ta + 1], qh[ta + 1], kh[ta], kh[ta + 1]);
                mma8(sl[h], ml, mh, kl[tc]);
                mma8(sh[h], ml, mh, kh[tc]);
            }
            if (!EXCH_FIRST) exchange();
#pragma unroll
            for (int h = 0; h < 4; h++) {
                const int ta = (h >> 1) * 5 + (h & 1) * 3, tc = (h >> 1) * 5 + 2;
                mma16(sp[h], ql[ta], qh[ta], ql[ta + 1], qh[ta + 1], kp[ta], kp[ta + 1]);
                mma8(sp[h], low != (h & 1) ? ql[tc] : 0u, low != (h & 1) ? qh[tc] : 0u, kp[tc]);
            }
#pragma unroll
            for (int t = 0; t < 10; t++) vp[t] = movm(vp[t]);
#pragma unroll
            for (int h = 0; h < 4; h++) {
                if (no_prev) sp[h][0] = sp[h][1] = -1e9f / 0.22360679774997896f;
                const float a0 = le0 ? sl[h][0] : sp[h][0], a1 = le1 ? sl[h][1] : sp[h][1];
                const float b0 = le0 ? sh[h][2] : sl[h][2], b1 = le1 ? sh[h][3] : sl[h][3];
                float ma = fmaxf(a0, a1), mb = fmaxf(b0, b1);
                ma = fmaxf(ma, __shfl_xor_sync(0xffffffffu, ma, 1));
                mb = fmaxf(mb, __shfl_xor_sync(0xffffffffu, mb, 1));
                ma = fmaxf(ma, __shfl_xor_sync(0xffffffffu, ma, 2)) * -scl;
                mb = fmaxf(mb, __shfl_xor_sync(0xffffffffu, mb, 2)) * -scl;
                pl[h] = pack2(ex2(fmaf(a0, scl, ma)), ex2(fmaf(a1, scl, ma)));
                ph[h] = pack2(ex2(fmaf(b0, scl, mb)), ex2(fmaf(b1, scl, mb)));
            }
        }
        TSA(warp == 0 ? 4 : warp == 4 ? 20 : warp == 5 ? 28 : 63);
        uint32_t ol[10], oh[10];
        {
            uint32_t* const po = reinterpret_cast<uint32_t*>(sc + SC_O + warp * 160) + lane;
            const uint32_t ONES = 0x3F803F80u;
            float o[12][4];
#pragma unroll
            for (int hp = 0; hp < 2; hp++) {
#pragma unroll
                for (int h = hp * 2; h < hp * 2 + 2; h++) {
                    const int ta = (h >> 1) * 5 + (h & 1) * 3, tc = (h >> 1) * 5 + 2;
                    const bool mine = (lane < 16) != (h & 1);
                    const uint32_t a0 = pl[h] & mle, a1 = ph[h] & ~mle, a3 = ph[h] & mle, ap = pl[h] & ~mle;
#pragma unroll
                    for (int i = 0; i < 3; i++) o[h * 3 + i][0] = o[h * 3 + i][1] = o[h * 3 + i][2] = o[h * 3 + i][3] = 0.f;
                    mma16(o[h * 3 + 2], a0, a1, 0u, a3, mine ? vl[tc] : ONES, mine ? vh[tc] : ONES);
                    mma16(o[h * 3], a0, a1, 0u, a3, vl[ta], vh[ta]);
                    mma16(o[h * 3 + 1], a0, a1, 0u, a3, vl[ta + 1], vh[ta + 1]);
                    mma8(o[h * 3 + 2], ap, 0u, mine ? vp[tc] : ONES);
                    mma8(o[h * 3], ap, 0u, vp[ta]);
                    mma8(o[h * 3 + 1], ap, 0u, vp[ta + 1]);
                }
                if (hp && wg != HALF) bar_arrive(2, 256);
                const float (&oa)[4] = o[hp * 6 + 2], (&ob)[4] = o[hp * 6 + 5];
                const float hl = rcp(low ? ob[0] : oa[0]) * g0, hh = rcp(low ? ob[2] : oa[2]) * g1;
                const float gl = __shfl_xor_sync(0xffffffffu, hl, 2), gh = __shfl_xor_sync(0xffffffffu, hh, 2);
                const float ial = low ? gl : hl, iah = low ? gh : hh, ibl = low ? hl : gl, ibh = low ? hh : gh;
#pragma unroll
                for (int i = 0; i < 2; i++) {
                    ol[hp * 5 + i] = pack2(o[hp * 6 + i][0] * ial, o[hp * 6 + i][1] * ial);
                    oh[hp * 5 + i] = pack2(o[hp * 6 + i][2] * iah, o[hp * 6 + i][3] * iah);
                    ol[hp * 5 + 3 + i] = pack2(o[hp * 6 + 3 + i][0] * ibl, o[hp * 6 + 3 + i][1] * ibl);
                    oh[hp * 5 + 3 + i] = pack2(o[hp * 6 + 3 + i][2] * ibh, o[hp * 6 + 3 + i][3] * ibh);
                }
                ol[hp * 5 + 2] = pack2((low ? oa[0] : ob[0]) * gl, (low ? oa[1] : ob[1]) * gl);
                oh[hp * 5 + 2] = pack2((low ? oa[2] : ob[2]) * gh, (low ? oa[3] : ob[3]) * gh);
#pragma unroll
                for (int t = hp * 5; t < hp * 5 + 5; t++) {
                    st_relaxed4(po + t * 32, ol[t]);
                    st_relaxed4(po + 320 + t * 32, oh[t]);
                }
            }
        }
        TS(warp == 0 ? 5 : warp == 4 ? 21 : warp == 5 ? 29 : warp == 1 ? 31 : 63);
        const unsigned t_pub = clock();
        if (lane == 0) mbar_arrive(B_PUB);
        const uint4* ow = sc + (SC_O + HALF * 640 - hg * SC_SIZE);
        mbar_wait(B_INIT, 0);
        if (wg != HALF) {
            mbar_wait(B_PUB, 0);
            const unsigned t0 = F0_T ? t_start + max((unsigned)clock() - t_start + (wg ? F0_D : F1_D), wg ? F0_T : F1_T) : clock() + (wg ? F0_D : F1_D);
            uint32_t ph = 0;
#pragma unroll 1
            for (int i = w4 + 1 + NRS; i < 8; i += 4) {
                const uint4* src = ow + src_of(i, hg) * SC_SIZE;
                const uint32_t buf = o_buf(i), chk = buf + lane * 132;
                pace(t0, (i - 2) * O_DT);
                if (i > 4 + NRS) mbar_wait(B_DF, 0);
                if (i == 1 + NRS) TS(wg ? 3 : 4);
                uint32_t c;
                do {
                    if (elect_one()) {
                        mbar_expect_tx(B_OT + w4 * 8, 10240);
                        bulk_load(buf, src, 10240, B_OT + w4 * 8);
                    }
                    mbar_wait(B_OT + w4 * 8, ph);
                    if (i == 1 + NRS && !ph) TS(wg ? 19 : 20);
                    ph ^= 1;
                    c = max(max(lds4(chk), lds4(chk + 4096)), lds4(chk + 6144));
                } while (__any_sync(0xffffffffu, c == SENT));
                if (lane == 0) mbar_arrive(B_G2 + i * 8);
                TS(i == 2 ? 33 : 32 + i);
            }
            return;
        }

        float oc[80];
        uint32_t af[20];
        auto fetch = [&]() {
            const uint32_t* p = reinterpret_cast<const uint32_t*>(ow + src_of(1, hg) * SC_SIZE + w4 * 160) + lane;
#pragma unroll
            for (int t = 0; t < 20; t++) af[t] = ld_relaxed4(p + t * 32);
        };
        mbar_wait(B_XS, 0);
        const int orow = p0 + wg * 64 + w4 * 16;
        const uint32_t tk1 = ~lds4(SM_KEY + 16 * 4) & 2047, tk2 = ~lds4(SM_KEY + 17 * 4) & 2047;
        const uint32_t sel1 = (tk1 & 1) == par ? (tk1 >> 1) - orow : 99, sel2 = (tk2 & 1) == par ? (tk2 >> 1) - orow : 99;
        const uint32_t n0 = pack2(1.f - g0, 1.f - g0), n1 = pack2(1.f - g1, 1.f - g1);
        const uint32_t stg = SM_OUT + w4 * 5120;
        const uint32_t m128 = keep(stg + (lane & 15) * 128 + (((lane >> 4) ^ (lane & 7)) << 4));
        const uint32_t m64 = keep(stg + 4096 + (lane & 15) * 64 + (((lane >> 4) ^ ((lane >> 1) & 3)) << 4));
        const uint32_t l128 = keep(stg + (lane >> 3) * 128 + (((lane & 7) ^ (lane >> 3)) << 4));
        const uint32_t l64 = keep(stg + 4096 + r * 64 + ((cq ^ (lane >> 3)) << 4));
        char* const o128 = reinterpret_cast<char*>(P.op) + keep(((orow + (lane >> 3)) * 2 + par) * 1280 + kba * 128 + (lane & 7) * 16);
        char* const o64 = reinterpret_cast<char*>(P.op) + keep(((orow + r) * 2 + par) * 1280 + kbr * 128 + odd * 64 + cq * 16);
        if (!SETL) mbar_wait(B_G2, 0), mbar_wait(B_G2 + 8, 0);
        const bool ff = FFV == 1 || (FFV == 2 && cid < NFFN) || (FFV == 3 && wg) || (FFV == 4 && (cid < NFFN || wg));
        if (ff) {
            if (L0_T) pace(t_start, wg ? L1_T : L0_T);
            else pace(t_pub, wg ? L1_D : L0_D);
            fetch();
        }
        if (SETL) mbar_wait(B_G2, 0);
        bar_sync(2, 256);
        TS(w4 == 0 ? 6 : 63);
        wg_fence();
#pragma unroll
        for (int s = 0; s < 5; s++)
            wgmma_own(oc, ol[2 * s], oh[2 * s], ol[2 * s + 1], oh[2 * s + 1], desc_lo(wo_buf(0), 10240) + s * 128, s);
        wg_commit();
        if (!ff) fetch();
        TS(w4 == 0 ? 28 : 63);
        if (OEV == 2) {
            wg_wait<0>();
            if (leader) mbar_arrive(B_OE);
        }
        if (DFV == 0) mbar_wait(B_DF, 0);
        for (;;) {
            uint32_t m = 0;
#pragma unroll
            for (int t = 0; t < 20; t++) m = max(m, af[t]);
            if (!__any_sync(0xffffffffu, m == SENT)) break;
            fetch();
        }
        TS(w4 == 0 ? 7 : 63);
        if (OEV == 0) {
            wg_wait<0>();
            if (leader) mbar_arrive(B_OE);
        }
        wg_fence();
#pragma unroll
        for (int s = 0; s < 5; s++)
            wgmma_own(oc, af[2 * s], af[10 + 2 * s], af[2 * s + 1], af[11 + 2 * s], desc_lo(wo_buf(1), 10240) + s * 128, 1);
        wg_commit();
        if (OEV == 1) {
            wg_wait<1>();
            if (leader) mbar_arrive(B_OE);
        }
        if (DFV == 1) mbar_wait(B_DF, 0);
#pragma unroll 1
        for (int i = 1 + NRS; i < 8; i++) {
            const uint32_t ao = desc_lo(0, 128) + (o_buf(i) >> 4), wo = desc_lo(0, 10240) + (wo_buf(i) >> 4);
            mbar_wait(B_G2 + i * 8, 0);
            TS(w4 == 0 ? (i < 2 ? 6 + i : i < 7 ? 9 + i : 17) : 63);
            wg_fence();
#pragma unroll
            for (int s = 0; s < 5; s++) wgmma_out(oc, ao + s * 16, wo + s * 128, 1);
            wg_commit();
            if (i < 4) {
                wg_wait<1>();
                if (i > 1 && leader) mbar_arrive(B_OE - 8 + i * 8);
            }
        }
        TS(w4 == 0 ? 8 : 63);

        if (min(sel1, sel2) < 16) {
            mbar_wait(B_MOD, 0);
#pragma unroll 1
            for (int j = 0; j < 2; j++) {
                const uint32_t sel = j ? sel2 : sel1;
#pragma unroll
                for (int t = 0; t < 20; t++) {
                    const uint32_t u = lds4(SM_U + j * 320 + cq * 4 + (t < 16 ? odd * 64 + t * 16 : (odd ? 0 : 256) + (t - 16) * 16));
                    if (sel == r) nb[2 * t] = hadd2(nb[2 * t], u);
                    if (sel == r + 8) nb[2 * t + 1] = hadd2(nb[2 * t + 1], u);
                }
            }
        }
        wg_wait<0>();
        TS(w4 == 0 ? 9 : 63);
        const bool nan = oc[0] != oc[0] || oc[2] != oc[2];
#pragma unroll
        for (int part = 0; part < 3; part++) {
            const int s0 = part ? part * 4 - 4 : 8, ns = part ? 4 : 2;
#pragma unroll
            for (int i = 0; i < 4; i++) {
                if (i >= ns) break;
                const int s = s0 + i;
                const uint32_t y0 = hfma2(n0, nb[s * 4], pack2(oc[s * 8 + 0], oc[s * 8 + 1]));
                const uint32_t y1 = hfma2(n1, nb[s * 4 + 1], pack2(oc[s * 8 + 2], oc[s * 8 + 3]));
                const uint32_t y2 = hfma2(n0, nb[s * 4 + 2], pack2(oc[s * 8 + 4], oc[s * 8 + 5]));
                const uint32_t y3 = hfma2(n1, nb[s * 4 + 3], pack2(oc[s * 8 + 6], oc[s * 8 + 7]));
                asm volatile("stmatrix.sync.aligned.m8n8.x4.shared.b16 [%0], {%1,%2,%3,%4};"
                             ::"r"(((s < 8 ? m128 : m64) ^ ((s & 3) * 32)) + (s & 4) * 512 + rk), "r"(y0), "r"(y1), "r"(y2), "r"(y3) : "memory");
            }
            __syncwarp();
            uint4 v[4];
#pragma unroll
            for (int i = 0; i < 4; i++)
                if (i < ns) v[i] = lds16(!part ? l64 + i * 512 : (l128 ^ ((i & 1) * 64)) + i * 512 + s0 * 512);
#pragma unroll
            for (int i = 0; i < 4; i++)
                if (i < ns) *reinterpret_cast<uint4*>(!part ? o64 + i * 8 * 2560 : o128 + i * 4 * 2560 + s0 * 32) = v[i];
            if (part == 0) TS(w4 == 0 ? 1 : 63);
        }
        TS(w4 == 0 ? 10 : 63);
        if (lane == 0) mbar_arrive(B_DONE);
        uint32_t redo;
        asm volatile("{\n.reg .pred p, q;\nsetp.ne.u32 p, %1, 0;\nbar.cta.red.or.pred q, 10, 128, p;\nselp.u32 %0, 1, 0, q;\n}"
                     : "=r"(redo) : "r"((uint32_t)nan) : "memory");
        if (redo) {
            const int cb = hg >> 1;
#pragma unroll 1
            for (int i = 0; i < 8; i++) {
                if (leader) {
                    mbar_expect_tx(B_RE, 25600);
                    tma_3d(SM_W, &P.woa, B_RE, 0, i * 80, (cb * 5 + 1) >> 1);
                    tma_2d(SM_W + 20480, &P.wob, B_RE, cb * 160 + ((cb & 1) ? 0 : 128), i * 80);
                }
#pragma unroll 1
                for (int s = 0; s < 20; s++) {
                    const int w = w4 * 640 + s * 32 + lane;
                    uint32_t v, it = 0;
                    do {
                        v = ld_relaxed4(reinterpret_cast<const uint32_t*>(ow + i * SC_SIZE) + w);
                        if (++it > (1u << 22)) fault();
                    } while ((v >> 16) == 0xFFFFu || (v & 0xFFFFu) == 0xFFFFu);
                    sts4(SM_X + w * 4, v);
                }
                fence_async_smem();
                __syncwarp();
                bar_sync(10, 128);
                mbar_wait(B_RE, i & 1);
                wg_fence();
#pragma unroll
                for (int s = 0; s < 5; s++) wgmma_out(oc, desc_lo(SM_X, 128) + s * 16, desc_lo(SM_W, 10240) + s * 128, s || i);
                wg_commit();
                wg_wait<0>();
                bar_sync(10, 128);
            }
#pragma unroll
            for (int t = 0; t < 40; t++) {
                const int col = (t < 32 ? kba * 64 + (t >> 1) * 8 : kbr * 64 + odd * 32 + ((t - 32) >> 1) * 8) + cq * 2;
                *reinterpret_cast<uint32_t*>(P.op + ((orow + r + (t & 1) * 8) * 2 + par) * 640 + col) =
                    hfma2((t & 1) ? n1 : n0, nb[t], pack2(oc[2 * t], oc[2 * t + 1]));
            }
        }
    } else if (role < 12) {
        asm volatile("setmaxnreg.dec.sync.aligned.u32 96;");
        const int t = tid - 256;
        uint32_t tag = ld_relaxed4(g_cnt);
        float gv = 0.f;
        int grow = hg * 16 + (t >> 3);
        mbar_wait(B_RG, 0);
        TS(warp == 8 ? 48 : 63);
        {
            float r0 = 0.f, r1 = 0.f, g0 = 0.f, g1 = 0.f;
            const uint32_t sw = (t >> 4) * 128 + (((t ^ (t >> 4)) & 7) << 4), hi = (t >> 3) & 1;
            mbar_wait(B_XL0, 0);
            tag = (tag * 8 + 2048) & 0xF800u;
            sts4(SM_KEY + 20 * 4, tag);
#pragma unroll 1
            for (int i = 0; i < 5; i++) {
                const int p = (RG_ORDER >> (i * 4)) & 7, kb = 2 * p + hi;
                mbar_wait(p < 3 ? B_FULL + (p & 1) * 32 : B_RG2, p == 2);
                if (p < 2) mbar_wait(B_FULL + p * 32 + 16, 0);
                const uint32_t xa = sw + (kb < 5 ? SM_X + (kb & 3) * 16384 + hg * 2048 : SM_HALO - 5 * 2048 + kb * 2048);
                const uint4 a = lds16(xa), b = lds16(xa + 1024);
                const uint4 w = lds16(SM_RED + p * 256 + (t & 15) * 16), v = lds16(SM_RED + 1280 + p * 256 + (t & 15) * 16);
                if (__ballot_sync(0xffffffffu, lane == 0 || a.w == b.w) && lane == 0 && p < 3) mbar_arrive(B_XE + p * 8);
                TS5(warp == 8 ? 51 + i : 63);
                const uint32_t as[4] = {a.x, a.y, a.z, a.w}, bs[4] = {b.x, b.y, b.z, b.w};
                const uint32_t ws[4] = {w.x, w.y, w.z, w.w}, vs[4] = {v.x, v.y, v.z, v.w};
#pragma unroll
                for (int e = 0; e < 4; e++) {
                    r0 = fmaf(bf_lo(as[e]), bf_lo(ws[e]), r0);
                    r1 = fmaf(bf_lo(bs[e]), bf_lo(ws[e]), r1);
                    g0 = fmaf(bf_lo(as[e]), bf_lo(vs[e]), g0);
                    g1 = fmaf(bf_lo(bs[e]), bf_lo(vs[e]), g1);
                    r0 = fmaf(bf_hi(as[e]), bf_hi(ws[e]), r0);
                    r1 = fmaf(bf_hi(bs[e]), bf_hi(ws[e]), r1);
                    g0 = fmaf(bf_hi(as[e]), bf_hi(vs[e]), g0);
                    g1 = fmaf(bf_hi(bs[e]), bf_hi(vs[e]), g1);
                }
            }
            const bool up = lane & 4;
            r0 = (hi ? r1 : r0) + __shfl_xor_sync(0xffffffffu, hi ? r0 : r1, 8);
            g0 = (hi ? g1 : g0) + __shfl_xor_sync(0xffffffffu, hi ? g0 : g1, 8);
            float r = (up ? g0 : r0) + __shfl_xor_sync(0xffffffffu, up ? r0 : g0, 4);
            r += __shfl_xor_sync(0xffffffffu, r, 2);
            r = bf_round(r + __shfl_xor_sync(0xffffffffu, r, 1));
            const int row = hg * 16 + (t >> 4) + hi * 8;
            const uint32_t u = f2u(r);
            if (!up) sts4(SM_KEY + (t >> 3) * 4, (((int)u < 0 ? ~u : u | 0x80000000u) & 0xFFFF0000u) | (2047 - (p0 + row) * 2 - par));
            gv = r;
            grow = row;
        }
        TS(warp == 8 ? 63 : 63);
        mbar_wait(B_RG2, 0);
        bar_sync(4, 128);
        if (warp == 8) {
            const uint32_t key = lds4(SM_KEY + (lane & 15) * 4);
            uint32_t k1 = __reduce_max_sync(0xffffffffu, key);
            uint32_t k2 = __reduce_max_sync(0xffffffffu, key == k1 ? 0u : key);
            if (elect_one()) {
                st_relaxed8(g_cand + cid, k1 | tag, k2 | tag);
                red_inc<MAPV == 3 ? 2 : 1>(g_cnt, tag);
            }
            TS(49);
        }
        if ((lane & 7) == 4) st_relaxed4(g_gate + tile * 128 + grow, f2u(bf_round(sigmoidf(gv))) | tag);
        const int cq = lane & 3, w4 = warp & 3;
        const uint32_t la = keep(cq * 256 + (((lane >> 2) ^ cq * 2) << 4));
        const uint32_t sel = keep(0x44444444u ^ (0x54u << (lane >> 2 & 1) * 8 + (lane & 16)));
        if (NFFN) {
            float4 d;
            uint4* dst;
            if (cid < NFFN) {
                float dg[8], du[8];
                mbar_wait(B_GU, 0);
                mbar_wait(B_XS, 0);
                TS(warp == 8 ? 50 : 63);
                if (GW & 1) mbar_wait(B_EMPTY + 3 * 8, 0);
                wg_fence();
#pragma unroll
                for (int i = 0; i < 10; i++) wgmma_vec(dg, desc_lo(SM_F + i * 2048, 16), desc_lo(SM_XS + i * 32, 16), i);
                wg_commit();
                mbar_wait(B_UP, 0);
                TS(warp == 10 ? 58 : 63);
                if (GW & 2) mbar_wait(B_EMPTY + 3 * 8, 0);
                wg_fence();
#pragma unroll
                for (int i = 0; i < 10; i++) wgmma_vec(du, desc_lo(SM_UP + i * 2048, 16), desc_lo(SM_XS + i * 32, 16), i);
                wg_commit();
                wg_wait<0>();
                if (lane == 0) mbar_arrive(B_GUD), mbar_arrive(B_DF);
                TS(warp == 8 ? 54 : warp == 10 ? 59 : 63);
                if (cq == 0) {
                    st_relaxed16(sc + SC_GU + w4 * 16 + (lane >> 2), f2u(dg[0]), f2u(dg[4]), f2u(du[0]), f2u(du[4]));
                    st_relaxed16(sc + SC_GU + w4 * 16 + 8 + (lane >> 2), f2u(dg[2]), f2u(dg[6]), f2u(du[2]), f2u(du[6]));
                }
            } else {
                uint4 wv[2][8], wr[4];
                mbar_wait(B_UP, 0);
                TS(warp == 10 ? 58 : 63);
                if (SP_W) mbar_wait(B_EMPTY + 3 * 8, 0);
#pragma unroll
                for (int i = 0; i < 8; i++) wv[i >> 2][4 + (i & 3)] = lds16((la ^ (i & 1) * 144) + SM_UP + w4 * 4096 + (i >> 1) * 1024);
                if (landed<4>(wv[0] + 4, lane) & landed<4>(wv[1] + 4, lane)) mbar_arrive(B_GUD);
                TS(warp == 8 ? 54 : 63);
                mbar_wait(B_GU, 0);
#pragma unroll
                for (int i = 0; i < 4; i++) wr[i] = lds16((la ^ (i & 1) * 144) + SM_F + 12288 + w4 * 2048 + (i >> 1) * 1024);
                mbar_wait(B_XS, 0);
                if (w4 == 0) {
                    uint4 pq[4];
                    pace(t_start, HS_T);
                    poll<4>(pq, g_sc + ((cid >> 1) * 4 - 148) * SC_SIZE + SC_GU + (cid & 1) * 32 + lane, SC_SIZE);
                    TS(warp == 8 ? 55 : 63);
                    swiglu(pq, SM_H + (lane & 6) * 8 + (lane >> 3) * 4 + (lane & 1) * 2, 64);
                }
                bar_sync(4, 128);
                TS(warp == 8 ? 57 : 63);
                const uint4 h = lds16(SM_H + (lane & 8) * 8 + cq * 16);
                const uint32_t hv[4] = {h.x, h.y, h.z, h.w}, hr[2] = {(w4 & 1) ? h.z : h.x, (w4 & 1) ? h.w : h.y};
                d = vec_mma<4>(wr, hr, sel);
                dst = g_sc + (cid * 5 - 520 + w4) * SC_SIZE + SC_Y + (lane & 1) * 32 + (lane >> 1);
                float c[2][2][4] = {};
                const uint32_t s2 = sel + ((sel & 0x10101010u) >> 3) * 17;
#pragma unroll
                for (int i = 7; i >= 0; i--) {
                    const uint32_t x0 = prmt(hv[i >> 1], (i & 1) ? s2 : sel), x1 = prmt(hv[i >> 1], ((i & 1) ? s2 : sel) >> 16);
#pragma unroll
                    for (int n = 0; n < 2; n++) {
                        if (i >= 4) wv[n][i - 4] = lds16((la ^ (i & 1) * 144) + SM_F - 6144 + w4 * 4096 + n * 2048 + (i >> 1) * 1024);
                        mma16(c[n][i & 1], wv[n][i].x, wv[n][i].y, wv[n][i].z, wv[n][i].w, x0, x1);
                    }
                }
#pragma unroll
                for (int n = 0; n < 2; n++)
                    st_relaxed16(dst + n * 16, f2u(c[n][0][0] + c[n][1][0]), f2u(c[n][0][1] + c[n][1][1]), f2u(c[n][0][2] + c[n][1][2]),
                                 f2u(c[n][0][3] + c[n][1][3]));
                dst += (4 - w4) * SC_SIZE + w4 * 8;
                TS(warp == 8 ? 30 : 63);
                if (lane == 0 && f2u(d.x) != SENT) mbar_arrive(B_DF);
                if (w4 & 1) {
                    sts16(SM_RED + 512 + (w4 & 2) * 256 + lane * 16, f2u(d.x), f2u(d.y), f2u(d.z), f2u(d.w));
                    bar_arrive(13 + (w4 >> 1), 64);
                } else {
                    bar_sync(13 + (w4 >> 1), 64);
                    const uint4 o = lds16(SM_RED + 512 + (w4 & 2) * 256 + lane * 16);
                    st_relaxed16(dst, f2u(d.x + u2f(o.x)), f2u(d.y + u2f(o.y)), f2u(d.z + u2f(o.z)), f2u(d.w + u2f(o.w)));
                }
            }
        } else {
            if (t < 4) mbar_arrive(B_GUD);
            if (t < 4) mbar_arrive(B_DF);
            mbar_wait(B_XS, 0);
        }
        TS(warp == 8 ? 51 : 63);
        const uint32_t k1 = lds4(SM_KEY + 16 * 4), k2 = lds4(SM_KEY + 17 * 4);
        const uint32_t mine = (tile >> 1) * 256 + HALF * 128 + par;
        const bool own1 = (~k1 & 0x781) == mine, own2 = (~k2 & 0x781) == mine;
        if ((own1 || own2) && NFFN) {
            const int rg = min(t / 40, 2), un = (hg >> 1) * 40 + t % 40, up = (hg >> 1) * 80 + min(t, 79);
            mbar_wait(B_RS, 0);
            pace(t_start, Y_T);
            TS(warp == 8 ? 60 : 63);
#pragma unroll 1
            for (int j = !own1; j <= own2; j++) {
                const uint4* p = g_sc + (rg * 5 + 20 + (un >> 5)) * SC_SIZE + SC_Y + j * 32 + (un & 31);
                float y[4];
                bool bad;
                do {
                    uint4 yp[7];
#pragma unroll
                    for (int i = 0; i < 7; i++) yp[i] = i < 6 || rg < 2 ? ld_relaxed16(p + i * 15 * SC_SIZE) : make_uint4(0, 0, 0, 0);
                    y[0] = y[1] = y[2] = y[3] = 0.f;
                    bad = false;
#pragma unroll
                    for (int i = 0; i < 7; i++) {
                        y[0] += u2f(yp[i].x); y[1] += u2f(yp[i].y); y[2] += u2f(yp[i].z); y[3] += u2f(yp[i].w);
                        bad |= yp[i].w == SENT;
                    }
                } while (__any_sync(0xffffffffu, bad));
                TS(warp == 8 ? 53 : 63);
                sts16(SM_SENT + j * 2048 + t * 16, f2u(y[0]), f2u(y[1]), f2u(y[2]), f2u(y[3]));
                bar_sync(4, 128);
                if (w4 < 3) {
                    const uint32_t key = j ? k2 : k1, ya = SM_SENT + j * 2048 + t * 8;
                    const float rs = bf_round(sigmoidf(u2f(((int)key < 0 ? key & 0x7FFFFFFFu : ~key) & 0xFFFF0000u)));
                    const float2 y0 = lds8f(ya), y1 = lds8f(ya + 640), y2 = lds8f(ya + 1280);
                    const uint2* q = reinterpret_cast<const uint2*>(g_sc + (up >> 6) * SC_SIZE + SC_Y + j * 32) + (up & 63);
                    const float sx = y0.x + y1.x + y2.x, sy = y0.y + y1.y + y2.y;
                    uint2 z[4];
                    pace(t_start, Y2_T);
                    do {
#pragma unroll
                        for (int i = 0; i < 4; i++) z[i] = ld_relaxed8(q + i * 10 * SC_SIZE);
                    } while (__any_sync(0xffffffffu, max(max(z[0].y, z[1].y), max(z[2].y, z[3].y)) == SENT));
                    TS(warp == 8 ? 62 : 63);
                    if (t < 80)
                        sts4(SM_U + j * 320 + t * 4, pack2(bf_round(sx + (u2f(z[0].x) + u2f(z[1].x)) + (u2f(z[2].x) + u2f(z[3].x))) * rs,
                                                           bf_round(sy + (u2f(z[0].y) + u2f(z[1].y)) + (u2f(z[2].y) + u2f(z[3].y))) * rs));
                }
            }
            bar_sync(4, 128);
        }
        if (t == 0) mbar_arrive(B_MOD);
        TS(warp == 8 ? 52 : 63);
    } else {
        asm volatile("setmaxnreg.dec.sync.aligned.u32 32;");
        if (warp == 15) {
            if (EPF_M) {
                pace(t_start, EPF_T);
                if (lane < (EPF_M << EPF_H)) l2_prefetch(P.wp + (EPF_N * 132 + (lane >> EPF_H) * 128 + bid) * 64 + (lane & EPF_H) * 32);
            }
#pragma unroll 1
            for (int i = PF_0; i < PF_N; i++) {
                pace(t_start, (i < 6 ? PF_UP : PF_DN) + i * PF_DT);
                const int ln = (i * 128 + cid) * 32 + lane;
                l2_prefetch((ln < 17280 ? P.upp : ln < 23680 ? P.wop - 17280 * 64 : P.dp - 23680 * 64) + ln * 64);
            }
            if (elect_one()) {
#pragma unroll 1
                for (int i = 0; i < (!NFFN ? 0 : cid < NFFN ? 8 : 12); i++) {
                    pace(t_start, GU_T0 + i * (cid < NFFN ? GU_DT : GU_DS) + (cid & 7) * GU_ST);
                    if (cid < NFFN) tma_2d(SM_F + i * 2560, &P.gate, B_GU, (cid >> 2) * 64, (cid & 3) * 160 + i * 20);
                    else tma_2d(SM_F - 4096 + i * 2048, &P.down, B_GU, min(i, 4 + (i >> 1)) * 64, cid * 32 - 2368 + (i > 8 ? (i & 1) * 16 : 0));
                }
            }
            __syncwarp();
            int it = (smem_u32(smem_raw) & 0xFFFFFF) == SB ? 0 : 1 << 20;
            while (!mbar_try(B_DONE, 0) || !mbar_try(B_MOD, 0))
                if (++it > (1 << 20)) fault();
        } else if (warp == 13) {
#pragma unroll 1
            for (int i = 0; i < 10; i++) sts16(SM_SENT + i * 512 + lane * 16, SENT, SENT, SENT, SENT);
            fence_async_smem();
            __syncwarp();
            if (elect_one()) {
                if (!RW_REG) mbar_expect_tx(B_RG, 2560);
                mbar_expect_tx(B_GU, cid < NFFN ? 20480 : 24576);
                asm volatile("mbarrier.expect_tx.relaxed.cta.shared::cta.b64 [%0], 10240;" ::"r"(B_RG2 + rk) : "memory");
                pace(t_start, RW1_T);
                bulk_load(SM_RED, P.w_r, 1280, B_RG);
                bulk_load(SM_RED + 1280, P.gate_w, 1280, B_RG);
#pragma unroll 1
                for (int i = 0; i < 5; i++) {
                    pace(t_start, RG1_T0 + i * RG1_DT);
                    tma_3d(SM_HALO + i * 2048, &P.xg, B_RG2, 320 + i * 64, par, p0 + hg * 16);
                }
#pragma unroll
                for (int i = 0; i < 23; i++) mbar_init(B_GUD + i * 8, i == 10 ? 8 : i == 22 || !i ? 4 : i < 16 ? 1 : 2);
                bulk_store(sc + SC_HALO, SM_SENT, 5120);
                asm volatile("cp.async.bulk.commit_group;\ncp.async.bulk.wait_group 0;" ::: "memory");
                mbar_arrive(B_RG2);
                TS(43);
                const unsigned goal = (ld_relaxed4(g_cnt + 32) | (NCTA - 1)) + 1;
#pragma unroll 1
                for (int i = RS_E; i < RS_N; i++) {
                    pace(t_start, RS_T0 + (i - RS_E) * RS_DT + (cid & 7) * RS_S);
                    bulk_store(sc + i * (1280 / RS_N), SM_SENT, 20480 / RS_N);
                }
                asm volatile("cp.async.bulk.commit_group;\ncp.async.bulk.wait_group 0;" ::: "memory");
                red_inc(g_cnt + 32, goal);
                mbar_arrive(B_RS);
                TS(44);
                while (ld_relaxed4(g_cnt + 32) - goal > 0x80000000u) {}
                mbar_arrive(B_INIT);
                TS(45);
            }
        } else if (warp == 14) {
            if (elect_one()) {
#pragma unroll 1
                for (int kb = 1; kb < 10; kb++) {
                    const uint32_t fb = B_FULL + (kb & 3) * 16, dst = SM_X + (kb & 3) * 16384;
                    mbar_wait(fb + (B_EMPTY - B_FULL + 8), ~(kb >> 2) & 1);
                    if (kb >= 4) mbar_wait(B_XE + (kb - 4 >> 1) * 8, 0);
                    pace(t_start, max(PACE_A - PACE_B / 2 + 2 * kb * PACE_B, PACE_W0 - X_OFF + (2 * kb + 1) * PACE));
                    tma_3d(dst, &P.x2, fb, kb * 64, par, p0);
                    TS5(41 + kb);
                }
            }
            __syncwarp();
            pace(t_start, CAND_T);
            {
                const uint32_t tag = lds4(SM_KEY + 20 * 4);
                uint4 c[2], v;
                do {
                    c[0] = ld_relaxed16(g_cand + lane * 2);
                    c[1] = ld_relaxed16(g_cand + lane * 2 + 64);
                    v = ld_relaxed16(g_gate + tile * 128 + lane * 4);
                } while (__any_sync(0xffffffffu, ((c[0].x ^ tag) | (c[0].z ^ tag) | (c[1].x ^ tag) | (c[1].z ^ tag) | (v.x ^ tag) |
                                                  (v.y ^ tag) | (v.z ^ tag) | (v.w ^ tag)) & 0xF800u));
                const uint32_t a1 = max(c[0].x, c[0].z), b1 = max(c[1].x, c[1].z), l1 = max(a1, b1);
                const uint32_t l2 = max(max(max(c[0].y, c[0].w), max(c[1].y, c[1].w)),
                                        max(max(min(c[0].x, c[0].z), min(c[1].x, c[1].z)), min(a1, b1)));
                const uint32_t k1 = __reduce_max_sync(0xffffffffu, l1);
                const uint32_t k2 = __reduce_max_sync(0xffffffffu, l1 == k1 ? l2 : l1);
                sts16(SM_GATE + lane * 16, v.x, v.y, v.z, v.w);
                __syncwarp();
                if (elect_one()) {
                    bulk_load(SM_XS, P.xp + (~k1 & 2047) * 640 + (cid & 3) * 160, 320, B_XS);
                    bulk_load(SM_XS + 320, P.xp + (~k2 & 2047) * 640 + (cid & 3) * 160, 320, B_XS);
                    sts16(SM_KEY + 16 * 4, k1, k2, 0, 0);
                    mbar_expect_tx(B_XS, 640);
                    mbar_arrive(B_GT);
                    TS(56);
                }
            }
            bar_sync(12, 64);
            pace(t_start, 0);
            pace(clock(), HALO_D);
            TS(24);
            uint4 hv[5];
            poll<5>(hv, sc + (SC_HALO - (tile < 2 ? 0 : 16 * SC_SIZE) + lane), 32);
#pragma unroll
            for (int s = 0; s < 5; s++) sts16(SM_HALO + s * 512 + lane * 16, hv[s].x, hv[s].y, hv[s].z, hv[s].w);
            bar_arrive(8, 64);
            TS(25);
        } else {
            if (elect_one()) {
#pragma unroll 1
                for (int s = W_S0; s < 20; s++) {
                    const uint32_t fb = B_FULL + (s & 7) * 8, dst = SM_W + (s & 7) * 15360;
                    mbar_wait(fb + (B_EMPTY - B_FULL), ~(s >> 3) & 1);
                    pace(t_start, max(PACE_A + s * PACE_B, PACE_W0 + s * PACE));
                    mbar_expect_tx(fb, (s & 1) ? 15360 : 15360 + 16384);
                    tma_3d(dst, &P.w, fb, wcm, s * 32, 0);
                    tma_3d(dst + 12288, &P.wr, fb, wcr, s * 32, 0);
                    TS2(20 + s);
                    if (s == W_S0) TS(41);
                }
                mbar_wait(B_RG2, 0);
                if (NFFN) {
                    mbar_wait(B_EMPTY + 5 * 8, 1);
                    mbar_expect_tx(B_UP, cid < NFFN ? 20480 : 16384);
                    TS(46);
                    if (cid < NFFN) tma_2d(SM_UP, &P.up, B_UP, (cid >> 2) * 64, (cid & 3) * 160);
                    else
#pragma unroll 1
                        for (int i = 0; i < 8; i++) tma_2d(SM_UP + i * 2048, &P.down, B_UP, i * 64, cid * 32 - 2352);
                }
                const int cb = hg >> 1, ca = (cb * 5 + 1) >> 1, cr = cb * 160 + ((cb & 1) ? 0 : 128);
#pragma unroll 1
                for (int j = 0; j < 8; j++) {
                    const int i = j ^ (j == 3 || j == 4 ? 7 : 0);
                    if (j != 3) mbar_wait(j < 3 ? B_EMPTY + ((2 * j + 7) & 7) * 8 : B_GUD + (j - 4) * 8, j == 0);
                    if (j >= 5) {
                        if (C5_T) pace(t_start, (j == 5 ? C5_T : j == 6 ? C6_T : C7_T) - HALF * C_O);
                        else pace(clock(), j == 5 ? C5_D : C6_D);
                    }
                    if (C0_T | C1_T | C2_T | C3_T | C4_T) pace(t_start, j == 0 ? C0_T : j == 1 ? C1_T : j == 2 ? C2_T : j == 3 ? C3_T : C4_T);
                    const uint32_t dst = wo_buf(i), gb = B_G2 + i * 8;
                    mbar_expect_tx(gb, 25600);
                    tma_3d(dst, &P.woa, gb, 0, src_of(i, hg) * 80, ca);
                    tma_2d(dst + 20480, &P.wob, gb, cr, src_of(i, hg) * 80);
                }
            }
        }
    }
}

typedef CUresult (*EncodeFn)(CUtensorMap*, CUtensorMapDataType, cuuint32_t, void*, const cuuint64_t*, const cuuint64_t*,
                             const cuuint32_t*, const cuuint32_t*, CUtensorMapInterleave, CUtensorMapSwizzle,
                             CUtensorMapL2promotion, CUtensorMapFloatOOBfill);

void encode(EncodeFn fn, CUtensorMap* m, const void* ptr, int rank, const cuuint64_t* dims, const cuuint64_t* strides,
            const cuuint32_t* box, CUtensorMapSwizzle swz) {
    const cuuint32_t es[4] = {1, 1, 1, 1};
    fn(m, CU_TENSOR_MAP_DATA_TYPE_BFLOAT16, rank, const_cast<void*>(ptr), dims, strides, box, es,
       CU_TENSOR_MAP_INTERLEAVE_NONE, swz, CU_TENSOR_MAP_L2_PROMOTION_L2_128B, CU_TENSOR_MAP_FLOAT_OOB_FILL_NONE);
}

}

extern "C" void kernel_launch(void* const* d_in, const int* in_sizes, int n_in, void* d_out, int out_size) {
    (void)in_sizes; (void)n_in; (void)out_size;
    Params P;
    P.xp = (const __nv_bfloat16*)d_in[0];
    P.wp = (const __nv_bfloat16*)d_in[1];
    P.wop = (const __nv_bfloat16*)d_in[2];
    P.dp = (const __nv_bfloat16*)d_in[7];
    P.upp = (const __nv_bfloat16*)d_in[6];
    P.op = (__nv_bfloat16*)d_out;
    P.w_r = (const __nv_bfloat16*)d_in[4];
    P.gate_w = (const __nv_bfloat16*)d_in[8];

    void* fp = nullptr;
    cudaDriverEntryPointQueryResult st;
    cudaGetDriverEntryPoint("cuTensorMapEncodeTiled", &fp, cudaEnableDefault, &st);
    EncodeFn fn = (EncodeFn)fp;
    const cuuint64_t xd[3] = {640, 2, 1024}, xs[2] = {1280, 2560};
    const cuuint32_t bx[3] = {64, 1, 64}, bx2[3] = {64, 1, 128};
    encode(fn, &P.x2, d_in[0], 3, xd, xs, bx2, CU_TENSOR_MAP_SWIZZLE_128B);
    encode(fn, &P.x, d_in[0], 3, xd, xs, bx, CU_TENSOR_MAP_SWIZZLE_128B);
    const cuuint64_t wd[3] = {640, 640, 3}, ws[2] = {3840, 1280};
    const cuuint32_t bw[3] = {64, 32, 3}, bwr[3] = {16, 32, 3};
    encode(fn, &P.w, d_in[1], 3, wd, ws, bw, CU_TENSOR_MAP_SWIZZLE_128B);
    encode(fn, &P.wr, d_in[1], 3, wd, ws, bwr, CU_TENSOR_MAP_SWIZZLE_32B);
    const cuuint64_t ad[3] = {64, 640, 10}, as[2] = {1280, 128}, bd[2] = {640, 640};
    const cuuint32_t ba[3] = {64, 80, 2}, bb[2] = {32, 80};
    encode(fn, &P.woa, d_in[2], 3, ad, as, ba, CU_TENSOR_MAP_SWIZZLE_128B);
    encode(fn, &P.wob, d_in[2], 2, bd, as, bb, CU_TENSOR_MAP_SWIZZLE_128B);
    const cuuint64_t gd[2] = {1728, 640}, gs[1] = {3456}, dd[2] = {640, 1728};
    const cuuint32_t bg[2] = {64, 20}, bu[2] = {64, 160}, bdn[2] = {64, 16}, bxg[3] = {64, 1, 16};
    encode(fn, &P.xg, d_in[0], 3, xd, xs, bxg, CU_TENSOR_MAP_SWIZZLE_128B);
    encode(fn, &P.gate, d_in[5], 2, gd, gs, bg, CU_TENSOR_MAP_SWIZZLE_128B);
    encode(fn, &P.up, d_in[6], 2, gd, gs, bu, CU_TENSOR_MAP_SWIZZLE_128B);
    encode(fn, &P.up2, d_in[6], 2, gd, gs, bg, CU_TENSOR_MAP_SWIZZLE_128B);
    encode(fn, &P.down, d_in[7], 2, dd, as, bdn, CU_TENSOR_MAP_SWIZZLE_128B);

    cudaFuncSetAttribute(fused_kernel, cudaFuncAttributeMaxDynamicSharedMemorySize, SM_TOTAL);
    fused_kernel<<<NCTA + (MAPV == 3 ? 0 : NEXTRA), 512, SM_TOTAL, cudaStreamPerThread>>>(P);
}
```

```cpp
#include <cuda_runtime.h>
#include <cuda_bf16.h>
#include <cuda.h>
#include <stdint.h>

namespace {

constexpr int NCTA = 128, NEXTRA = 4;
constexpr int NFFN = 108;
constexpr uint32_t SENT = 0xFFFFFFFFu;

constexpr uint32_t SB = 1024;
constexpr uint32_t SM_W = SB;
constexpr uint32_t SM_X = SB + 122880;
constexpr uint32_t SM_F = SB + 192512;
constexpr uint32_t SM_HALO = SB + 212992;
constexpr uint32_t SM_BAR = SB + 223232;
constexpr uint32_t SM_PROF = SB + 223744;
constexpr uint32_t SM_KEY = SB + 224000;
constexpr uint32_t SM_RED = SB + 224128;
constexpr uint32_t SM_XS = SB + 226688;
constexpr uint32_t SM_SENT = SB + 227328;
constexpr uint32_t SM_U = SM_RED + 1920;
constexpr uint32_t SM_H = SM_RED + 1536;
constexpr uint32_t SM_GATE = SM_RED;
constexpr uint32_t SM_TOTAL = 232448;
constexpr uint32_t SM_HALO1 = SM_X + 32768;
constexpr uint32_t SM_UP = SM_W + 61440;
constexpr uint32_t SM_OUT = SM_W + 61440;

constexpr uint32_t B_XL0 = SM_BAR, B_FULL = SM_BAR + 8, B_GT = SM_BAR + 72, B_RG = SM_BAR + 80, B_RG2 = SM_BAR + 88,
                   B_XS = SM_BAR + 96, B_EMPTY = SM_BAR + 128, B_DONE = SM_BAR + 192, B_XE = SM_BAR + 200,
                   B_GUD = SM_BAR + 224, B_OE = SM_BAR + 232, B_OT = SM_BAR + 264, B_MOD = SM_BAR + 296,
                   B_GU = SM_BAR + 104, B_UP = SM_BAR + 112, B_RS = SM_BAR + 312, B_INIT = SM_BAR + 320,
                   B_RE = SM_BAR + 328, B_PUB = SM_BAR + 304, B_G2 = SM_BAR + 336, B_DF = SM_BAR + 400;

struct Params {
    CUtensorMap x, x2, w, wr, woa, wob, xg, gate, up, down, up2;
    __nv_bfloat16* op;
    const __nv_bfloat16 *xp, *wp, *dp, *upp, *wop, *w_r, *gate_w;
};

constexpr int SC_O = 0;
constexpr int SC_HALO = 1280;
constexpr int SC_GU = 1440;
constexpr int SC_Y = 1504;
constexpr int SC_SIZE = 1600;
__device__ __align__(128) uint4 g_sc[NCTA * SC_SIZE];
__device__ __align__(128) uint2 g_cand[NCTA];
__device__ __align__(16) uint32_t g_gate[2048];
__device__ __align__(128) unsigned g_cnt[64];
#define TS(i) do { } while (0)
#define TS2(i) do { } while (0)
#define TSX(i) do { } while (0)

#define TS5(i) do { } while (0)
__device__ __forceinline__ uint32_t smem_u32(const void* p) { return (uint32_t)__cvta_generic_to_shared(p); }
__device__ __forceinline__ void fault() { asm volatile("st.shared.u32 [%0], %0;" ::"r"(0x100001) : "memory"); }
__device__ __forceinline__ void mbar_init(uint32_t bar, uint32_t cnt) {
    asm volatile("mbarrier.init.shared::cta.b64 [%0], %1;" ::"r"(bar), "r"(cnt) : "memory");
}
__device__ __forceinline__ void mbar_expect_tx(uint32_t bar, uint32_t bytes) {
    asm volatile("mbarrier.arrive.expect_tx.shared::cta.b64 _, [%0], %1;" ::"r"(bar), "r"(bytes) : "memory");
}
__device__ __forceinline__ void mbar_arrive(uint32_t bar) {
    asm volatile("mbarrier.arrive.shared::cta.b64 _, [%0];" ::"r"(bar) : "memory");
}
__device__ __forceinline__ bool mbar_try(uint32_t bar, uint32_t parity) {
    uint32_t ok;
    asm volatile("{\n.reg .pred p;\nmbarrier.try_wait.parity.shared::cta.b64 p, [%1], %2;\nselp.u32 %0, 1, 0, p;\n}"
                 : "=r"(ok) : "r"(bar), "r"(parity) : "memory");
    return ok;
}
__device__ __forceinline__ void mbar_wait(uint32_t bar, uint32_t parity) {
    asm volatile("{\n.reg .pred p;\nAGAIN:\nmbarrier.try_wait.parity.shared::cta.b64 p, [%0], %1;\n@!p bra AGAIN;\n}"
                 ::"r"(bar), "r"(parity) : "memory");
}
__device__ __forceinline__ void tma_2d(uint32_t dst, const CUtensorMap* m, uint32_t bar, int c0, int c1) {
    asm volatile("cp.async.bulk.tensor.2d.shared::cluster.global.mbarrier::complete_tx::bytes [%0], [%1, {%3, %4}], [%2];"
                 ::"r"(dst), "l"(m), "r"(bar), "r"(c0), "r"(c1) : "memory");
}
__device__ __forceinline__ void bulk_load(uint32_t dst, const void* src, uint32_t bytes, uint32_t bar) {
    asm volatile("cp.async.bulk.shared::cluster.global.mbarrier::complete_tx::bytes [%0], [%1], %2, [%3];"
                 ::"r"(dst), "l"(src), "r"(bytes), "r"(bar) : "memory");
}
__device__ __forceinline__ void bulk_store(void* dst, uint32_t src, uint32_t bytes) {
    asm volatile("cp.async.bulk.global.shared::cta.bulk_group [%0], [%1], %2;" ::"l"(dst), "r"(src), "r"(bytes) : "memory");
}
__device__ __forceinline__ void tma_3d(uint32_t dst, const CUtensorMap* m, uint32_t bar, int c0, int c1, int c2) {
    asm volatile("cp.async.bulk.tensor.3d.shared::cluster.global.mbarrier::complete_tx::bytes [%0], [%1, {%3, %4, %5}], [%2];"
                 ::"r"(dst), "l"(m), "r"(bar), "r"(c0), "r"(c1), "r"(c2) : "memory");
}
__device__ __forceinline__ void fence_async_smem() { asm volatile("fence.proxy.async.shared::cta;" ::: "memory"); }
__device__ __forceinline__ void wg_fence() { asm volatile("wgmma.fence.sync.aligned;" ::: "memory"); }
__device__ __forceinline__ void wg_commit() { asm volatile("wgmma.commit_group.sync.aligned;" ::: "memory"); }
template <int N> __device__ __forceinline__ void wg_wait() { asm volatile("wgmma.wait_group.sync.aligned %0;" ::"n"(N) : "memory"); }
__device__ __forceinline__ void bar_sync(int id, int n) { asm volatile("bar.cta.sync %0, %1;" ::"r"(id), "r"(n) : "memory"); }
__device__ __forceinline__ void bar_arrive(int id, int n) { asm volatile("bar.cta.arrive %0, %1;" ::"r"(id), "r"(n) : "memory"); }

__device__ constexpr uint32_t desc_lo(uint32_t addr, uint32_t lbo) { return (addr >> 4) | ((lbo >> 4) << 16); }
__device__ __forceinline__ bool elect_one() {
    uint32_t p;
    asm volatile("{\n.reg .pred p;\nelect.sync _|p, 0xffffffff;\nselp.u32 %0, 1, 0, p;\n}" : "=r"(p));
    return p;
}
__device__ __forceinline__ uint32_t ld_relaxed4(const void* p) {
    uint32_t v;
    asm volatile("ld.relaxed.gpu.global.u32 %0, [%1];" : "=r"(v) : "l"(p) : "memory");
    return v;
}
__device__ __forceinline__ void st_relaxed4(void* p, uint32_t v) {
    asm volatile("st.relaxed.gpu.global.u32 [%0], %1;" ::"l"(p), "r"(v) : "memory");
}
template <int N = 1>
__device__ __forceinline__ void red_inc(unsigned* p, unsigned after) {
    asm volatile("red.relaxed.gpu.global.add.u32 [%0], %2;" ::"l"(p), "r"(after), "n"(N) : "memory");
}
__device__ __forceinline__ uint32_t lds4(uint32_t a) {
    uint32_t v;
    asm volatile("ld.shared.u32 %0, [%1];" : "=r"(v) : "r"(a) : "memory");
    return v;
}
__device__ __forceinline__ float2 lds8f(uint32_t a) {
    float2 v;
    asm volatile("ld.shared.v2.f32 {%0, %1}, [%2];" : "=f"(v.x), "=f"(v.y) : "r"(a) : "memory");
    return v;
}
__device__ __forceinline__ void sts4(uint32_t a, uint32_t v) { asm volatile("st.shared.u32 [%0], %1;" ::"r"(a), "r"(v) : "memory"); }
__device__ __forceinline__ uint32_t hmul2(uint32_t a, uint32_t b) {
    uint32_t d;
    asm("mul.rn.bf16x2 %0, %1, %2;" : "=r"(d) : "r"(a), "r"(b));
    return d;
}
__device__ __forceinline__ uint32_t hadd2(uint32_t a, uint32_t b) {
    uint32_t d;
    asm("add.rn.bf16x2 %0, %1, %2;" : "=r"(d) : "r"(a), "r"(b));
    return d;
}
__device__ __forceinline__ uint32_t hfma2(uint32_t a, uint32_t b, uint32_t c) {
    uint32_t d;
    asm("fma.rn.bf16x2 %0, %1, %2, %3;" : "=r"(d) : "r"(a), "r"(b), "r"(c));
    return d;
}
__device__ __forceinline__ uint4 ld_relaxed16(const void* p) {
    uint4 v;
    asm volatile("{\n.reg .b128 t;\n.reg .b64 lo, hi;\nld.relaxed.gpu.global.b128 t, [%4];\nmov.b128 {lo, hi}, t;\n"
                 "mov.b64 {%0, %1}, lo;\nmov.b64 {%2, %3}, hi;\n}" : "=r"(v.x), "=r"(v.y), "=r"(v.z), "=r"(v.w) : "l"(p) : "memory");
    return v;
}
__device__ __forceinline__ void st_relaxed16(void* p, uint32_t a, uint32_t b, uint32_t c, uint32_t d) {
    uint64_t lo = (uint64_t)a | ((uint64_t)b << 32), hi = (uint64_t)c | ((uint64_t)d << 32);
    asm volatile("{\n.reg .b128 t;\nmov.b128 t, {%1, %2};\nst.relaxed.gpu.global.b128 [%0], t;\n}" ::"l"(p), "l"(lo), "l"(hi) : "memory");
}
__device__ __forceinline__ void st_relaxed8(void* p, uint32_t a, uint32_t b) {
    asm volatile("{\n.reg .b64 t;\nmov.b64 t, {%1, %2};\nst.relaxed.gpu.global.b64 [%0], t;\n}" ::"l"(p), "r"(a), "r"(b) : "memory");
}
__device__ __forceinline__ uint2 ld_relaxed8(const void* p) {
    uint2 v;
    asm volatile("{\n.reg .b64 t;\nld.relaxed.gpu.global.b64 t, [%2];\nmov.b64 {%0, %1}, t;\n}" : "=r"(v.x), "=r"(v.y) : "l"(p) : "memory");
    return v;
}
__device__ __forceinline__ uint4 ld_nc16(const void* p) {
    uint4 v;
    asm volatile("ld.global.L1::no_allocate.v4.u32 {%0, %1, %2, %3}, [%4];" : "=r"(v.x), "=r"(v.y), "=r"(v.z), "=r"(v.w) : "l"(p) : "memory");
    return v;
}
__device__ __forceinline__ uint2 ld_nc8(const void* p) {
    uint2 v;
    asm volatile("ld.global.nc.L1::no_allocate.v2.u32 {%0, %1}, [%2];" : "=r"(v.x), "=r"(v.y) : "l"(p));
    return v;
}
__device__ __forceinline__ uint4 lds16(uint32_t a) {
    uint4 v;
    asm volatile("ld.shared.v4.u32 {%0, %1, %2, %3}, [%4];" : "=r"(v.x), "=r"(v.y), "=r"(v.z), "=r"(v.w) : "r"(a) : "memory");
    return v;
}
__device__ __forceinline__ void sts16(uint32_t a, uint32_t x, uint32_t y, uint32_t z, uint32_t w) {
    asm volatile("st.shared.v4.u32 [%0], {%1, %2, %3, %4};" ::"r"(a), "r"(x), "r"(y), "r"(z), "r"(w) : "memory");
}
__device__ __forceinline__ uint32_t pack2(float lo, float hi) {
    uint32_t r;
    asm("cvt.rn.bf16x2.f32 %0, %1, %2;" : "=r"(r) : "f"(hi), "f"(lo));
    return r;
}
__device__ __forceinline__ uint32_t pack2v(float lo, float hi) {
    uint32_t r;
    asm volatile("cvt.rn.bf16x2.f32 %0, %1, %2;" : "=r"(r) : "f"(hi), "f"(lo));
    return r;
}
__device__ __forceinline__ float bf_lo(uint32_t u) { return __uint_as_float(u << 16); }
__device__ __forceinline__ float bf_hi(uint32_t u) { return __uint_as_float(u & 0xFFFF0000u); }
__device__ __forceinline__ float bf_round(float f) { return __bfloat162float(__float2bfloat16_rn(f)); }
__device__ __forceinline__ uint32_t prmt(uint32_t a, uint32_t sel) {
    uint32_t d;
    asm("prmt.b32 %0, %1, 0, %2;" : "=r"(d) : "r"(a), "r"(sel));
    return d;
}
__device__ __forceinline__ uint32_t movm(uint32_t a) {
    uint32_t d;
    asm volatile("movmatrix.sync.aligned.m8n8.trans.b16 %0, %1;" : "=r"(d) : "r"(a));
    return d;
}
__device__ __forceinline__ void mma16(float (&c)[4], uint32_t a0, uint32_t a1, uint32_t a2, uint32_t a3, uint32_t b0, uint32_t b1) {
    asm volatile("mma.sync.aligned.m16n8k16.row.col.f32.bf16.bf16.f32 {%0,%1,%2,%3}, {%4,%5,%6,%7}, {%8,%9}, {%0,%1,%2,%3};"
                 : "+f"(c[0]), "+f"(c[1]), "+f"(c[2]), "+f"(c[3]) : "r"(a0), "r"(a1), "r"(a2), "r"(a3), "r"(b0), "r"(b1));
}
__device__ __forceinline__ void mma8(float (&c)[4], uint32_t a0, uint32_t a1, uint32_t b0) {
    asm volatile("mma.sync.aligned.m16n8k8.row.col.f32.bf16.bf16.f32 {%0,%1,%2,%3}, {%4,%5}, {%6}, {%0,%1,%2,%3};"
                 : "+f"(c[0]), "+f"(c[1]), "+f"(c[2]), "+f"(c[3]) : "r"(a0), "r"(a1), "r"(b0));
}
__device__ __forceinline__ float ex2(float x) { float y; asm("ex2.approx.ftz.f32 %0, %1;" : "=f"(y) : "f"(x)); return y; }
__device__ __forceinline__ float rcp(float x) { float y; asm("rcp.approx.ftz.f32 %0, %1;" : "=f"(y) : "f"(x)); return y; }
__device__ __forceinline__ float sigmoidf(float z) { return rcp(1.0f + ex2(z * -1.4426950408889634f)); }
__device__ __forceinline__ float u2f(uint32_t u) { return __uint_as_float(u); }
__device__ __forceinline__ uint32_t f2u(float f) { return __float_as_uint(f); }

__device__ __forceinline__ void wgmma_main(float (&d)[96], uint32_t a, uint32_t b, int scale_d) {
    asm volatile("{\n.reg .pred p;\n.reg .b64 da, db;\nsetp.ne.b32 p, %98, 0;\n"
        "mov.b64 da, {%96, 0x40000040};\nmov.b64 db, {%97, 0x40000040};\n"
        "wgmma.mma_async.sync.aligned.m64n192k16.f32.bf16.bf16 "
        "{%0, %1, %2, %3, %4, %5, %6, %7, %8, %9, %10, %11, %12, %13, %14, %15, "
        "%16, %17, %18, %19, %20, %21, %22, %23, %24, %25, %26, %27, %28, %29, %30, %31, "
        "%32, %33, %34, %35, %36, %37, %38, %39, %40, %41, %42, %43, %44, %45, %46, %47, "
        "%48, %49, %50, %51, %52, %53, %54, %55, %56, %57, %58, %59, %60, %61, %62, %63, "
        "%64, %65, %66, %67, %68, %69, %70, %71, %72, %73, %74, %75, %76, %77, %78, %79, "
        "%80, %81, %82, %83, %84, %85, %86, %87, %88, %89, %90, %91, %92, %93, %94, %95}, "
        "da, db, p, 1, 1, 0, 1;\n}\n"
        : "+f"(d[0]), "+f"(d[1]), "+f"(d[2]), "+f"(d[3]), "+f"(d[4]), "+f"(d[5]), "+f"(d[6]), "+f"(d[7]),
          "+f"(d[8]), "+f"(d[9]), "+f"(d[10]), "+f"(d[11]), "+f"(d[12]), "+f"(d[13]), "+f"(d[14]), "+f"(d[15]),
          "+f"(d[16]), "+f"(d[17]), "+f"(d[18]), "+f"(d[19]), "+f"(d[20]), "+f"(d[21]), "+f"(d[22]), "+f"(d[23]),
          "+f"(d[24]), "+f"(d[25]), "+f"(d[26]), "+f"(d[27]), "+f"(d[28]), "+f"(d[29]), "+f"(d[30]), "+f"(d[31]),
          "+f"(d[32]), "+f"(d[33]), "+f"(d[34]), "+f"(d[35]), "+f"(d[36]), "+f"(d[37]), "+f"(d[38]), "+f"(d[39]),
          "+f"(d[40]), "+f"(d[41]), "+f"(d[42]), "+f"(d[43]), "+f"(d[44]), "+f"(d[45]), "+f"(d[46]), "+f"(d[47]),
          "+f"(d[48]), "+f"(d[49]), "+f"(d[50]), "+f"(d[51]), "+f"(d[52]), "+f"(d[53]), "+f"(d[54]), "+f"(d[55]),
          "+f"(d[56]), "+f"(d[57]), "+f"(d[58]), "+f"(d[59]), "+f"(d[60]), "+f"(d[61]), "+f"(d[62]), "+f"(d[63]),
          "+f"(d[64]), "+f"(d[65]), "+f"(d[66]), "+f"(d[67]), "+f"(d[68]), "+f"(d[69]), "+f"(d[70]), "+f"(d[71]),
          "+f"(d[72]), "+f"(d[73]), "+f"(d[74]), "+f"(d[75]), "+f"(d[76]), "+f"(d[77]), "+f"(d[78]), "+f"(d[79]),
          "+f"(d[80]), "+f"(d[81]), "+f"(d[82]), "+f"(d[83]), "+f"(d[84]), "+f"(d[85]), "+f"(d[86]), "+f"(d[87]),
          "+f"(d[88]), "+f"(d[89]), "+f"(d[90]), "+f"(d[91]), "+f"(d[92]), "+f"(d[93]), "+f"(d[94]), "+f"(d[95])
        : "r"(a), "r"(b), "r"(scale_d));
}

__device__ __forceinline__ void wgmma_rem(float (&d)[24], uint32_t a, uint32_t b, int scale_d) {
    asm volatile("{\n.reg .pred p;\n.reg .b64 da, db;\nsetp.ne.b32 p, %26, 0;\n"
        "mov.b64 da, {%24, 0x40000040};\nmov.b64 db, {%25, 0xC0000010};\n"
        "wgmma.mma_async.sync.aligned.m64n48k16.f32.bf16.bf16 "
        "{%0, %1, %2, %3, %4, %5, %6, %7, %8, %9, %10, %11, %12, %13, %14, %15, "
        "%16, %17, %18, %19, %20, %21, %22, %23}, "
        "da, db, p, 1, 1, 0, 1;\n}\n"
        : "+f"(d[0]), "+f"(d[1]), "+f"(d[2]), "+f"(d[3]), "+f"(d[4]), "+f"(d[5]), "+f"(d[6]), "+f"(d[7]),
          "+f"(d[8]), "+f"(d[9]), "+f"(d[10]), "+f"(d[11]), "+f"(d[12]), "+f"(d[13]), "+f"(d[14]), "+f"(d[15]),
          "+f"(d[16]), "+f"(d[17]), "+f"(d[18]), "+f"(d[19]), "+f"(d[20]), "+f"(d[21]), "+f"(d[22]), "+f"(d[23])
        : "r"(a), "r"(b), "r"(scale_d));
}

__device__ __forceinline__ void wgmma_out(float (&d)[80], uint32_t a, uint32_t b, int scale_d) {
    asm volatile("{\n.reg .pred p;\n.reg .b64 da, db;\nsetp.ne.b32 p, %82, 0;\n"
        "mov.b64 da, {%80, 0x50};\nmov.b64 db, {%81, 0x40000040};\n"
        "wgmma.mma_async.sync.aligned.m64n160k16.f32.bf16.bf16 "
        "{%0, %1, %2, %3, %4, %5, %6, %7, %8, %9, %10, %11, %12, %13, %14, %15, "
        "%16, %17, %18, %19, %20, %21, %22, %23, %24, %25, %26, %27, %28, %29, %30, %31, "
        "%32, %33, %34, %35, %36, %37, %38, %39, %40, %41, %42, %43, %44, %45, %46, %47, "
        "%48, %49, %50, %51, %52, %53, %54, %55, %56, %57, %58, %59, %60, %61, %62, %63, "
        "%64, %65, %66, %67, %68, %69, %70, %71, %72, %73, %74, %75, %76, %77, %78, %79}, "
        "da, db, p, 1, 1, 0, 1;\n}\n"
        : "+f"(d[0]), "+f"(d[1]), "+f"(d[2]), "+f"(d[3]), "+f"(d[4]), "+f"(d[5]), "+f"(d[6]), "+f"(d[7]),
          "+f"(d[8]), "+f"(d[9]), "+f"(d[10]), "+f"(d[11]), "+f"(d[12]), "+f"(d[13]), "+f"(d[14]), "+f"(d[15]),
          "+f"(d[16]), "+f"(d[17]), "+f"(d[18]), "+f"(d[19]), "+f"(d[20]), "+f"(d[21]), "+f"(d[22]), "+f"(d[23]),
          "+f"(d[24]), "+f"(d[25]), "+f"(d[26]), "+f"(d[27]), "+f"(d[28]), "+f"(d[29]), "+f"(d[30]), "+f"(d[31]),
          "+f"(d[32]), "+f"(d[33]), "+f"(d[34]), "+f"(d[35]), "+f"(d[36]), "+f"(d[37]), "+f"(d[38]), "+f"(d[39]),
          "+f"(d[40]), "+f"(d[41]), "+f"(d[42]), "+f"(d[43]), "+f"(d[44]), "+f"(d[45]), "+f"(d[46]), "+f"(d[47]),
          "+f"(d[48]), "+f"(d[49]), "+f"(d[50]), "+f"(d[51]), "+f"(d[52]), "+f"(d[53]), "+f"(d[54]), "+f"(d[55]),
          "+f"(d[56]), "+f"(d[57]), "+f"(d[58]), "+f"(d[59]), "+f"(d[60]), "+f"(d[61]), "+f"(d[62]), "+f"(d[63]),
          "+f"(d[64]), "+f"(d[65]), "+f"(d[66]), "+f"(d[67]), "+f"(d[68]), "+f"(d[69]), "+f"(d[70]), "+f"(d[71]),
          "+f"(d[72]), "+f"(d[73]), "+f"(d[74]), "+f"(d[75]), "+f"(d[76]), "+f"(d[77]), "+f"(d[78]), "+f"(d[79])
        : "r"(a), "r"(b), "r"(scale_d));
}

__device__ __forceinline__ void wgmma_own(float (&d)[80], uint32_t a0, uint32_t a1, uint32_t a2, uint32_t a3, uint32_t b, int scale_d) {
    asm volatile("{\n.reg .pred p;\n.reg .b64 db;\nsetp.ne.b32 p, %85, 0;\nmov.b64 db, {%84, 0x40000040};\n"
        "wgmma.mma_async.sync.aligned.m64n160k16.f32.bf16.bf16 "
        "{%0, %1, %2, %3, %4, %5, %6, %7, %8, %9, %10, %11, %12, %13, %14, %15, "
        "%16, %17, %18, %19, %20, %21, %22, %23, %24, %25, %26, %27, %28, %29, %30, %31, "
        "%32, %33, %34, %35, %36, %37, %38, %39, %40, %41, %42, %43, %44, %45, %46, %47, "
        "%48, %49, %50, %51, %52, %53, %54, %55, %56, %57, %58, %59, %60, %61, %62, %63, "
        "%64, %65, %66, %67, %68, %69, %70, %71, %72, %73, %74, %75, %76, %77, %78, %79}, "
        "{%80, %81, %82, %83}, db, p, 1, 1, 1;\n}\n"
        : "+f"(d[0]), "+f"(d[1]), "+f"(d[2]), "+f"(d[3]), "+f"(d[4]), "+f"(d[5]), "+f"(d[6]), "+f"(d[7]),
          "+f"(d[8]), "+f"(d[9]), "+f"(d[10]), "+f"(d[11]), "+f"(d[12]), "+f"(d[13]), "+f"(d[14]), "+f"(d[15]),
          "+f"(d[16]), "+f"(d[17]), "+f"(d[18]), "+f"(d[19]), "+f"(d[20]), "+f"(d[21]), "+f"(d[22]), "+f"(d[23]),
          "+f"(d[24]), "+f"(d[25]), "+f"(d[26]), "+f"(d[27]), "+f"(d[28]), "+f"(d[29]), "+f"(d[30]), "+f"(d[31]),
          "+f"(d[32]), "+f"(d[33]), "+f"(d[34]), "+f"(d[35]), "+f"(d[36]), "+f"(d[37]), "+f"(d[38]), "+f"(d[39]),
          "+f"(d[40]), "+f"(d[41]), "+f"(d[42]), "+f"(d[43]), "+f"(d[44]), "+f"(d[45]), "+f"(d[46]), "+f"(d[47]),
          "+f"(d[48]), "+f"(d[49]), "+f"(d[50]), "+f"(d[51]), "+f"(d[52]), "+f"(d[53]), "+f"(d[54]), "+f"(d[55]),
          "+f"(d[56]), "+f"(d[57]), "+f"(d[58]), "+f"(d[59]), "+f"(d[60]), "+f"(d[61]), "+f"(d[62]), "+f"(d[63]),
          "+f"(d[64]), "+f"(d[65]), "+f"(d[66]), "+f"(d[67]), "+f"(d[68]), "+f"(d[69]), "+f"(d[70]), "+f"(d[71]),
          "+f"(d[72]), "+f"(d[73]), "+f"(d[74]), "+f"(d[75]), "+f"(d[76]), "+f"(d[77]), "+f"(d[78]), "+f"(d[79])
        : "r"(a0), "r"(a1), "r"(a2), "r"(a3), "r"(b), "r"(scale_d));
}

__device__ __forceinline__ void wgmma_vec(float (&d)[8], uint32_t a, uint32_t b, int scale_d) {
    asm volatile("{\n.reg .pred p;\n.reg .b64 da, db;\nsetp.ne.b32 p, %10, 0;\n"
        "mov.b64 da, {%8, 0x40000040};\nmov.b64 db, {%9, 0x14};\n"
        "wgmma.mma_async.sync.aligned.m64n16k16.f32.bf16.bf16 {%0, %1, %2, %3, %4, %5, %6, %7}, da, db, p, 1, 1, 1, 0;\n}\n"
        : "+f"(d[0]), "+f"(d[1]), "+f"(d[2]), "+f"(d[3]), "+f"(d[4]), "+f"(d[5]), "+f"(d[6]), "+f"(d[7])
        : "r"(a), "r"(b), "r"(scale_d));
}

#define TSA(i) do { } while (0)
#define MAP_TILE(b) ((((b) >> 1) & 14) | ((b) & 1))
#define MAP_HG(b) (((b) >> 4 & 14) | ((b) >> 1 & 1))
#define SRCV 3
#define L1_D 300
#define L0_D 300
#define F1_D 0
#define F0_D 200
#define HALFV 0
#define HALF (int)(HALFV == 0 ? bid >> 1 & 1 : HALFV == 1 ? (bid >> 1 ^ bid) & 1 : (bid >> 1 ^ bid >> 4) & 1)
#define GM 0x78A0
#define H_C 1000
#define PV 0
#define BX 0
#define SETL 0
#define L0_T 14350
#define L1_T (L0_T - 300)
#define F0_T 14550
#define F1_T 14300
#define C5_T 0
#define C6_T (C5_T + 450)
#define C7_T (C6_T + 400)
#define C_O 250
#define FFV 2
#define DFV 0
#define OEV 1
#define B_OFF 0
#define W_S0 2
#define E_V 0
#define MAPV 4
#define GW 0
#define GU_DS (GU_DT * 7 / 11)
#define GU_ST 90
#define X_OFF 350
#define RW_REG 0
#define P2W 4
#define RES_V 2
#define Y2_T 17000
#define ENT_V 0
#define TPF 1
#define SKEW 4
#define PACE 500
#define PACE_W0 (-600)
#define PACE_A 250
#define PACE_B 450
#define RG_ORDER 0x24130
#define GU_T0 3600
#define GU_DT 750
#define RS_T0 9000
#define RS_DT 120
#define EXCH_FIRST 1
#define HALO_D 450
#define PF_UP 4200
#define O_D 0
#define O_DT 300
#define PF_DN 4200
#define PF_DT 450
#define GX_NS 200
#define NRS 1
#define C5_D 0
#define C6_D 100
#define PF_N 4
#define PF_0 4
#define EPF_N 15
#define EPF_M 15
#define EPF_T 900
#define RG1_T0 1700
#define RG1_DT 200
#define RW1_T 0
#define Y_T 15500
#define GL_T 0
#define DN_T0 500
#define DN_DT 68
#define DN_T1 100000
#define DN_D1 45
#define DN_R 5
#define H_T 13400
#define HS_T 13500
#define GL_N 16
#define C1_T 0
#define C0_T 11100
#define RS_N 10
#define SP_W 1
#define PF2_N 0
#define C2_T 0
#define C3_T 0
#define C4_T 0
#define EPF_G 0
#define EPF_H 0
#define UPF 0
#define UPF_D 700
#define UPF_T 3200
#define UPF_S 90
#define RS_E 0
#define RS_D 0
#define GL15 1
#define RS_S 0
#define CAND_T 9000

__device__ __forceinline__ uint32_t keep(uint32_t v) { return __shfl_xor_sync(0xffffffffu, v, 0); }
__device__ __forceinline__ uint32_t ukeep(uint32_t v) { return __shfl_sync(0xffffffffu, v, 0); }
__device__ __forceinline__ void ldsm2(uint32_t* d, uint32_t a) {
    asm volatile("ldmatrix.sync.aligned.m8n8.x4.shared.b16 {%0,%1,%2,%3}, [%8];\nldmatrix.sync.aligned.m8n8.x4.shared.b16 {%4,%5,%6,%7}, [%9];"
                 : "=r"(d[0]), "=r"(d[1]), "=r"(d[2]), "=r"(d[3]), "=r"(d[4]), "=r"(d[5]), "=r"(d[6]), "=r"(d[7])
                 : "r"(a), "r"(a ^ 32) : "memory");
}
__device__ __forceinline__ void ldsm_t(uint32_t (&d)[4], uint32_t a) {
    asm volatile("ldmatrix.sync.aligned.m8n8.x4.trans.shared.b16 {%0,%1,%2,%3}, [%4];"
                 : "=r"(d[0]), "=r"(d[1]), "=r"(d[2]), "=r"(d[3]) : "r"(a) : "memory");
}
template <bool SWP, int SEG, int E>
__device__ __forceinline__ void pack_blocks(uint32_t (&d)[10], const float (&am)[96], const float (&ar)[24]) {
#pragma unroll
    for (int t = 0; t < 10; t++) {
        const float* p = (SWP ? t < 2 : t >= 8) ? ar + (SEG * 2 + (t & 1)) * 4 + E : am + (SEG * 8 + t - (SWP ? 2 : 0)) * 4 + E;
        d[t] = pack2v(p[0], p[1]);
    }
}
__device__ __forceinline__ int src_of(int i, int hg) { return i == 0 ? hg : i > 3 ? 2 * i - 7 - (hg & 1) : 2 * (i - (i <= (hg >> 1))) + (hg & 1); }

__device__ __forceinline__ uint32_t o_buf(int i) { return __byte_perm(0xD199ADA3u, 0xC7BDu, i - 1 - NRS | 0x7770) << 10; }
__device__ constexpr uint32_t wo_buf(int i) { return SM_W + ((0x10342103u >> i * 4) & 7) * 30720; }

template <int N>
__device__ __forceinline__ void poll(uint4 (&a)[N], const uint4* p, int stride) {
    bool bad;
    do {
        bad = false;
#pragma unroll
        for (int s = 0; s < N; s++) a[s] = ld_relaxed16(p + s * stride);
#pragma unroll
        for (int s = 0; s < N; s++) bad |= a[s].w == SENT;
    } while (__any_sync(0xffffffffu, bad));
}
__device__ __forceinline__ void pace(unsigned t0, int t) {
    asm volatile("{\n.reg .pred p;\n.reg .s32 d;\nAGAIN:\nmov.u32 d, %%clock;\nsub.s32 d, d, %0;\nsetp.lt.s32 p, d, 0;\n"
                 "@p nanosleep.u32 20;\n@p bra AGAIN;\n}" ::"r"(t0 + t) : "memory");
}
__device__ __forceinline__ void l2_prefetch(const void* p) { asm volatile("prefetch.global.L2 [%0];" ::"l"(p) : "memory"); }

template <int N>
__device__ __forceinline__ bool landed(const uint4* w, int lane) {
    uint32_t a = 0;
#pragma unroll
    for (int i = 0; i < N; i++) a ^= w[i].w;
    return __ballot_sync(0xffffffffu, lane == 0 || a == 0) && lane == 0;
}
__device__ __forceinline__ void swiglu(const uint4 (&a)[4], uint32_t dst, uint32_t stride) {
    const float g0 = bf_round((u2f(a[0].x) + u2f(a[1].x)) + (u2f(a[2].x) + u2f(a[3].x)));
    const float g1 = bf_round((u2f(a[0].y) + u2f(a[1].y)) + (u2f(a[2].y) + u2f(a[3].y)));
    const float u0 = bf_round((u2f(a[0].z) + u2f(a[1].z)) + (u2f(a[2].z) + u2f(a[3].z)));
    const float u1 = bf_round((u2f(a[0].w) + u2f(a[1].w)) + (u2f(a[2].w) + u2f(a[3].w)));
    const uint32_t h = pack2(bf_round(g0 * sigmoidf(g0)) * u0, bf_round(g1 * sigmoidf(g1)) * u1);
    asm volatile("st.shared.u16 [%0], %2;\nst.shared.u16 [%1], %3;" ::"r"(dst), "r"(dst + stride), "h"((uint16_t)h), "h"((uint16_t)(h >> 16)) : "memory");
}
template <int N>
__device__ __forceinline__ float4 vec_mma(const uint4 (&w)[N], const uint32_t* x, uint32_t sel) {
    float c[4][4] = {};
    const uint32_t s[4] = {sel, sel >> 16, sel + ((sel & 0x10101010u) >> 3) * 17, (sel + ((sel & 0x10101010u) >> 3) * 17) >> 16};
#pragma unroll
    for (int i = 0; i < N; i++)
        mma16(c[i & 3], w[i].x, w[i].y, w[i].z, w[i].w, prmt(x[i >> 1], s[(i & 1) * 2]), prmt(x[i >> 1], s[(i & 1) * 2 + 1]));
    return make_float4((c[0][0] + c[1][0]) + (c[2][0] + c[3][0]), (c[0][1] + c[1][1]) + (c[2][1] + c[3][1]),
                       (c[0][2] + c[1][2]) + (c[2][2] + c[3][2]), (c[0][3] + c[1][3]) + (c[2][3] + c[3][3]));
}

__global__ void __launch_bounds__(512, 1) fused_kernel(const __grid_constant__ Params P) {
    extern __shared__ __align__(1024) uint8_t smem_raw[];
    const unsigned t_start = clock();
    const int tid = threadIdx.x, lane = tid & 31;
    unsigned sm, bid;
    asm("mov.u32 %0, %%smid;" : "=r"(sm));
    const CUtensorMap* mx = &P.x;
    asm volatile("" : "+l"(mx));
    if ((unsigned)(tid - 480) < EPF_N) l2_prefetch(P.wp + (tid * 132 + sm) * 64 - 480 * 132 * 64);
    const int warp = __shfl_sync(0xffffffffu, threadIdx.x >> 5, 0);
    constexpr uint32_t rk = 0;
    asm("{\n.reg .pred p;\n.reg .b32 t, u;\nshr.u32 t, %1, 1;\nmad.lo.s32 u, t, 14, -928;\nmad.lo.s32 t, t, 37, -925;\nmax.s32 t, t, 0;\n"
        "shr.u32 t, t, 7;\nand.b32 t, t, 14;\nsetp.ge.u32 p, %1, 124;\nselp.b32 t, u, t, p;\nadd.s32 %0, %1, t;\n}" : "=r"(bid) : "r"(sm));
    bid ^= (GM >> (bid & 14) & 6) ^ BX;
    const int hg = MAP_HG(bid), par = bid & 1, p0 = (MAP_TILE(bid) >> 1) * 128;
    const bool swp = (hg & 3) == 3;
    const int wcm = hg * 80 + (swp ? 16 : 0), wcr = hg * 80 + (swp ? 0 : 64);
    if (warp == 0) {
        if (elect_one()) {
#pragma unroll
            for (int i = 0; i < 4; i++) mbar_init(SM_BAR + i * 8, 1);
            asm volatile("fence.mbarrier_init.release.cluster;" ::: "memory");
            if (bid < NCTA) {
                mbar_expect_tx(B_FULL, 15360 + 8192);
                tma_3d(SM_X + 8192, mx, B_FULL, 0, par, p0 + 64);
                tma_3d(SM_W, mx + 2, B_FULL, wcm, 0, 0);
                tma_3d(SM_W + 12288, mx + 3, B_FULL, wcr, 0, 0);
                TS(40);
                mbar_expect_tx(B_XL0, 8192);
                tma_3d(SM_X, mx, B_XL0, 0, par, p0);
                mbar_expect_tx(B_FULL + 8, 15360);
                tma_3d(SM_W + 15360, mx + 2, B_FULL + 8, wcm, 32, 0);
                tma_3d(SM_W + 15360 + 12288, mx + 3, B_FULL + 8, wcr, 32, 0);
            }
        }
    }
    if ((unsigned)(warp - 1) < 6 && elect_one()) {
#pragma unroll
        for (int i = 0; i < 4; i++) mbar_init(SM_BAR + warp * 32 + i * 8, warp < 4 ? 1 : warp < 6 ? 2 : 4);
        asm volatile("fence.mbarrier_init.release.cluster;" ::: "memory");
    }
    asm volatile("" : "+r"(bid));
    const int role = bid >= NCTA ? -1 : warp, e = sm & 3;
    const int tile = MAP_TILE(bid), cid = tile * 8 + hg;
    uint4* const sc = g_sc + cid * SC_SIZE;
    __syncthreads();

    if (role < 0) {
        const int half = warp >> 3;
        if (!NFFN) {
            if (tid == 0) red_inc<NCTA / NEXTRA>(g_cnt, 0);
            return;
        }
        uint32_t wf[DN_R][5][4], la[5];
        auto rows = [&](uint32_t l) {
#pragma unroll
            for (int i = 0; i < 5; i++) {
                const uint32_t c = (warp & 7) * 10 + 2 * i + (l >> 3 & 1);
                la[i] = SB + half * 20480 + (c >> 3) * 2048 + (l & 7) * 128 + (l >> 4) * 1024 + (((c ^ l) & 7) << 4);
            }
        };
        rows(lane);
        auto fetch = [&](int j, int n, uint32_t bar) {
#pragma unroll 1
            for (int h = 0; h < n; h++) {
                pace(t_start, min(DN_T0 + (j * 20 + h * 10 + warp) * DN_DT, DN_T1 + (j * 20 + h * 10 + warp) * DN_D1));
                tma_2d(SB + (j % 5) * 40960 + h * 20480 + warp * 2048, &P.down, bar, warp * 64, e * 272 + (j + h * 9) * 16);
            }
        };
        if (warp < 10 && elect_one()) {
            if (warp <= DN_R) mbar_expect_tx(B_FULL + warp * 8, warp < DN_R ? 40960 : (17 - 2 * DN_R) * 20480);
#pragma unroll 1
            for (int j = 0; j < 5; j++) fetch(j, 2, B_FULL + j * 8);
        }
        const uint32_t tag = (ukeep(ld_relaxed4(g_cnt)) * 8 + 2048) & 0xF800u;
#pragma unroll
        for (int j = 0; j < DN_R; j++) {
            uint32_t any = 0;
            mbar_wait(B_FULL + j * 8, 0);
#pragma unroll
            for (int i = 0; i < 5; i++) {
                ldsm_t(wf[j][i], la[i] + j * 40960);
                any ^= wf[j][i][3];
            }
            if (j < 4) {
                if (__syncthreads_count(any == 0) == 1000) fault();
                if (warp < 10 && elect_one()) fetch(j + 5, j < 3 ? 2 : 1, B_FULL + DN_R * 8);
                if (j == 0 && tid == 0) red_inc<NCTA / NEXTRA>(g_cnt, tag);
            }
            TSX(warp == 0 && j == 0 ? 0 : warp == 0 && j == 3 ? 1 : 63);
        }
        if (warp < 9) {
            pace(t_start, H_T - H_C);
            uint4 a[4];
            do {
                a[0] = ld_relaxed16(g_cand + lane * 2);
                a[1] = ld_relaxed16(g_cand + lane * 2 + 64);
            } while (__any_sync(0xffffffffu, ((a[0].x ^ tag) | (a[0].z ^ tag) | (a[1].x ^ tag) | (a[1].z ^ tag)) & 0xF800u));
            const int u = min(tid, 271), f = e * 272 + u;
            pace(t_start, H_T);
            TSX(warp == 0 ? 3 : 63);
            poll<4>(a, g_sc + (f >> 6) * 4 * SC_SIZE + SC_GU + (f & 63), SC_SIZE);
            TSX(warp == 0 ? 4 : warp == 8 ? 5 : 63);
            swiglu(a, SM_RED + (u >> 4) * 64 + (u & 6) * 4 + (u & 8) / 2 + (u & 1) * 2, 32);
        }
        rows(keep(lane));
        mbar_wait(B_FULL + DN_R * 8, 0);
        TSX(warp == 15 ? 2 : 63);
        __syncthreads();
        float c[5][4] = {};
#pragma unroll
        for (int j = 0; j < 9; j++) {
            if (j == 8 && half) break;
            const float2 b = lds8f(SM_RED + half * 576 + j * 64 + (lane & 7) * 8);
            if (j == 1) TSX(warp == 0 ? 6 : 63);
#pragma unroll
            for (int i = 0; i < 5; i++) {
                if (j >= DN_R) ldsm_t(wf[j % DN_R][i], la[i] + (j % 5) * 40960);
                mma16(c[i], wf[j % DN_R][i][0], wf[j % DN_R][i][1], wf[j % DN_R][i][2], wf[j % DN_R][i][3], f2u(b.x), f2u(b.y));
            }
        }
        const uint32_t ra = SB + 7 * 20480 + half * 5248 + (lane & 1) * 2624 + (warp & 7) * 320 + (lane & 2) * 16 + (lane >> 2) * 4;
#pragma unroll
        for (int i = 0; i < 5; i++) sts4(ra + i * 64, f2u((lane & 2) ? ((lane & 1) ? c[i][3] : c[i][2]) : ((lane & 1) ? c[i][1] : c[i][0])));
        TSX(warp == 0 ? 7 : 63);
        __syncthreads();
        if (warp < 10) {
            const uint32_t ya = SB + 7 * 20480 + (warp & 1) * 2624 + (warp >> 1) * 512 + lane * 16;
            const uint4 y0 = lds16(ya), y1 = lds16(ya + 5248);
            st_relaxed16(g_sc + (e * 5 + (warp >> 1)) * SC_SIZE + SC_Y + (tid & 63), f2u(u2f(y0.x) + u2f(y1.x)), f2u(u2f(y0.y) + u2f(y1.y)),
                         f2u(u2f(y0.z) + u2f(y1.z)), f2u(u2f(y0.w) + u2f(y1.w)));
        }
    } else if (role < 8) {
        asm volatile("setmaxnreg.inc.sync.aligned.u32 192;");
        const int wg = warp >> 2;
        const bool leader = (tid & 127) == 0;
        float am[96], ar[24];
        if (wg == 0) mbar_wait(B_XL0, 0);
        bool rel = false;
        uint32_t nb[40];
        const int odd = (hg >> 1) & 1, kba = ukeep(RES_V && wg != HALF ? 99 : ((hg >> 1) * 5 + 1) >> 1), kbr = ukeep(kba + 2 - odd * 3);
        const int kbs = wg ? -1 : (20 - SKEW) / 2;
        const uint32_t xrow = keep(SM_X + (warp * 16 + (lane & 15)) * 128 + (((lane >> 4) ^ (lane & 7)) << 4));
#pragma unroll 1
        for (int kb = 0; kb < 10; kb++) {
            const uint32_t fb = B_FULL + (kb & 3) * 16, wo = (kb & 3) * 1920, ph = (kb >> 2) & 1;
            const uint32_t xo = desc_lo(SM_X, 16) + wg * 512 + (kb & 3) * 1024;
#pragma unroll
            for (int h = 0; h < 2; h++) {
                mbar_wait(fb + h * 8, ph);
                if (kb == 0 && h == 0) TS(warp == 0 ? 0 : warp == 4 ? 16 : 63);
                TS2(warp == P2W ? kb * 2 + h : 63);
                if (RES_V == 2) {
                    const uint32_t xa = (xrow ^ h * 64) + (kb & 3) * 16384;
                    if (kb == kba) ldsm2(nb + h * 8, xa);
                    if (kb == kba + 1) ldsm2(nb + 16 + h * 8, xa);
                    if (h == 0 && kb == kbr) ldsm2(nb + 32, xa ^ (odd * 64));
                } else if (h == 0) {
                    const uint32_t xa = xrow + (kb & 3) * 16384;
                    if (kb == kba) { ldsm2(nb, xa); ldsm2(nb + 8, xa ^ 64); }
                    if (kb == kba + 1) { ldsm2(nb + 16, xa); ldsm2(nb + 24, xa ^ 64); }
                    if (kb == kbr) ldsm2(nb + 32, xa ^ (odd * 64));
                }
                wg_wait<1>();
                if (rel && (h == 0 || kb != kbs)) mbar_arrive(B_EMPTY + ((kb * 16 - 16) & 48) + h * 8);
                if (h == 0 && kb == kbs) {
                    wg_wait<0>();
                    if (rel) mbar_arrive(B_EMPTY + ((19 - SKEW) & 7) * 8);
                    bar_sync(5, 256);
                }
                wg_fence();
                wgmma_main(am, xo + h * 4, desc_lo(SM_W + h * 15360, 4096) + wo, h || kb);
                wgmma_rem(ar, xo + h * 4, desc_lo(SM_W + h * 15360 + 12288, 1024) + wo, h || kb);
                wgmma_main(am, xo + h * 4 + 2, desc_lo(SM_W + h * 15360 + 2048, 4096) + wo, 1);
                wgmma_rem(ar, xo + h * 4 + 2, desc_lo(SM_W + h * 15360 + 12288 + 512, 1024) + wo, 1);
                wg_commit();
            }
            rel = leader;
        }
        if (wg == 1) bar_arrive(5, 256);
        mbar_wait(B_XE + 16, 0);
        mbar_wait(B_RG2, 0);
        mbar_wait(B_EMPTY + 5 * 8, 1);
        wg_wait<0>();
        if (leader) mbar_arrive(B_EMPTY + 3 * 8);
        TS(warp == 0 ? 2 : warp == 4 ? 18 : 63);
        TS2(warp == 0 ? 41 : warp == 4 ? 40 : 63);

        uint32_t kl[10], kh[10], vl[10], vh[10], ql[10], qh[10], kp[10], vp[10];
        if (swp) {
            pack_blocks<true, 1, 2>(kh, am, ar);
            pack_blocks<true, 2, 2>(vh, am, ar);
        } else {
            pack_blocks<false, 1, 2>(kh, am, ar);
            pack_blocks<false, 2, 2>(vh, am, ar);
        }
        const int w4 = warp & 3;
        const uint32_t pbuf = (wg ? SM_HALO1 : SM_HALO) + w4 * 2560 + lane * 16;
        const uint32_t hbuf = warp == 3 ? SM_HALO1 + lane * 16 : pbuf + 2560;
        {
            const uint32_t ex[20] = {kh[0], kh[1], kh[3], kh[4], kh[5], kh[6], kh[8], kh[9], kh[2], kh[7],
                                     vh[0], vh[1], vh[2], vh[3], vh[4], vh[5], vh[6], vh[7], vh[8], vh[9]};
            if (warp == 7) {
                uint4* const hp = sc + SC_HALO + lane;
#pragma unroll
                for (int s = 0; s < 5; s++) st_relaxed16(hp + s * 32, ex[4 * s], ex[4 * s + 1], ex[4 * s + 2], ex[4 * s + 3]);
                bar_arrive(12, 64);
            } else {
#pragma unroll
                for (int s = 0; s < 5; s++) sts16(hbuf + s * 512, ex[4 * s], ex[4 * s + 1], ex[4 * s + 2], ex[4 * s + 3]);
            }
        }
        TS(warp == 7 ? 22 : warp == 3 ? 23 : 63);
        if (warp == 3) bar_arrive(11, 64);
        if (swp) {
            pack_blocks<true, 2, 0>(vl, am, ar);
            pack_blocks<true, 0, 0>(ql, am, ar);
            pack_blocks<true, 0, 2>(qh, am, ar);
            pack_blocks<true, 1, 0>(kl, am, ar);
        } else {
            pack_blocks<false, 2, 0>(vl, am, ar);
            pack_blocks<false, 0, 0>(ql, am, ar);
            pack_blocks<false, 0, 2>(qh, am, ar);
            pack_blocks<false, 1, 0>(kl, am, ar);
        }
#pragma unroll
        for (int t = 0; t < 10; t++) { vl[t] = movm(vl[t]); vh[t] = movm(vh[t]); }
        mbar_wait(B_RS, 0);
        mbar_wait(B_GT, 0);
        const float g0 = bf_hi(lds4(SM_GATE + warp * 64 + (lane & 28))), g1 = bf_hi(lds4(SM_GATE + 32 + warp * 64 + (lane & 28)));

        const int r = lane >> 2, cq = lane & 3;
        const bool no_prev = warp == 0 && tile < 2, low = cq < 2;
        const bool le0 = 2 * cq <= r, le1 = 2 * cq + 1 <= r;
        const uint32_t mle = (le0 ? 0xFFFFu : 0u) | (le1 ? 0xFFFF0000u : 0u);
        const float scl = 0.22360679774997896f * 1.4426950408889634f;
        uint32_t pl[4], ph[4];
        {
            float sl[4][4], sh[4][4], sp[4][4];
            auto exchange = [&]() {
            TSA(warp == 1 ? 26 : 63);
            bar_sync(6 + wg, 128);
            if (w4 == 0) bar_sync(8 + wg * 3, 64);
            {
                const uint4 a = lds16(pbuf), b = lds16(pbuf + 512), c = lds16(pbuf + 1024), d = lds16(pbuf + 1536), e = lds16(pbuf + 2048);
                kp[0] = a.x; kp[1] = a.y; kp[3] = a.z; kp[4] = a.w; kp[5] = b.x; kp[6] = b.y; kp[8] = b.z; kp[9] = b.w;
                kp[2] = c.x; kp[7] = c.y; vp[0] = c.z; vp[1] = c.w; vp[2] = d.x; vp[3] = d.y; vp[4] = d.z; vp[5] = d.w;
                vp[6] = e.x; vp[7] = e.y; vp[8] = e.z; vp[9] = e.w;
            }
            TSA(warp == 0 ? 3 : warp == 4 ? 19 : warp == 5 ? 27 : 63);
            };
            if (EXCH_FIRST) exchange();
#pragma unroll
            for (int h = 0; h < 4; h++) {
                const int ta = (h >> 1) * 5 + (h & 1) * 3, tc = (h >> 1) * 5 + 2;
                const uint32_t ml = low != (h & 1) ? ql[tc] : 0u, mh = low != (h & 1) ? qh[tc] : 0u;
#pragma unroll
                for (int e = 0; e < 4; e++) sl[h][e] = sh[h][e] = sp[h][e] = 0.f;
                mma16(sl[h], ql[ta], qh[ta], ql[ta + 1], qh[ta + 1], kl[ta], kl[ta + 1]);
                mma16(sh[h], ql[ta], qh[ta], ql[ta + 1], qh[ta + 1], kh[ta], kh[ta + 1]);
                mma8(sl[h], ml, mh, kl[tc]);
                mma8(sh[h], ml, mh, kh[tc]);
            }
            if (!EXCH_FIRST) exchange();
#pragma unroll
            for (int h = 0; h < 4; h++) {
                const int ta = (h >> 1) * 5 + (h & 1) * 3, tc = (h >> 1) * 5 + 2;
                mma16(sp[h], ql[ta], qh[ta], ql[ta + 1], qh[ta + 1], kp[ta], kp[ta + 1]);
                mma8(sp[h], low != (h & 1) ? ql[tc] : 0u, low != (h & 1) ? qh[tc] : 0u, kp[tc]);
            }
#pragma unroll
            for (int t = 0; t < 10; t++) vp[t] = movm(vp[t]);
#pragma unroll
            for (int h = 0; h < 4; h++) {
                if (no_prev) sp[h][0] = sp[h][1] = -1e9f / 0.22360679774997896f;
                const float a0 = le0 ? sl[h][0] : sp[h][0], a1 = le1 ? sl[h][1] : sp[h][1];
                const float b0 = le0 ? sh[h][2] : sl[h][2], b1 = le1 ? sh[h][3] : sl[h][3];
                float ma = fmaxf(a0, a1), mb = fmaxf(b0, b1);
                ma = fmaxf(ma, __shfl_xor_sync(0xffffffffu, ma, 1));
                mb = fmaxf(mb, __shfl_xor_sync(0xffffffffu, mb, 1));
                ma = fmaxf(ma, __shfl_xor_sync(0xffffffffu, ma, 2)) * -scl;
                mb = fmaxf(mb, __shfl_xor_sync(0xffffffffu, mb, 2)) * -scl;
                pl[h] = pack2(ex2(fmaf(a0, scl, ma)), ex2(fmaf(a1, scl, ma)));
                ph[h] = pack2(ex2(fmaf(b0, scl, mb)), ex2(fmaf(b1, scl, mb)));
            }
        }
        TSA(warp == 0 ? 4 : warp == 4 ? 20 : warp == 5 ? 28 : 63);
        uint32_t ol[10], oh[10];
        {
            uint32_t* const po = reinterpret_cast<uint32_t*>(sc + SC_O + warp * 160) + lane;
            const uint32_t ONES = 0x3F803F80u;
            float o[12][4];
#pragma unroll
            for (int hp = 0; hp < 2; hp++) {
#pragma unroll
                for (int h = hp * 2; h < hp * 2 + 2; h++) {
                    const int ta = (h >> 1) * 5 + (h & 1) * 3, tc = (h >> 1) * 5 + 2;
                    const bool mine = (lane < 16) != (h & 1);
                    const uint32_t a0 = pl[h] & mle, a1 = ph[h] & ~mle, a3 = ph[h] & mle, ap = pl[h] & ~mle;
#pragma unroll
                    for (int i = 0; i < 3; i++) o[h * 3 + i][0] = o[h * 3 + i][1] = o[h * 3 + i][2] = o[h * 3 + i][3] = 0.f;
                    mma16(o[h * 3 + 2], a0, a1, 0u, a3, mine ? vl[tc] : ONES, mine ? vh[tc] : ONES);
                    mma16(o[h * 3], a0, a1, 0u, a3, vl[ta], vh[ta]);
                    mma16(o[h * 3 + 1], a0, a1, 0u, a3, vl[ta + 1], vh[ta + 1]);
                    mma8(o[h * 3 + 2], ap, 0u, mine ? vp[tc] : ONES);
                    mma8(o[h * 3], ap, 0u, vp[ta]);
                    mma8(o[h * 3 + 1], ap, 0u, vp[ta + 1]);
                }
                if (hp && wg != HALF) bar_arrive(2, 256);
                const float (&oa)[4] = o[hp * 6 + 2], (&ob)[4] = o[hp * 6 + 5];
                const float hl = rcp(low ? ob[0] : oa[0]) * g0, hh = rcp(low ? ob[2] : oa[2]) * g1;
                const float gl = __shfl_xor_sync(0xffffffffu, hl, 2), gh = __shfl_xor_sync(0xffffffffu, hh, 2);
                const float ial = low ? gl : hl, iah = low ? gh : hh, ibl = low ? hl : gl, ibh = low ? hh : gh;
#pragma unroll
                for (int i = 0; i < 2; i++) {
                    ol[hp * 5 + i] = pack2(o[hp * 6 + i][0] * ial, o[hp * 6 + i][1] * ial);
                    oh[hp * 5 + i] = pack2(o[hp * 6 + i][2] * iah, o[hp * 6 + i][3] * iah);
                    ol[hp * 5 + 3 + i] = pack2(o[hp * 6 + 3 + i][0] * ibl, o[hp * 6 + 3 + i][1] * ibl);
                    oh[hp * 5 + 3 + i] = pack2(o[hp * 6 + 3 + i][2] * ibh, o[hp * 6 + 3 + i][3] * ibh);
                }
                ol[hp * 5 + 2] = pack2((low ? oa[0] : ob[0]) * gl, (low ? oa[1] : ob[1]) * gl);
                oh[hp * 5 + 2] = pack2((low ? oa[2] : ob[2]) * gh, (low ? oa[3] : ob[3]) * gh);
#pragma unroll
                for (int t = hp * 5; t < hp * 5 + 5; t++) {
                    st_relaxed4(po + t * 32, ol[t]);
                    st_relaxed4(po + 320 + t * 32, oh[t]);
                }
            }
        }
        TS(warp == 0 ? 5 : warp == 4 ? 21 : warp == 5 ? 29 : warp == 1 ? 31 : 63);
        const unsigned t_pub = clock();
        if (lane == 0) mbar_arrive(B_PUB);
        const uint4* ow = sc + (SC_O + HALF * 640 - hg * SC_SIZE);
        mbar_wait(B_INIT, 0);
        if (wg != HALF) {
            mbar_wait(B_PUB, 0);
            const unsigned t0 = F0_T ? t_start + max((unsigned)clock() - t_start + (wg ? F0_D : F1_D), wg ? F0_T : F1_T) : clock() + (wg ? F0_D : F1_D);
            uint32_t ph = 0;
#pragma unroll 1
            for (int i = w4 + 1 + NRS; i < 8; i += 4) {
                const uint4* src = ow + src_of(i, hg) * SC_SIZE;
                const uint32_t buf = o_buf(i), chk = buf + lane * 132;
                pace(t0, (i - 2) * O_DT);
                if (i > 4 + NRS) mbar_wait(B_DF, 0);
                if (i == 1 + NRS) TS(wg ? 3 : 4);
                uint32_t c;
                do {
                    if (elect_one()) {
                        mbar_expect_tx(B_OT + w4 * 8, 10240);
                        bulk_load(buf, src, 10240, B_OT + w4 * 8);
                    }
                    mbar_wait(B_OT + w4 * 8, ph);
                    if (i == 1 + NRS && !ph) TS(wg ? 19 : 20);
                    ph ^= 1;
                    c = max(max(lds4(chk), lds4(chk + 4096)), lds4(chk + 6144));
                } while (__any_sync(0xffffffffu, c == SENT));
                if (lane == 0) mbar_arrive(B_G2 + i * 8);
                TS(i == 2 ? 33 : 32 + i);
            }
            return;
        }

        float oc[80];
        uint32_t af[20];
        auto fetch = [&]() {
            const uint32_t* p = reinterpret_cast<const uint32_t*>(ow + src_of(1, hg) * SC_SIZE + w4 * 160) + lane;
#pragma unroll
            for (int t = 0; t < 20; t++) af[t] = ld_relaxed4(p + t * 32);
        };
        mbar_wait(B_XS, 0);
        const int orow = p0 + wg * 64 + w4 * 16;
        const uint32_t tk1 = ~lds4(SM_KEY + 16 * 4) & 2047, tk2 = ~lds4(SM_KEY + 17 * 4) & 2047;
        const uint32_t sel1 = (tk1 & 1) == par ? (tk1 >> 1) - orow : 99, sel2 = (tk2 & 1) == par ? (tk2 >> 1) - orow : 99;
        const uint32_t n0 = pack2(1.f - g0, 1.f - g0), n1 = pack2(1.f - g1, 1.f - g1);
        const uint32_t stg = SM_OUT + w4 * 5120;
        const uint32_t m128 = keep(stg + (lane & 15) * 128 + (((lane >> 4) ^ (lane & 7)) << 4));
        const uint32_t m64 = keep(stg + 4096 + (lane & 15) * 64 + (((lane >> 4) ^ ((lane >> 1) & 3)) << 4));
        const uint32_t l128 = keep(stg + (lane >> 3) * 128 + (((lane & 7) ^ (lane >> 3)) << 4));
        const uint32_t l64 = keep(stg + 4096 + r * 64 + ((cq ^ (lane >> 3)) << 4));
        char* const o128 = reinterpret_cast<char*>(P.op) + keep(((orow + (lane >> 3)) * 2 + par) * 1280 + kba * 128 + (lane & 7) * 16);
        char* const o64 = reinterpret_cast<char*>(P.op) + keep(((orow + r) * 2 + par) * 1280 + kbr * 128 + odd * 64 + cq * 16);
        if (!SETL) mbar_wait(B_G2, 0), mbar_wait(B_G2 + 8, 0);
        const bool ff = FFV == 1 || (FFV == 2 && cid < NFFN) || (FFV == 3 && wg) || (FFV == 4 && (cid < NFFN || wg));
        if (ff) {
            if (L0_T) pace(t_start, wg ? L1_T : L0_T);
            else pace(t_pub, wg ? L1_D : L0_D);
            fetch();
        }
        if (SETL) mbar_wait(B_G2, 0);
        bar_sync(2, 256);
        TS(w4 == 0 ? 6 : 63);
        wg_fence();
#pragma unroll
        for (int s = 0; s < 5; s++)
            wgmma_own(oc, ol[2 * s], oh[2 * s], ol[2 * s + 1], oh[2 * s + 1], desc_lo(wo_buf(0), 10240) + s * 128, s);
        wg_commit();
        if (!ff) fetch();
        TS(w4 == 0 ? 28 : 63);
        if (OEV == 2) {
            wg_wait<0>();
            if (leader) mbar_arrive(B_OE);
        }
        if (DFV == 0) mbar_wait(B_DF, 0);
        for (;;) {
            uint32_t m = 0;
#pragma unroll
            for (int t = 0; t < 20; t++) m = max(m, af[t]);
            if (!__any_sync(0xffffffffu, m == SENT)) break;
            fetch();
        }
        TS(w4 == 0 ? 7 : 63);
        if (OEV == 0) {
            wg_wait<0>();
            if (leader) mbar_arrive(B_OE);
        }
        wg_fence();
#pragma unroll
        for (int s = 0; s < 5; s++)
            wgmma_own(oc, af[2 * s], af[10 + 2 * s], af[2 * s + 1], af[11 + 2 * s], desc_lo(wo_buf(1), 10240) + s * 128, 1);
        wg_commit();
        if (OEV == 1) {
            wg_wait<1>();
            if (leader) mbar_arrive(B_OE);
        }
        if (DFV == 1) mbar_wait(B_DF, 0);
#pragma unroll 1
        for (int i = 1 + NRS; i < 8; i++) {
            const uint32_t ao = desc_lo(0, 128) + (o_buf(i) >> 4), wo = desc_lo(0, 10240) + (wo_buf(i) >> 4);
            mbar_wait(B_G2 + i * 8, 0);
            TS(w4 == 0 ? (i < 2 ? 6 + i : i < 7 ? 9 + i : 17) : 63);
            wg_fence();
#pragma unroll
            for (int s = 0; s < 5; s++) wgmma_out(oc, ao + s * 16, wo + s * 128, 1);
            wg_commit();
            if (i < 4) {
                wg_wait<1>();
                if (i > 1 && leader) mbar_arrive(B_OE - 8 + i * 8);
            }
        }
        TS(w4 == 0 ? 8 : 63);

        if (min(sel1, sel2) < 16) {
#pragma unroll 1
            for (int j = -PV; j < 2; j++) {
                const uint32_t sel = j > 0 ? sel2 : j ? 16 : sel1;
                if (sel > 16) continue;
                if (j >= 0) mbar_wait(B_MOD, 0);
#pragma unroll
                for (int t = 0; t < 5; t++) {
                    const uint4 v = lds16(SM_U + j * 320 + cq * 80 + t * 16);
                    const uint32_t u[4] = {v.x, v.y, v.z, v.w};
#pragma unroll
                    for (int k = 0; k < 4; k++) {
                        if (sel == r) nb[8 * t + 2 * k] = hadd2(nb[8 * t + 2 * k], u[k]);
                        if (sel == r + 8) nb[8 * t + 2 * k + 1] = hadd2(nb[8 * t + 2 * k + 1], u[k]);
                    }
                }
            }
            TS(26);
        }
        wg_wait<0>();
        TS(w4 == 0 ? 9 : 63);
        const bool nan = oc[0] != oc[0] || oc[2] != oc[2];
#pragma unroll
        for (int part = 0; part < 3; part++) {
            const int s0 = part ? part * 4 - 4 : 8, ns = part ? 4 : 2;
#pragma unroll
            for (int i = 0; i < 4; i++) {
                if (i >= ns) break;
                const int s = s0 + i;
                const uint32_t y0 = hfma2(n0, nb[s * 4], pack2(oc[s * 8 + 0], oc[s * 8 + 1]));
                const uint32_t y1 = hfma2(n1, nb[s * 4 + 1], pack2(oc[s * 8 + 2], oc[s * 8 + 3]));
                const uint32_t y2 = hfma2(n0, nb[s * 4 + 2], pack2(oc[s * 8 + 4], oc[s * 8 + 5]));
                const uint32_t y3 = hfma2(n1, nb[s * 4 + 3], pack2(oc[s * 8 + 6], oc[s * 8 + 7]));
                asm volatile("stmatrix.sync.aligned.m8n8.x4.shared.b16 [%0], {%1,%2,%3,%4};"
                             ::"r"(((s < 8 ? m128 : m64) ^ ((s & 3) * 32)) + (s & 4) * 512 + rk), "r"(y0), "r"(y1), "r"(y2), "r"(y3) : "memory");
            }
            __syncwarp();
            uint4 v[4];
#pragma unroll
            for (int i = 0; i < 4; i++)
                if (i < ns) v[i] = lds16(!part ? l64 + i * 512 : (l128 ^ ((i & 1) * 64)) + i * 512 + s0 * 512);
#pragma unroll
            for (int i = 0; i < 4; i++)
                if (i < ns) *reinterpret_cast<uint4*>(!part ? o64 + i * 8 * 2560 : o128 + i * 4 * 2560 + s0 * 32) = v[i];
            if (part == 0) TS(w4 == 0 ? 1 : 63);
        }
        TS(w4 == 0 ? 10 : 63);
        if (lane == 0) mbar_arrive(B_DONE);
        uint32_t redo;
        asm volatile("{\n.reg .pred p, q;\nsetp.ne.u32 p, %1, 0;\nbar.cta.red.or.pred q, 10, 128, p;\nselp.u32 %0, 1, 0, q;\n}"
                     : "=r"(redo) : "r"((uint32_t)nan) : "memory");
        if (redo) {
            const int cb = hg >> 1;
#pragma unroll 1
            for (int i = 0; i < 8; i++) {
                if (leader) {
                    mbar_expect_tx(B_RE, 25600);
                    tma_3d(SM_W, &P.woa, B_RE, 0, i * 80, (cb * 5 + 1) >> 1);
                    tma_2d(SM_W + 20480, &P.wob, B_RE, cb * 160 + ((cb & 1) ? 0 : 128), i * 80);
                }
#pragma unroll 1
                for (int s = 0; s < 20; s++) {
                    const int w = w4 * 640 + s * 32 + lane;
                    uint32_t v, it = 0;
                    do {
                        v = ld_relaxed4(reinterpret_cast<const uint32_t*>(ow + i * SC_SIZE) + w);
                        if (++it > (1u << 22)) fault();
                    } while ((v >> 16) == 0xFFFFu || (v & 0xFFFFu) == 0xFFFFu);
                    sts4(SM_X + w * 4, v);
                }
                fence_async_smem();
                __syncwarp();
                bar_sync(10, 128);
                mbar_wait(B_RE, i & 1);
                wg_fence();
#pragma unroll
                for (int s = 0; s < 5; s++) wgmma_out(oc, desc_lo(SM_X, 128) + s * 16, desc_lo(SM_W, 10240) + s * 128, s || i);
                wg_commit();
                wg_wait<0>();
                bar_sync(10, 128);
            }
#pragma unroll
            for (int t = 0; t < 40; t++) {
                const int col = (t < 32 ? kba * 64 + (t >> 1) * 8 : kbr * 64 + odd * 32 + ((t - 32) >> 1) * 8) + cq * 2;
                *reinterpret_cast<uint32_t*>(P.op + ((orow + r + (t & 1) * 8) * 2 + par) * 640 + col) =
                    hfma2((t & 1) ? n1 : n0, nb[t], pack2(oc[2 * t], oc[2 * t + 1]));
            }
        }
    } else if (role < 12) {
        asm volatile("setmaxnreg.dec.sync.aligned.u32 96;");
        const int t = tid - 256;
        uint32_t tag = ld_relaxed4(g_cnt);
        float gv = 0.f;
        int grow = hg * 16 + (t >> 3);
        mbar_wait(B_RG, 0);
        TS(warp == 8 ? 48 : 63);
        {
            float r0 = 0.f, r1 = 0.f, g0 = 0.f, g1 = 0.f;
            const uint32_t sw = (t >> 4) * 128 + (((t ^ (t >> 4)) & 7) << 4), hi = (t >> 3) & 1;
            mbar_wait(B_XL0, 0);
            tag = (tag * 8 + 2048) & 0xF800u;
            sts4(SM_KEY + 20 * 4, tag);
#pragma unroll 1
            for (int i = 0; i < 5; i++) {
                const int p = (RG_ORDER >> (i * 4)) & 7, kb = 2 * p + hi;
                mbar_wait(p < 3 ? B_FULL + (p & 1) * 32 : B_RG2, p == 2);
                if (p < 2) mbar_wait(B_FULL + p * 32 + 16, 0);
                const uint32_t xa = sw + (kb < 5 ? SM_X + (kb & 3) * 16384 + hg * 2048 : SM_HALO - 5 * 2048 + kb * 2048);
                const uint4 a = lds16(xa), b = lds16(xa + 1024);
                const uint4 w = lds16(SM_RED + p * 256 + (t & 15) * 16), v = lds16(SM_RED + 1280 + p * 256 + (t & 15) * 16);
                if (__ballot_sync(0xffffffffu, lane == 0 || a.w == b.w) && lane == 0 && p < 3) mbar_arrive(B_XE + p * 8);
                TS5(warp == 8 ? 51 + i : 63);
                const uint32_t as[4] = {a.x, a.y, a.z, a.w}, bs[4] = {b.x, b.y, b.z, b.w};
                const uint32_t ws[4] = {w.x, w.y, w.z, w.w}, vs[4] = {v.x, v.y, v.z, v.w};
#pragma unroll
                for (int e = 0; e < 4; e++) {
                    r0 = fmaf(bf_lo(as[e]), bf_lo(ws[e]), r0);
                    r1 = fmaf(bf_lo(bs[e]), bf_lo(ws[e]), r1);
                    g0 = fmaf(bf_lo(as[e]), bf_lo(vs[e]), g0);
                    g1 = fmaf(bf_lo(bs[e]), bf_lo(vs[e]), g1);
                    r0 = fmaf(bf_hi(as[e]), bf_hi(ws[e]), r0);
                    r1 = fmaf(bf_hi(bs[e]), bf_hi(ws[e]), r1);
                    g0 = fmaf(bf_hi(as[e]), bf_hi(vs[e]), g0);
                    g1 = fmaf(bf_hi(bs[e]), bf_hi(vs[e]), g1);
                }
            }
            const bool up = lane & 4;
            r0 = (hi ? r1 : r0) + __shfl_xor_sync(0xffffffffu, hi ? r0 : r1, 8);
            g0 = (hi ? g1 : g0) + __shfl_xor_sync(0xffffffffu, hi ? g0 : g1, 8);
            float r = (up ? g0 : r0) + __shfl_xor_sync(0xffffffffu, up ? r0 : g0, 4);
            r += __shfl_xor_sync(0xffffffffu, r, 2);
            r = bf_round(r + __shfl_xor_sync(0xffffffffu, r, 1));
            const int row = hg * 16 + (t >> 4) + hi * 8;
            const uint32_t u = f2u(r);
            if (!up) sts4(SM_KEY + (t >> 3) * 4, (((int)u < 0 ? ~u : u | 0x80000000u) & 0xFFFF0000u) | (2047 - (p0 + row) * 2 - par));
            gv = r;
            grow = row;
        }
        TS(warp == 8 ? 63 : 63);
        mbar_wait(B_RG2, 0);
        bar_sync(4, 128);
        if (warp == 8) {
            const uint32_t key = lds4(SM_KEY + (lane & 15) * 4);
            uint32_t k1 = __reduce_max_sync(0xffffffffu, key);
            uint32_t k2 = __reduce_max_sync(0xffffffffu, key == k1 ? 0u : key);
            if (elect_one()) {
                st_relaxed8(g_cand + cid, k1 | tag, k2 | tag);
                red_inc<MAPV == 3 ? 2 : 1>(g_cnt, tag);
            }
            TS(49);
        }
        if ((lane & 7) == 4) st_relaxed4(g_gate + tile * 128 + grow, f2u(bf_round(sigmoidf(gv))) | tag);
        const int cq = lane & 3, w4 = warp & 3;
        const uint32_t la = keep(cq * 256 + (((lane >> 2) ^ cq * 2) << 4));
        const uint32_t sel = keep(0x44444444u ^ (0x54u << (lane >> 2 & 1) * 8 + (lane & 16)));
        if (NFFN) {
            float4 d;
            uint4* dst;
            if (cid < NFFN) {
                float dg[8], du[8];
                mbar_wait(B_GU, 0);
                mbar_wait(B_XS, 0);
                TS(warp == 8 ? 50 : 63);
                if (GW & 1) mbar_wait(B_EMPTY + 3 * 8, 0);
                wg_fence();
#pragma unroll
                for (int i = 0; i < 10; i++) wgmma_vec(dg, desc_lo(SM_F + i * 2048, 16), desc_lo(SM_XS + i * 32, 16), i);
                wg_commit();
                mbar_wait(B_UP, 0);
                TS(warp == 10 ? 58 : 63);
                if (GW & 2) mbar_wait(B_EMPTY + 3 * 8, 0);
                wg_fence();
#pragma unroll
                for (int i = 0; i < 10; i++) wgmma_vec(du, desc_lo(SM_UP + i * 2048, 16), desc_lo(SM_XS + i * 32, 16), i);
                wg_commit();
                wg_wait<0>();
                if (lane == 0) mbar_arrive(B_GUD), mbar_arrive(B_DF);
                TS(warp == 8 ? 54 : warp == 10 ? 59 : 63);
                if (cq == 0) {
                    st_relaxed16(sc + SC_GU + w4 * 16 + (lane >> 2), f2u(dg[0]), f2u(dg[4]), f2u(du[0]), f2u(du[4]));
                    st_relaxed16(sc + SC_GU + w4 * 16 + 8 + (lane >> 2), f2u(dg[2]), f2u(dg[6]), f2u(du[2]), f2u(du[6]));
                }
            } else {
                uint4 wv[2][8], wr[4];
                mbar_wait(B_UP, 0);
                TS(warp == 10 ? 58 : 63);
                if (SP_W) mbar_wait(B_EMPTY + 3 * 8, 0);
#pragma unroll
                for (int i = 0; i < 8; i++) wv[i >> 2][4 + (i & 3)] = lds16((la ^ (i & 1) * 144) + SM_UP + w4 * 4096 + (i >> 1) * 1024);
                if (landed<4>(wv[0] + 4, lane) & landed<4>(wv[1] + 4, lane)) mbar_arrive(B_GUD);
                TS(warp == 8 ? 54 : 63);
                mbar_wait(B_GU, 0);
#pragma unroll
                for (int i = 0; i < 4; i++) wr[i] = lds16((la ^ (i & 1) * 144) + SM_F + 12288 + w4 * 2048 + (i >> 1) * 1024);
                mbar_wait(B_XS, 0);
                if (w4 == 0) {
                    uint4 pq[4];
                    pace(t_start, HS_T);
                    poll<4>(pq, g_sc + ((cid >> 1) * 4 - 148) * SC_SIZE + SC_GU + (cid & 1) * 32 + lane, SC_SIZE);
                    TS(warp == 8 ? 55 : 63);
                    swiglu(pq, SM_H + (lane & 6) * 8 + (lane >> 3) * 4 + (lane & 1) * 2, 64);
                }
                bar_sync(4, 128);
                TS(warp == 8 ? 57 : 63);
                const uint4 h = lds16(SM_H + (lane & 8) * 8 + cq * 16);
                const uint32_t hv[4] = {h.x, h.y, h.z, h.w}, hr[2] = {(w4 & 1) ? h.z : h.x, (w4 & 1) ? h.w : h.y};
                d = vec_mma<4>(wr, hr, sel);
                dst = g_sc + (cid * 5 - 520 + w4) * SC_SIZE + SC_Y + (lane & 1) * 32 + (lane >> 1);
                float c[2][2][4] = {};
                const uint32_t s2 = sel + ((sel & 0x10101010u) >> 3) * 17;
#pragma unroll
                for (int i = 7; i >= 0; i--) {
                    const uint32_t x0 = prmt(hv[i >> 1], (i & 1) ? s2 : sel), x1 = prmt(hv[i >> 1], ((i & 1) ? s2 : sel) >> 16);
#pragma unroll
                    for (int n = 0; n < 2; n++) {
                        if (i >= 4) wv[n][i - 4] = lds16((la ^ (i & 1) * 144) + SM_F - 6144 + w4 * 4096 + n * 2048 + (i >> 1) * 1024);
                        mma16(c[n][i & 1], wv[n][i].x, wv[n][i].y, wv[n][i].z, wv[n][i].w, x0, x1);
                    }
                }
#pragma unroll
                for (int n = 0; n < 2; n++)
                    st_relaxed16(dst + n * 16, f2u(c[n][0][0] + c[n][1][0]), f2u(c[n][0][1] + c[n][1][1]), f2u(c[n][0][2] + c[n][1][2]),
                                 f2u(c[n][0][3] + c[n][1][3]));
                dst += (4 - w4) * SC_SIZE + w4 * 8;
                TS(warp == 8 ? 30 : 63);
                if (lane == 0 && f2u(d.x) != SENT) mbar_arrive(B_DF);
                if (w4 & 1) {
                    sts16(SM_RED + 512 + (w4 & 2) * 256 + lane * 16, f2u(d.x), f2u(d.y), f2u(d.z), f2u(d.w));
                    bar_arrive(13 + (w4 >> 1), 64);
                } else {
                    bar_sync(13 + (w4 >> 1), 64);
                    const uint4 o = lds16(SM_RED + 512 + (w4 & 2) * 256 + lane * 16);
                    st_relaxed16(dst, f2u(d.x + u2f(o.x)), f2u(d.y + u2f(o.y)), f2u(d.z + u2f(o.z)), f2u(d.w + u2f(o.w)));
                }
            }
        } else {
            if (t < 4) mbar_arrive(B_GUD);
            if (t < 4) mbar_arrive(B_DF);
            mbar_wait(B_XS, 0);
        }
        TS(warp == 8 ? 51 : 63);
        const uint32_t k1 = lds4(SM_KEY + 16 * 4), k2 = lds4(SM_KEY + 17 * 4);
        const uint32_t mine = (tile >> 1) * 256 + HALF * 128 + par;
        const bool own1 = (~k1 & 0x781) == mine, own2 = (~k2 & 0x781) == mine;
        if ((own1 || own2) && NFFN) {
            const int rg = min(t / 40, 2), un = (hg >> 1) * 40 + t % 40, up = (hg >> 1) * 80 + min(t, 79);
            mbar_wait(B_RS, 0);
            pace(t_start, Y_T);
            TS(warp == 8 ? 60 : 63);
#pragma unroll 1
            for (int j = !own1; j <= own2; j++) {
                const uint4* p = g_sc + (rg * 5 + 20 + (un >> 5)) * SC_SIZE + SC_Y + j * 32 + (un & 31);
                float y[4];
                bool bad;
                do {
                    uint4 yp[7];
#pragma unroll
                    for (int i = 0; i < 7; i++) yp[i] = i < 6 || rg < 2 ? ld_relaxed16(p + i * 15 * SC_SIZE) : make_uint4(0, 0, 0, 0);
                    y[0] = y[1] = y[2] = y[3] = 0.f;
                    bad = false;
#pragma unroll
                    for (int i = 0; i < 7; i++) {
                        y[0] += u2f(yp[i].x); y[1] += u2f(yp[i].y); y[2] += u2f(yp[i].z); y[3] += u2f(yp[i].w);
                        bad |= yp[i].w == SENT;
                    }
                } while (__any_sync(0xffffffffu, bad));
                TS(warp == 8 ? 53 : 63);
                sts16(SM_SENT + j * 2048 + t * 16, f2u(y[0]), f2u(y[1]), f2u(y[2]), f2u(y[3]));
                bar_sync(4, 128);
                if (w4 < 3) {
                    const uint32_t key = j ? k2 : k1, ya = SM_SENT + j * 2048 + t * 8;
                    const float rs = bf_round(sigmoidf(u2f(((int)key < 0 ? key & 0x7FFFFFFFu : ~key) & 0xFFFF0000u)));
                    const float2 y0 = lds8f(ya), y1 = lds8f(ya + 640), y2 = lds8f(ya + 1280);
                    const uint2* q = reinterpret_cast<const uint2*>(g_sc + (up >> 6) * SC_SIZE + SC_Y + j * 32) + (up & 63);
                    const float sx = y0.x + y1.x + y2.x, sy = y0.y + y1.y + y2.y;
                    uint2 z[4];
                    pace(t_start, Y2_T);
                    do {
#pragma unroll
                        for (int i = 0; i < 4; i++) z[i] = ld_relaxed8(q + i * 10 * SC_SIZE);
                    } while (__any_sync(0xffffffffu, max(max(z[0].y, z[1].y), max(z[2].y, z[3].y)) == SENT));
                    TS(warp == 8 ? 62 : 63);
                    if (t < 80)
                        sts4(SM_U + j * 320 + (t & 3) * 80 + ((t >> 2) + (hg & 2) * 8) % 20 * 4, pack2(bf_round(sx + (u2f(z[0].x) + u2f(z[1].x)) + (u2f(z[2].x) + u2f(z[3].x))) * rs,
                                                           bf_round(sy + (u2f(z[0].y) + u2f(z[1].y)) + (u2f(z[2].y) + u2f(z[3].y))) * rs));
                }
            }
        }
        __syncwarp();
        if (lane == 0) mbar_arrive(B_MOD);
        TS(warp == 8 ? 52 : 63);
    } else {
        asm volatile("setmaxnreg.dec.sync.aligned.u32 32;");
        if (warp == 15) {
            if (EPF_M) {
                pace(t_start, EPF_T);
                if (lane < (EPF_M << EPF_H)) l2_prefetch(P.wp + (EPF_N * 132 + (lane >> EPF_H) * 128 + bid) * 64 + (lane & EPF_H) * 32);
            }
#pragma unroll 1
            for (int i = PF_0; i < PF_N; i++) {
                pace(t_start, (i < 6 ? PF_UP : PF_DN) + i * PF_DT);
                const int ln = (i * 128 + cid) * 32 + lane;
                l2_prefetch((ln < 17280 ? P.upp : ln < 23680 ? P.wop - 17280 * 64 : P.dp - 23680 * 64) + ln * 64);
            }
            if (elect_one()) {
#pragma unroll 1
                for (int i = 0; i < (!NFFN ? 0 : cid < NFFN ? 8 : 12); i++) {
                    pace(t_start, GU_T0 + i * (cid < NFFN ? GU_DT : GU_DS) + (cid & 7) * GU_ST);
                    if (cid < NFFN) tma_2d(SM_F + i * 2560, &P.gate, B_GU, (cid >> 2) * 64, (cid & 3) * 160 + i * 20);
                    else tma_2d(SM_F - 4096 + i * 2048, &P.down, B_GU, min(i, 4 + (i >> 1)) * 64, cid * 32 - 2368 + (i > 8 ? (i & 1) * 16 : 0));
                }
            }
            __syncwarp();
            int it = (smem_u32(smem_raw) & 0xFFFFFF) == SB ? 0 : 1 << 20;
            while (!mbar_try(B_DONE, 0) || !mbar_try(B_MOD, 0))
                if (++it > (1 << 20)) fault();
        } else if (warp == 13) {
#pragma unroll 1
            for (int i = 0; i < 10; i++) sts16(SM_SENT + i * 512 + lane * 16, SENT, SENT, SENT, SENT);
            fence_async_smem();
            __syncwarp();
            if (elect_one()) {
                if (!RW_REG) mbar_expect_tx(B_RG, 2560);
                mbar_expect_tx(B_GU, cid < NFFN ? 20480 : 24576);
                asm volatile("mbarrier.expect_tx.relaxed.cta.shared::cta.b64 [%0], 10240;" ::"r"(B_RG2 + rk) : "memory");
                pace(t_start, RW1_T);
                bulk_load(SM_RED, P.w_r, 1280, B_RG);
                bulk_load(SM_RED + 1280, P.gate_w, 1280, B_RG);
#pragma unroll 1
                for (int i = 0; i < 5; i++) {
                    pace(t_start, RG1_T0 + i * RG1_DT);
                    tma_3d(SM_HALO + i * 2048, &P.xg, B_RG2, 320 + i * 64, par, p0 + hg * 16);
                }
#pragma unroll
                for (int i = 0; i < 23; i++) mbar_init(B_GUD + i * 8, i == 10 ? 8 : i == 22 || i == 9 || !i ? 4 : i < 16 ? 1 : 2);
                bulk_store(sc + SC_HALO, SM_SENT, 5120);
                asm volatile("cp.async.bulk.commit_group;\ncp.async.bulk.wait_group 0;" ::: "memory");
                mbar_arrive(B_RG2);
                TS(43);
                const unsigned goal = (ld_relaxed4(g_cnt + 32) | (NCTA - 1)) + 1;
#pragma unroll 1
                for (int i = RS_E; i < RS_N; i++) {
                    pace(t_start, RS_T0 + (i - RS_E) * RS_DT + (cid & 7) * RS_S);
                    bulk_store(sc + i * (1280 / RS_N), SM_SENT, 20480 / RS_N);
                }
                asm volatile("cp.async.bulk.commit_group;\ncp.async.bulk.wait_group 0;" ::: "memory");
                red_inc(g_cnt + 32, goal);
                mbar_arrive(B_RS);
                TS(44);
                while (ld_relaxed4(g_cnt + 32) - goal > 0x80000000u) {}
                mbar_arrive(B_INIT);
                TS(45);
            }
        } else if (warp == 14) {
            if (elect_one()) {
#pragma unroll 1
                for (int kb = 1; kb < 10; kb++) {
                    const uint32_t fb = B_FULL + (kb & 3) * 16, dst = SM_X + (kb & 3) * 16384;
                    mbar_wait(fb + (B_EMPTY - B_FULL + 8), ~(kb >> 2) & 1);
                    if (kb >= 4) mbar_wait(B_XE + (kb - 4 >> 1) * 8, 0);
                    pace(t_start, max(PACE_A - PACE_B / 2 + 2 * kb * PACE_B, PACE_W0 - X_OFF + (2 * kb + 1) * PACE));
                    tma_3d(dst, &P.x2, fb, kb * 64, par, p0);
                    TS5(41 + kb);
                }
            }
            __syncwarp();
            pace(t_start, CAND_T);
            {
                const uint32_t tag = lds4(SM_KEY + 20 * 4);
                uint4 c[2], v;
                do {
                    c[0] = ld_relaxed16(g_cand + lane * 2);
                    c[1] = ld_relaxed16(g_cand + lane * 2 + 64);
                    v = ld_relaxed16(g_gate + tile * 128 + lane * 4);
                } while (__any_sync(0xffffffffu, ((c[0].x ^ tag) | (c[0].z ^ tag) | (c[1].x ^ tag) | (c[1].z ^ tag) | (v.x ^ tag) |
                                                  (v.y ^ tag) | (v.z ^ tag) | (v.w ^ tag)) & 0xF800u));
                const uint32_t a1 = max(c[0].x, c[0].z), b1 = max(c[1].x, c[1].z), l1 = max(a1, b1);
                const uint32_t l2 = max(max(max(c[0].y, c[0].w), max(c[1].y, c[1].w)),
                                        max(max(min(c[0].x, c[0].z), min(c[1].x, c[1].z)), min(a1, b1)));
                const uint32_t k1 = __reduce_max_sync(0xffffffffu, l1);
                const uint32_t k2 = __reduce_max_sync(0xffffffffu, l1 == k1 ? l2 : l1);
                sts16(SM_GATE + lane * 16, v.x, v.y, v.z, v.w);
                __syncwarp();
                if (elect_one()) {
                    bulk_load(SM_XS, P.xp + (~k1 & 2047) * 640 + (cid & 3) * 160, 320, B_XS);
                    bulk_load(SM_XS + 320, P.xp + (~k2 & 2047) * 640 + (cid & 3) * 160, 320, B_XS);
                    sts16(SM_KEY + 16 * 4, k1, k2, 0, 0);
                    mbar_expect_tx(B_XS, 640);
                    mbar_arrive(B_GT);
                    TS(56);
                }
            }
            bar_sync(12, 64);
            pace(t_start, 0);
            pace(clock(), HALO_D);
            TS(24);
            uint4 hv[5];
            poll<5>(hv, sc + (SC_HALO - (tile < 2 ? 0 : 16 * SC_SIZE) + lane), 32);
#pragma unroll
            for (int s = 0; s < 5; s++) sts16(SM_HALO + s * 512 + lane * 16, hv[s].x, hv[s].y, hv[s].z, hv[s].w);
            bar_arrive(8, 64);
            TS(25);
        } else {
            if (elect_one()) {
#pragma unroll 1
                for (int s = W_S0; s < 20; s++) {
                    const uint32_t fb = B_FULL + (s & 7) * 8, dst = SM_W + (s & 7) * 15360;
                    mbar_wait(fb + (B_EMPTY - B_FULL), ~(s >> 3) & 1);
                    pace(t_start, max(PACE_A + s * PACE_B, PACE_W0 + s * PACE));
                    mbar_expect_tx(fb, (s & 1) ? 15360 : 15360 + 16384);
                    tma_3d(dst, &P.w, fb, wcm, s * 32, 0);
                    tma_3d(dst + 12288, &P.wr, fb, wcr, s * 32, 0);
                    TS2(20 + s);
                    if (s == W_S0) TS(41);
                }
                mbar_wait(B_RG2, 0);
                if (NFFN) {
                    mbar_wait(B_EMPTY + 5 * 8, 1);
                    mbar_expect_tx(B_UP, cid < NFFN ? 20480 : 16384);
                    TS(46);
                    if (cid < NFFN) tma_2d(SM_UP, &P.up, B_UP, (cid >> 2) * 64, (cid & 3) * 160);
                    else
#pragma unroll 1
                        for (int i = 0; i < 8; i++) tma_2d(SM_UP + i * 2048, &P.down, B_UP, i * 64, cid * 32 - 2352);
                }
                const int cb = hg >> 1, ca = (cb * 5 + 1) >> 1, cr = cb * 160 + ((cb & 1) ? 0 : 128);
                if (C0_T) pace(t_start, C0_T);
#pragma unroll 1
                for (int j = 0; j < 8; j++) {
                    const int i = j ^ (j == 3 || j == 4 ? 7 : 0);
                    if (j != 3) mbar_wait(j < 3 ? B_EMPTY + ((2 * j + 7) & 7) * 8 : B_GUD + (j - 4) * 8, j == 0);
                    if (j >= 5) {
                        if (C5_T) pace(t_start, (j == 5 ? C5_T : j == 6 ? C6_T : C7_T) - HALF * C_O);
                        else pace(clock(), j == 5 ? C5_D : C6_D);
                    }
                    const uint32_t dst = wo_buf(i), gb = B_G2 + i * 8;
                    mbar_expect_tx(gb, 25600);
                    tma_3d(dst, &P.woa, gb, 0, src_of(i, hg) * 80, ca);
                    tma_2d(dst + 20480, &P.wob, gb, cr, src_of(i, hg) * 80);
                }
            }
        }
    }
}

typedef CUresult (*EncodeFn)(CUtensorMap*, CUtensorMapDataType, cuuint32_t, void*, const cuuint64_t*, const cuuint64_t*,
                             const cuuint32_t*, const cuuint32_t*, CUtensorMapInterleave, CUtensorMapSwizzle,
                             CUtensorMapL2promotion, CUtensorMapFloatOOBfill);

void encode(EncodeFn fn, CUtensorMap* m, const void* ptr, int rank, const cuuint64_t* dims, const cuuint64_t* strides,
            const cuuint32_t* box, CUtensorMapSwizzle swz) {
    const cuuint32_t es[4] = {1, 1, 1, 1};
    fn(m, CU_TENSOR_MAP_DATA_TYPE_BFLOAT16, rank, const_cast<void*>(ptr), dims, strides, box, es,
       CU_TENSOR_MAP_INTERLEAVE_NONE, swz, CU_TENSOR_MAP_L2_PROMOTION_L2_128B, CU_TENSOR_MAP_FLOAT_OOB_FILL_NONE);
}

}

extern "C" void kernel_launch(void* const* d_in, const int* in_sizes, int n_in, void* d_out, int out_size) {
    (void)in_sizes; (void)n_in; (void)out_size;
    Params P;
    P.xp = (const __nv_bfloat16*)d_in[0];
    P.wp = (const __nv_bfloat16*)d_in[1];
    P.wop = (const __nv_bfloat16*)d_in[2];
    P.dp = (const __nv_bfloat16*)d_in[7];
    P.upp = (const __nv_bfloat16*)d_in[6];
    P.op = (__nv_bfloat16*)d_out;
    P.w_r = (const __nv_bfloat16*)d_in[4];
    P.gate_w = (const __nv_bfloat16*)d_in[8];

    void* fp = nullptr;
    cudaDriverEntryPointQueryResult st;
    cudaGetDriverEntryPoint("cuTensorMapEncodeTiled", &fp, cudaEnableDefault, &st);
    EncodeFn fn = (EncodeFn)fp;
    const cuuint64_t xd[3] = {640, 2, 1024}, xs[2] = {1280, 2560};
    const cuuint32_t bx[3] = {64, 1, 64}, bx2[3] = {64, 1, 128};
    encode(fn, &P.x2, d_in[0], 3, xd, xs, bx2, CU_TENSOR_MAP_SWIZZLE_128B);
    encode(fn, &P.x, d_in[0], 3, xd, xs, bx, CU_TENSOR_MAP_SWIZZLE_128B);
    const cuuint64_t wd[3] = {640, 640, 3}, ws[2] = {3840, 1280};
    const cuuint32_t bw[3] = {64, 32, 3}, bwr[3] = {16, 32, 3};
    encode(fn, &P.w, d_in[1], 3, wd, ws, bw, CU_TENSOR_MAP_SWIZZLE_128B);
    encode(fn, &P.wr, d_in[1], 3, wd, ws, bwr, CU_TENSOR_MAP_SWIZZLE_32B);
    const cuuint64_t ad[3] = {64, 640, 10}, as[2] = {1280, 128}, bd[2] = {640, 640};
    const cuuint32_t ba[3] = {64, 80, 2}, bb[2] = {32, 80};
    encode(fn, &P.woa, d_in[2], 3, ad, as, ba, CU_TENSOR_MAP_SWIZZLE_128B);
    encode(fn, &P.wob, d_in[2], 2, bd, as, bb, CU_TENSOR_MAP_SWIZZLE_128B);
    const cuuint64_t gd[2] = {1728, 640}, gs[1] = {3456}, dd[2] = {640, 1728};
    const cuuint32_t bg[2] = {64, 20}, bu[2] = {64, 160}, bdn[2] = {64, 16}, bxg[3] = {64, 1, 16};
    encode(fn, &P.xg, d_in[0], 3, xd, xs, bxg, CU_TENSOR_MAP_SWIZZLE_128B);
    encode(fn, &P.gate, d_in[5], 2, gd, gs, bg, CU_TENSOR_MAP_SWIZZLE_128B);
    encode(fn, &P.up, d_in[6], 2, gd, gs, bu, CU_TENSOR_MAP_SWIZZLE_128B);
    encode(fn, &P.up2, d_in[6], 2, gd, gs, bg, CU_TENSOR_MAP_SWIZZLE_128B);
    encode(fn, &P.down, d_in[7], 2, dd, as, bdn, CU_TENSOR_MAP_SWIZZLE_128B);

    cudaFuncSetAttribute(fused_kernel, cudaFuncAttributeMaxDynamicSharedMemorySize, SM_TOTAL);
    fused_kernel<<<NCTA + (MAPV == 3 ? 0 : NEXTRA), 512, SM_TOTAL, cudaStreamPerThread>>>(P);
}
```

```cpp
#include <cuda_runtime.h>
#include <cuda_bf16.h>
#include <cuda.h>
#include <stdint.h>

namespace {

constexpr int NCTA = 128, NEXTRA = 4;
constexpr int NFFN = 108;
constexpr uint32_t SENT = 0xFFFFFFFFu;

constexpr uint32_t SB = 1024;
constexpr uint32_t SM_W = SB;
constexpr uint32_t SM_X = SB + 122880;
constexpr uint32_t SM_F = SB + 192512;
constexpr uint32_t SM_HALO = SB + 212992;
constexpr uint32_t SM_BAR = SB + 223232;
constexpr uint32_t SM_PROF = SB + 223744;
constexpr uint32_t SM_KEY = SB + 224000;
constexpr uint32_t SM_RED = SB + 224128;
constexpr uint32_t SM_XS = SB + 226688;
constexpr uint32_t SM_SENT = SB + 227328;
constexpr uint32_t SM_U = SM_RED + 1920;
constexpr uint32_t SM_H = SM_RED + 1536;
constexpr uint32_t SM_GATE = SM_RED;
constexpr uint32_t SM_TOTAL = 232448;
constexpr uint32_t SM_HALO1 = SM_X + 32768;
constexpr uint32_t SM_UP = SM_W + 61440;
constexpr uint32_t SM_OUT = SM_W + 61440;

constexpr uint32_t B_XL0 = SM_BAR, B_FULL = SM_BAR + 8, B_GT = SM_BAR + 72, B_RG = SM_BAR + 80, B_RG2 = SM_BAR + 88,
                   B_XS = SM_BAR + 96, B_EMPTY = SM_BAR + 128, B_DONE = SM_BAR + 192, B_XE = SM_BAR + 200,
                   B_GUD = SM_BAR + 224, B_OE = SM_BAR + 232, B_OT = SM_BAR + 264, B_MOD = SM_BAR + 296,
                   B_GU = SM_BAR + 104, B_UP = SM_BAR + 112, B_RS = SM_BAR + 312, B_INIT = SM_BAR + 320,
                   B_RE = SM_BAR + 328, B_PUB = SM_BAR + 304, B_G2 = SM_BAR + 336, B_DF = SM_BAR + 400;

struct Params {
    CUtensorMap x, x2, w, wr, woa, wob, xg, gate, up, down, up2;
    __nv_bfloat16* op;
    const __nv_bfloat16 *xp, *wp, *dp, *upp, *wop, *w_r, *gate_w;
};

constexpr int SC_O = 0;
constexpr int SC_HALO = 1280;
constexpr int SC_GU = 1440;
constexpr int SC_Y = 1504;
constexpr int SC_SIZE = 1600;
__device__ __align__(128) uint4 g_sc[NCTA * SC_SIZE];
__device__ __align__(128) uint2 g_cand[NCTA];
__device__ __align__(16) uint32_t g_gate[2048];
__device__ __align__(128) unsigned g_cnt[64];
#define TS(i) do { } while (0)
#define TS2(i) do { } while (0)
#define TSX(i) do { } while (0)

#define TSL(i) do { } while (0)
#define TS5(i) do { } while (0)
__device__ __forceinline__ uint32_t smem_u32(const void* p) { return (uint32_t)__cvta_generic_to_shared(p); }
__device__ __forceinline__ void fault() { asm volatile("st.shared.u32 [%0], %0;" ::"r"(0x100001) : "memory"); }
__device__ __forceinline__ void mbar_init(uint32_t bar, uint32_t cnt) {
    asm volatile("mbarrier.init.shared::cta.b64 [%0], %1;" ::"r"(bar), "r"(cnt) : "memory");
}
__device__ __forceinline__ void mbar_expect_tx(uint32_t bar, uint32_t bytes) {
    asm volatile("mbarrier.arrive.expect_tx.shared::cta.b64 _, [%0], %1;" ::"r"(bar), "r"(bytes) : "memory");
}
__device__ __forceinline__ void mbar_arrive(uint32_t bar) {
    asm volatile("mbarrier.arrive.shared::cta.b64 _, [%0];" ::"r"(bar) : "memory");
}
__device__ __forceinline__ bool mbar_try(uint32_t bar, uint32_t parity) {
    uint32_t ok;
    asm volatile("{\n.reg .pred p;\nmbarrier.try_wait.parity.shared::cta.b64 p, [%1], %2;\nselp.u32 %0, 1, 0, p;\n}"
                 : "=r"(ok) : "r"(bar), "r"(parity) : "memory");
    return ok;
}
__device__ __forceinline__ void mbar_wait(uint32_t bar, uint32_t parity) {
    asm volatile("{\n.reg .pred p;\nAGAIN:\nmbarrier.try_wait.parity.shared::cta.b64 p, [%0], %1;\n@!p bra AGAIN;\n}"
                 ::"r"(bar), "r"(parity) : "memory");
}
__device__ __forceinline__ void tma_2d(uint32_t dst, const CUtensorMap* m, uint32_t bar, int c0, int c1) {
    asm volatile("cp.async.bulk.tensor.2d.shared::cluster.global.mbarrier::complete_tx::bytes [%0], [%1, {%3, %4}], [%2];"
                 ::"r"(dst), "l"(m), "r"(bar), "r"(c0), "r"(c1) : "memory");
}
__device__ __forceinline__ void bulk_load(uint32_t dst, const void* src, uint32_t bytes, uint32_t bar) {
    asm volatile("cp.async.bulk.shared::cluster.global.mbarrier::complete_tx::bytes [%0], [%1], %2, [%3];"
                 ::"r"(dst), "l"(src), "r"(bytes), "r"(bar) : "memory");
}
__device__ __forceinline__ void bulk_store(void* dst, uint32_t src, uint32_t bytes) {
    asm volatile("cp.async.bulk.global.shared::cta.bulk_group [%0], [%1], %2;" ::"l"(dst), "r"(src), "r"(bytes) : "memory");
}
__device__ __forceinline__ void tma_3d(uint32_t dst, const CUtensorMap* m, uint32_t bar, int c0, int c1, int c2) {
    asm volatile("cp.async.bulk.tensor.3d.shared::cluster.global.mbarrier::complete_tx::bytes [%0], [%1, {%3, %4, %5}], [%2];"
                 ::"r"(dst), "l"(m), "r"(bar), "r"(c0), "r"(c1), "r"(c2) : "memory");
}
__device__ __forceinline__ void fence_async_smem() { asm volatile("fence.proxy.async.shared::cta;" ::: "memory"); }
__device__ __forceinline__ void wg_fence() { asm volatile("wgmma.fence.sync.aligned;" ::: "memory"); }
__device__ __forceinline__ void wg_commit() { asm volatile("wgmma.commit_group.sync.aligned;" ::: "memory"); }
template <int N> __device__ __forceinline__ void wg_wait() { asm volatile("wgmma.wait_group.sync.aligned %0;" ::"n"(N) : "memory"); }
__device__ __forceinline__ void bar_sync(int id, int n) { asm volatile("bar.cta.sync %0, %1;" ::"r"(id), "r"(n) : "memory"); }
__device__ __forceinline__ void bar_arrive(int id, int n) { asm volatile("bar.cta.arrive %0, %1;" ::"r"(id), "r"(n) : "memory"); }

__device__ constexpr uint32_t desc_lo(uint32_t addr, uint32_t lbo) { return (addr >> 4) | ((lbo >> 4) << 16); }
__device__ __forceinline__ bool elect_one() {
    uint32_t p;
    asm volatile("{\n.reg .pred p;\nelect.sync _|p, 0xffffffff;\nselp.u32 %0, 1, 0, p;\n}" : "=r"(p));
    return p;
}
__device__ __forceinline__ uint32_t ld_relaxed4(const void* p) {
    uint32_t v;
    asm volatile("ld.relaxed.gpu.global.u32 %0, [%1];" : "=r"(v) : "l"(p) : "memory");
    return v;
}
__device__ __forceinline__ void st_relaxed4(void* p, uint32_t v) {
    asm volatile("st.relaxed.gpu.global.u32 [%0], %1;" ::"l"(p), "r"(v) : "memory");
}
template <int N = 1>
__device__ __forceinline__ void red_inc(unsigned* p, unsigned after) {
    asm volatile("red.relaxed.gpu.global.add.u32 [%0], %2;" ::"l"(p), "r"(after), "n"(N) : "memory");
}
__device__ __forceinline__ uint32_t lds4(uint32_t a) {
    uint32_t v;
    asm volatile("ld.shared.u32 %0, [%1];" : "=r"(v) : "r"(a) : "memory");
    return v;
}
__device__ __forceinline__ float2 lds8f(uint32_t a) {
    float2 v;
    asm volatile("ld.shared.v2.f32 {%0, %1}, [%2];" : "=f"(v.x), "=f"(v.y) : "r"(a) : "memory");
    return v;
}
__device__ __forceinline__ void sts4(uint32_t a, uint32_t v) { asm volatile("st.shared.u32 [%0], %1;" ::"r"(a), "r"(v) : "memory"); }
__device__ __forceinline__ uint32_t hmul2(uint32_t a, uint32_t b) {
    uint32_t d;
    asm("mul.rn.bf16x2 %0, %1, %2;" : "=r"(d) : "r"(a), "r"(b));
    return d;
}
__device__ __forceinline__ uint32_t hadd2(uint32_t a, uint32_t b) {
    uint32_t d;
    asm("add.rn.bf16x2 %0, %1, %2;" : "=r"(d) : "r"(a), "r"(b));
    return d;
}
__device__ __forceinline__ uint32_t hfma2(uint32_t a, uint32_t b, uint32_t c) {
    uint32_t d;
    asm("fma.rn.bf16x2 %0, %1, %2, %3;" : "=r"(d) : "r"(a), "r"(b), "r"(c));
    return d;
}
__device__ __forceinline__ uint4 ld_relaxed16(const void* p) {
    uint4 v;
    asm volatile("{\n.reg .b128 t;\n.reg .b64 lo, hi;\nld.relaxed.gpu.global.b128 t, [%4];\nmov.b128 {lo, hi}, t;\n"
                 "mov.b64 {%0, %1}, lo;\nmov.b64 {%2, %3}, hi;\n}" : "=r"(v.x), "=r"(v.y), "=r"(v.z), "=r"(v.w) : "l"(p) : "memory");
    return v;
}
__device__ __forceinline__ void st_relaxed16(void* p, uint32_t a, uint32_t b, uint32_t c, uint32_t d) {
    uint64_t lo = (uint64_t)a | ((uint64_t)b << 32), hi = (uint64_t)c | ((uint64_t)d << 32);
    asm volatile("{\n.reg .b128 t;\nmov.b128 t, {%1, %2};\nst.relaxed.gpu.global.b128 [%0], t;\n}" ::"l"(p), "l"(lo), "l"(hi) : "memory");
}
__device__ __forceinline__ void st_relaxed8(void* p, uint32_t a, uint32_t b) {
    asm volatile("{\n.reg .b64 t;\nmov.b64 t, {%1, %2};\nst.relaxed.gpu.global.b64 [%0], t;\n}" ::"l"(p), "r"(a), "r"(b) : "memory");
}
__device__ __forceinline__ uint2 ld_relaxed8(const void* p) {
    uint2 v;
    asm volatile("{\n.reg .b64 t;\nld.relaxed.gpu.global.b64 t, [%2];\nmov.b64 {%0, %1}, t;\n}" : "=r"(v.x), "=r"(v.y) : "l"(p) : "memory");
    return v;
}
__device__ __forceinline__ uint4 ld_nc16(const void* p) {
    uint4 v;
    asm volatile("ld.global.L1::no_allocate.v4.u32 {%0, %1, %2, %3}, [%4];" : "=r"(v.x), "=r"(v.y), "=r"(v.z), "=r"(v.w) : "l"(p) : "memory");
    return v;
}
__device__ __forceinline__ uint2 ld_nc8(const void* p) {
    uint2 v;
    asm volatile("ld.global.nc.L1::no_allocate.v2.u32 {%0, %1}, [%2];" : "=r"(v.x), "=r"(v.y) : "l"(p));
    return v;
}
__device__ __forceinline__ uint4 lds16(uint32_t a) {
    uint4 v;
    asm volatile("ld.shared.v4.u32 {%0, %1, %2, %3}, [%4];" : "=r"(v.x), "=r"(v.y), "=r"(v.z), "=r"(v.w) : "r"(a) : "memory");
    return v;
}
__device__ __forceinline__ void sts16(uint32_t a, uint32_t x, uint32_t y, uint32_t z, uint32_t w) {
    asm volatile("st.shared.v4.u32 [%0], {%1, %2, %3, %4};" ::"r"(a), "r"(x), "r"(y), "r"(z), "r"(w) : "memory");
}
__device__ __forceinline__ uint32_t pack2(float lo, float hi) {
    uint32_t r;
    asm("cvt.rn.bf16x2.f32 %0, %1, %2;" : "=r"(r) : "f"(hi), "f"(lo));
    return r;
}
__device__ __forceinline__ uint32_t pack2v(float lo, float hi) {
    uint32_t r;
    asm volatile("cvt.rn.bf16x2.f32 %0, %1, %2;" : "=r"(r) : "f"(hi), "f"(lo));
    return r;
}
__device__ __forceinline__ float bf_lo(uint32_t u) { return __uint_as_float(u << 16); }
__device__ __forceinline__ float bf_hi(uint32_t u) { return __uint_as_float(u & 0xFFFF0000u); }
__device__ __forceinline__ float bf_round(float f) { return __bfloat162float(__float2bfloat16_rn(f)); }
__device__ __forceinline__ uint32_t prmt(uint32_t a, uint32_t sel) {
    uint32_t d;
    asm("prmt.b32 %0, %1, 0, %2;" : "=r"(d) : "r"(a), "r"(sel));
    return d;
}
__device__ __forceinline__ uint32_t movm(uint32_t a) {
    uint32_t d;
    asm volatile("movmatrix.sync.aligned.m8n8.trans.b16 %0, %1;" : "=r"(d) : "r"(a));
    return d;
}
__device__ __forceinline__ void mma16(float (&c)[4], uint32_t a0, uint32_t a1, uint32_t a2, uint32_t a3, uint32_t b0, uint32_t b1) {
    asm volatile("mma.sync.aligned.m16n8k16.row.col.f32.bf16.bf16.f32 {%0,%1,%2,%3}, {%4,%5,%6,%7}, {%8,%9}, {%0,%1,%2,%3};"
                 : "+f"(c[0]), "+f"(c[1]), "+f"(c[2]), "+f"(c[3]) : "r"(a0), "r"(a1), "r"(a2), "r"(a3), "r"(b0), "r"(b1));
}
__device__ __forceinline__ void mma8(float (&c)[4], uint32_t a0, uint32_t a1, uint32_t b0) {
    asm volatile("mma.sync.aligned.m16n8k8.row.col.f32.bf16.bf16.f32 {%0,%1,%2,%3}, {%4,%5}, {%6}, {%0,%1,%2,%3};"
                 : "+f"(c[0]), "+f"(c[1]), "+f"(c[2]), "+f"(c[3]) : "r"(a0), "r"(a1), "r"(b0));
}
__device__ __forceinline__ float ex2(float x) { float y; asm("ex2.approx.ftz.f32 %0, %1;" : "=f"(y) : "f"(x)); return y; }
__device__ __forceinline__ float rcp(float x) { float y; asm("rcp.approx.ftz.f32 %0, %1;" : "=f"(y) : "f"(x)); return y; }
__device__ __forceinline__ float sigmoidf(float z) { return rcp(1.0f + ex2(z * -1.4426950408889634f)); }
__device__ __forceinline__ float u2f(uint32_t u) { return __uint_as_float(u); }
__device__ __forceinline__ uint32_t f2u(float f) { return __float_as_uint(f); }

__device__ __forceinline__ void wgmma_main(float (&d)[96], uint32_t a, uint32_t b, int scale_d) {
    asm volatile("{\n.reg .pred p;\n.reg .b64 da, db;\nsetp.ne.b32 p, %98, 0;\n"
        "mov.b64 da, {%96, 0x40000040};\nmov.b64 db, {%97, 0x40000040};\n"
        "wgmma.mma_async.sync.aligned.m64n192k16.f32.bf16.bf16 "
        "{%0, %1, %2, %3, %4, %5, %6, %7, %8, %9, %10, %11, %12, %13, %14, %15, "
        "%16, %17, %18, %19, %20, %21, %22, %23, %24, %25, %26, %27, %28, %29, %30, %31, "
        "%32, %33, %34, %35, %36, %37, %38, %39, %40, %41, %42, %43, %44, %45, %46, %47, "
        "%48, %49, %50, %51, %52, %53, %54, %55, %56, %57, %58, %59, %60, %61, %62, %63, "
        "%64, %65, %66, %67, %68, %69, %70, %71, %72, %73, %74, %75, %76, %77, %78, %79, "
        "%80, %81, %82, %83, %84, %85, %86, %87, %88, %89, %90, %91, %92, %93, %94, %95}, "
        "da, db, p, 1, 1, 0, 1;\n}\n"
        : "+f"(d[0]), "+f"(d[1]), "+f"(d[2]), "+f"(d[3]), "+f"(d[4]), "+f"(d[5]), "+f"(d[6]), "+f"(d[7]),
          "+f"(d[8]), "+f"(d[9]), "+f"(d[10]), "+f"(d[11]), "+f"(d[12]), "+f"(d[13]), "+f"(d[14]), "+f"(d[15]),
          "+f"(d[16]), "+f"(d[17]), "+f"(d[18]), "+f"(d[19]), "+f"(d[20]), "+f"(d[21]), "+f"(d[22]), "+f"(d[23]),
          "+f"(d[24]), "+f"(d[25]), "+f"(d[26]), "+f"(d[27]), "+f"(d[28]), "+f"(d[29]), "+f"(d[30]), "+f"(d[31]),
          "+f"(d[32]), "+f"(d[33]), "+f"(d[34]), "+f"(d[35]), "+f"(d[36]), "+f"(d[37]), "+f"(d[38]), "+f"(d[39]),
          "+f"(d[40]), "+f"(d[41]), "+f"(d[42]), "+f"(d[43]), "+f"(d[44]), "+f"(d[45]), "+f"(d[46]), "+f"(d[47]),
          "+f"(d[48]), "+f"(d[49]), "+f"(d[50]), "+f"(d[51]), "+f"(d[52]), "+f"(d[53]), "+f"(d[54]), "+f"(d[55]),
          "+f"(d[56]), "+f"(d[57]), "+f"(d[58]), "+f"(d[59]), "+f"(d[60]), "+f"(d[61]), "+f"(d[62]), "+f"(d[63]),
          "+f"(d[64]), "+f"(d[65]), "+f"(d[66]), "+f"(d[67]), "+f"(d[68]), "+f"(d[69]), "+f"(d[70]), "+f"(d[71]),
          "+f"(d[72]), "+f"(d[73]), "+f"(d[74]), "+f"(d[75]), "+f"(d[76]), "+f"(d[77]), "+f"(d[78]), "+f"(d[79]),
          "+f"(d[80]), "+f"(d[81]), "+f"(d[82]), "+f"(d[83]), "+f"(d[84]), "+f"(d[85]), "+f"(d[86]), "+f"(d[87]),
          "+f"(d[88]), "+f"(d[89]), "+f"(d[90]), "+f"(d[91]), "+f"(d[92]), "+f"(d[93]), "+f"(d[94]), "+f"(d[95])
        : "r"(a), "r"(b), "r"(scale_d));
}

__device__ __forceinline__ void wgmma_rem(float (&d)[24], uint32_t a, uint32_t b, int scale_d) {
    asm volatile("{\n.reg .pred p;\n.reg .b64 da, db;\nsetp.ne.b32 p, %26, 0;\n"
        "mov.b64 da, {%24, 0x40000040};\nmov.b64 db, {%25, 0xC0000010};\n"
        "wgmma.mma_async.sync.aligned.m64n48k16.f32.bf16.bf16 "
        "{%0, %1, %2, %3, %4, %5, %6, %7, %8, %9, %10, %11, %12, %13, %14, %15, "
        "%16, %17, %18, %19, %20, %21, %22, %23}, "
        "da, db, p, 1, 1, 0, 1;\n}\n"
        : "+f"(d[0]), "+f"(d[1]), "+f"(d[2]), "+f"(d[3]), "+f"(d[4]), "+f"(d[5]), "+f"(d[6]), "+f"(d[7]),
          "+f"(d[8]), "+f"(d[9]), "+f"(d[10]), "+f"(d[11]), "+f"(d[12]), "+f"(d[13]), "+f"(d[14]), "+f"(d[15]),
          "+f"(d[16]), "+f"(d[17]), "+f"(d[18]), "+f"(d[19]), "+f"(d[20]), "+f"(d[21]), "+f"(d[22]), "+f"(d[23])
        : "r"(a), "r"(b), "r"(scale_d));
}

__device__ __forceinline__ void wgmma_out(float (&d)[80], uint32_t a, uint32_t b, int scale_d) {
    asm volatile("{\n.reg .pred p;\n.reg .b64 da, db;\nsetp.ne.b32 p, %82, 0;\n"
        "mov.b64 da, {%80, 0x50};\nmov.b64 db, {%81, 0x40000040};\n"
        "wgmma.mma_async.sync.aligned.m64n160k16.f32.bf16.bf16 "
        "{%0, %1, %2, %3, %4, %5, %6, %7, %8, %9, %10, %11, %12, %13, %14, %15, "
        "%16, %17, %18, %19, %20, %21, %22, %23, %24, %25, %26, %27, %28, %29, %30, %31, "
        "%32, %33, %34, %35, %36, %37, %38, %39, %40, %41, %42, %43, %44, %45, %46, %47, "
        "%48, %49, %50, %51, %52, %53, %54, %55, %56, %57, %58, %59, %60, %61, %62, %63, "
        "%64, %65, %66, %67, %68, %69, %70, %71, %72, %73, %74, %75, %76, %77, %78, %79}, "
        "da, db, p, 1, 1, 0, 1;\n}\n"
        : "+f"(d[0]), "+f"(d[1]), "+f"(d[2]), "+f"(d[3]), "+f"(d[4]), "+f"(d[5]), "+f"(d[6]), "+f"(d[7]),
          "+f"(d[8]), "+f"(d[9]), "+f"(d[10]), "+f"(d[11]), "+f"(d[12]), "+f"(d[13]), "+f"(d[14]), "+f"(d[15]),
          "+f"(d[16]), "+f"(d[17]), "+f"(d[18]), "+f"(d[19]), "+f"(d[20]), "+f"(d[21]), "+f"(d[22]), "+f"(d[23]),
          "+f"(d[24]), "+f"(d[25]), "+f"(d[26]), "+f"(d[27]), "+f"(d[28]), "+f"(d[29]), "+f"(d[30]), "+f"(d[31]),
          "+f"(d[32]), "+f"(d[33]), "+f"(d[34]), "+f"(d[35]), "+f"(d[36]), "+f"(d[37]), "+f"(d[38]), "+f"(d[39]),
          "+f"(d[40]), "+f"(d[41]), "+f"(d[42]), "+f"(d[43]), "+f"(d[44]), "+f"(d[45]), "+f"(d[46]), "+f"(d[47]),
          "+f"(d[48]), "+f"(d[49]), "+f"(d[50]), "+f"(d[51]), "+f"(d[52]), "+f"(d[53]), "+f"(d[54]), "+f"(d[55]),
          "+f"(d[56]), "+f"(d[57]), "+f"(d[58]), "+f"(d[59]), "+f"(d[60]), "+f"(d[61]), "+f"(d[62]), "+f"(d[63]),
          "+f"(d[64]), "+f"(d[65]), "+f"(d[66]), "+f"(d[67]), "+f"(d[68]), "+f"(d[69]), "+f"(d[70]), "+f"(d[71]),
          "+f"(d[72]), "+f"(d[73]), "+f"(d[74]), "+f"(d[75]), "+f"(d[76]), "+f"(d[77]), "+f"(d[78]), "+f"(d[79])
        : "r"(a), "r"(b), "r"(scale_d));
}

__device__ __forceinline__ void wgmma_own(float (&d)[80], uint32_t a0, uint32_t a1, uint32_t a2, uint32_t a3, uint32_t b, int scale_d) {
    asm volatile("{\n.reg .pred p;\n.reg .b64 db;\nsetp.ne.b32 p, %85, 0;\nmov.b64 db, {%84, 0x40000040};\n"
        "wgmma.mma_async.sync.aligned.m64n160k16.f32.bf16.bf16 "
        "{%0, %1, %2, %3, %4, %5, %6, %7, %8, %9, %10, %11, %12, %13, %14, %15, "
        "%16, %17, %18, %19, %20, %21, %22, %23, %24, %25, %26, %27, %28, %29, %30, %31, "
        "%32, %33, %34, %35, %36, %37, %38, %39, %40, %41, %42, %43, %44, %45, %46, %47, "
        "%48, %49, %50, %51, %52, %53, %54, %55, %56, %57, %58, %59, %60, %61, %62, %63, "
        "%64, %65, %66, %67, %68, %69, %70, %71, %72, %73, %74, %75, %76, %77, %78, %79}, "
        "{%80, %81, %82, %83}, db, p, 1, 1, 1;\n}\n"
        : "+f"(d[0]), "+f"(d[1]), "+f"(d[2]), "+f"(d[3]), "+f"(d[4]), "+f"(d[5]), "+f"(d[6]), "+f"(d[7]),
          "+f"(d[8]), "+f"(d[9]), "+f"(d[10]), "+f"(d[11]), "+f"(d[12]), "+f"(d[13]), "+f"(d[14]), "+f"(d[15]),
          "+f"(d[16]), "+f"(d[17]), "+f"(d[18]), "+f"(d[19]), "+f"(d[20]), "+f"(d[21]), "+f"(d[22]), "+f"(d[23]),
          "+f"(d[24]), "+f"(d[25]), "+f"(d[26]), "+f"(d[27]), "+f"(d[28]), "+f"(d[29]), "+f"(d[30]), "+f"(d[31]),
          "+f"(d[32]), "+f"(d[33]), "+f"(d[34]), "+f"(d[35]), "+f"(d[36]), "+f"(d[37]), "+f"(d[38]), "+f"(d[39]),
          "+f"(d[40]), "+f"(d[41]), "+f"(d[42]), "+f"(d[43]), "+f"(d[44]), "+f"(d[45]), "+f"(d[46]), "+f"(d[47]),
          "+f"(d[48]), "+f"(d[49]), "+f"(d[50]), "+f"(d[51]), "+f"(d[52]), "+f"(d[53]), "+f"(d[54]), "+f"(d[55]),
          "+f"(d[56]), "+f"(d[57]), "+f"(d[58]), "+f"(d[59]), "+f"(d[60]), "+f"(d[61]), "+f"(d[62]), "+f"(d[63]),
          "+f"(d[64]), "+f"(d[65]), "+f"(d[66]), "+f"(d[67]), "+f"(d[68]), "+f"(d[69]), "+f"(d[70]), "+f"(d[71]),
          "+f"(d[72]), "+f"(d[73]), "+f"(d[74]), "+f"(d[75]), "+f"(d[76]), "+f"(d[77]), "+f"(d[78]), "+f"(d[79])
        : "r"(a0), "r"(a1), "r"(a2), "r"(a3), "r"(b), "r"(scale_d));
}

__device__ __forceinline__ void wgmma_vec(float (&d)[8], uint32_t a, uint32_t b, int scale_d) {
    asm volatile("{\n.reg .pred p;\n.reg .b64 da, db;\nsetp.ne.b32 p, %10, 0;\n"
        "mov.b64 da, {%8, 0x40000040};\nmov.b64 db, {%9, 0x14};\n"
        "wgmma.mma_async.sync.aligned.m64n16k16.f32.bf16.bf16 {%0, %1, %2, %3, %4, %5, %6, %7}, da, db, p, 1, 1, 1, 0;\n}\n"
        : "+f"(d[0]), "+f"(d[1]), "+f"(d[2]), "+f"(d[3]), "+f"(d[4]), "+f"(d[5]), "+f"(d[6]), "+f"(d[7])
        : "r"(a), "r"(b), "r"(scale_d));
}

#define TSA(i) do { } while (0)
#define MAP_TILE(b) ((((b) >> 1) & 14) | ((b) & 1))
#define MAP_HG(b) (((b) >> 4 & 14) | ((b) >> 1 & 1))
#define SRCV 4
#define L1_D 300
#define L0_D 300
#define F1_D 0
#define F0_D 200
#define HALFV 0
#define HALF (int)(HALFV == 0 ? bid >> 1 & 1 : HALFV == 1 ? (bid >> 1 ^ bid) & 1 : (bid >> 1 ^ bid >> 4) & 1)
#define GM 0x78A0
#define H_C 1000
#define PV 0
#define LS_T 14450
#define BX 0
#define SETL 0
#define L0_T 14450
#define L1_T 14050
#define F0_T 14650
#define F1_T 14300
#define C5_T 0
#define C6_T (C5_T + 450)
#define C7_T (C6_T + 400)
#define C_O 250
#define FFV 2
#define DFV 0
#define OEV 1
#define B_OFF 0
#define W_S0 2
#define E_V 0
#define MAPV 4
#define GW 0
#define GU_DS (GU_DT * 7 / 11)
#define GU_ST 90
#define X_OFF 350
#define RW_REG 0
#define P2W 4
#define RES_V 2
#define Y2_T 17000
#define ENT_V 0
#define TPF 1
#define SKEW 4
#define PACE 500
#define PACE_W0 (-600)
#define PACE_A 250
#define PACE_B 450
#define RG_ORDER 0x24130
#define GU_T0 3600
#define GU_DT 750
#define RS_T0 9000
#define RS_DT 120
#define EXCH_FIRST 1
#define HALO_D 450
#define PF_UP 4200
#define O_D 0
#define O_DT 300
#define PF_DN 4200
#define PF_DT 450
#define GX_NS 200
#define NRS 1
#define C5_D 0
#define C6_D 100
#define PF_N 4
#define PF_0 4
#define EPF_N 15
#define EPF_M 15
#define EPF_T 900
#define RG1_T0 1700
#define RG1_DT 200
#define RW1_T 0
#define Y_T 15500
#define GL_T 0
#define DN_T0 500
#define DN_DT 68
#define DN_T1 100000
#define DN_D1 45
#define DN_R 5
#define H_T 13300
#define HS_T 13300
#define GL_N 16
#define C1_T 0
#define C0_T 11100
#define RS_N 10
#define SP_W 1
#define PF2_N 0
#define C2_T 0
#define C3_T 0
#define C4_T 0
#define EPF_G 0
#define EPF_H 0
#define UPF 0
#define UPF_D 700
#define UPF_T 3200
#define UPF_S 90
#define RS_E 0
#define RS_D 0
#define GL15 1
#define RS_S 0
#define CAND_T 9000

__device__ __forceinline__ uint32_t keep(uint32_t v) { return __shfl_xor_sync(0xffffffffu, v, 0); }
__device__ __forceinline__ uint32_t ukeep(uint32_t v) { return __shfl_sync(0xffffffffu, v, 0); }
__device__ __forceinline__ void ldsm2(uint32_t* d, uint32_t a) {
    asm volatile("ldmatrix.sync.aligned.m8n8.x4.shared.b16 {%0,%1,%2,%3}, [%8];\nldmatrix.sync.aligned.m8n8.x4.shared.b16 {%4,%5,%6,%7}, [%9];"
                 : "=r"(d[0]), "=r"(d[1]), "=r"(d[2]), "=r"(d[3]), "=r"(d[4]), "=r"(d[5]), "=r"(d[6]), "=r"(d[7])
                 : "r"(a), "r"(a ^ 32) : "memory");
}
__device__ __forceinline__ void ldsm_t(uint32_t (&d)[4], uint32_t a) {
    asm volatile("ldmatrix.sync.aligned.m8n8.x4.trans.shared.b16 {%0,%1,%2,%3}, [%4];"
                 : "=r"(d[0]), "=r"(d[1]), "=r"(d[2]), "=r"(d[3]) : "r"(a) : "memory");
}
template <bool SWP, int SEG, int E>
__device__ __forceinline__ void pack_blocks(uint32_t (&d)[10], const float (&am)[96], const float (&ar)[24]) {
#pragma unroll
    for (int t = 0; t < 10; t++) {
        const float* p = (SWP ? t < 2 : t >= 8) ? ar + (SEG * 2 + (t & 1)) * 4 + E : am + (SEG * 8 + t - (SWP ? 2 : 0)) * 4 + E;
        d[t] = pack2v(p[0], p[1]);
    }
}
__device__ __forceinline__ int src_of(int i, int hg) {
    return i == 0 ? hg : (0x75316240u >> (i - (i <= (hg >> 2 | hg & 2))) * 4 & 7) ^ (hg & 1);
}

__device__ __forceinline__ uint32_t o_buf(int i) { return __byte_perm(0xD199ADA3u, 0xC7BDu, i - 1 - NRS | 0x7770) << 10; }
__device__ constexpr uint32_t wo_buf(int i) { return SM_W + ((0x10342103u >> i * 4) & 7) * 30720; }

template <int N>
__device__ __forceinline__ void poll(uint4 (&a)[N], const uint4* p, int stride) {
    bool bad;
    do {
        bad = false;
#pragma unroll
        for (int s = 0; s < N; s++) a[s] = ld_relaxed16(p + s * stride);
#pragma unroll
        for (int s = 0; s < N; s++) bad |= a[s].w == SENT;
    } while (__any_sync(0xffffffffu, bad));
}
__device__ __forceinline__ void pace(unsigned t0, int t) {
    asm volatile("{\n.reg .pred p;\n.reg .s32 d;\nAGAIN:\nmov.u32 d, %%clock;\nsub.s32 d, d, %0;\nsetp.lt.s32 p, d, 0;\n"
                 "@p nanosleep.u32 20;\n@p bra AGAIN;\n}" ::"r"(t0 + t) : "memory");
}
__device__ __forceinline__ void l2_prefetch(const void* p) { asm volatile("prefetch.global.L2 [%0];" ::"l"(p) : "memory"); }

template <int N>
__device__ __forceinline__ bool landed(const uint4* w, int lane) {
    uint32_t a = 0;
#pragma unroll
    for (int i = 0; i < N; i++) a ^= w[i].w;
    return __ballot_sync(0xffffffffu, lane == 0 || a == 0) && lane == 0;
}
__device__ __forceinline__ void swiglu(const uint4 (&a)[4], uint32_t dst, uint32_t stride) {
    const float g0 = bf_round((u2f(a[0].x) + u2f(a[1].x)) + (u2f(a[2].x) + u2f(a[3].x)));
    const float g1 = bf_round((u2f(a[0].y) + u2f(a[1].y)) + (u2f(a[2].y) + u2f(a[3].y)));
    const float u0 = bf_round((u2f(a[0].z) + u2f(a[1].z)) + (u2f(a[2].z) + u2f(a[3].z)));
    const float u1 = bf_round((u2f(a[0].w) + u2f(a[1].w)) + (u2f(a[2].w) + u2f(a[3].w)));
    const uint32_t h = pack2(bf_round(g0 * sigmoidf(g0)) * u0, bf_round(g1 * sigmoidf(g1)) * u1);
    asm volatile("st.shared.u16 [%0], %2;\nst.shared.u16 [%1], %3;" ::"r"(dst), "r"(dst + stride), "h"((uint16_t)h), "h"((uint16_t)(h >> 16)) : "memory");
}
template <int N>
__device__ __forceinline__ float4 vec_mma(const uint4 (&w)[N], const uint32_t* x, uint32_t sel) {
    float c[4][4] = {};
    const uint32_t s[4] = {sel, sel >> 16, sel + ((sel & 0x10101010u) >> 3) * 17, (sel + ((sel & 0x10101010u) >> 3) * 17) >> 16};
#pragma unroll
    for (int i = 0; i < N; i++)
        mma16(c[i & 3], w[i].x, w[i].y, w[i].z, w[i].w, prmt(x[i >> 1], s[(i & 1) * 2]), prmt(x[i >> 1], s[(i & 1) * 2 + 1]));
    return make_float4((c[0][0] + c[1][0]) + (c[2][0] + c[3][0]), (c[0][1] + c[1][1]) + (c[2][1] + c[3][1]),
                       (c[0][2] + c[1][2]) + (c[2][2] + c[3][2]), (c[0][3] + c[1][3]) + (c[2][3] + c[3][3]));
}

__global__ void __launch_bounds__(512, 1) fused_kernel(const __grid_constant__ Params P) {
    extern __shared__ __align__(1024) uint8_t smem_raw[];
    const unsigned t_start = clock();
    const int tid = threadIdx.x, lane = tid & 31;
    unsigned sm, bid;
    asm("mov.u32 %0, %%smid;" : "=r"(sm));
    const CUtensorMap* mx = &P.x;
    asm volatile("" : "+l"(mx));
    if ((unsigned)(tid - 480) < EPF_N) l2_prefetch(P.wp + (tid * 132 + sm) * 64 - 480 * 132 * 64);
    const int warp = __shfl_sync(0xffffffffu, threadIdx.x >> 5, 0);
    constexpr uint32_t rk = 0;
    asm("{\n.reg .pred p;\n.reg .b32 t, u;\nshr.u32 t, %1, 1;\nmad.lo.s32 u, t, 14, -928;\nmad.lo.s32 t, t, 37, -925;\nmax.s32 t, t, 0;\n"
        "shr.u32 t, t, 7;\nand.b32 t, t, 14;\nsetp.ge.u32 p, %1, 124;\nselp.b32 t, u, t, p;\nadd.s32 %0, %1, t;\n}" : "=r"(bid) : "r"(sm));
    bid ^= (GM >> (bid & 14) & 6) ^ BX;
    const int hg = MAP_HG(bid), par = bid & 1, p0 = (MAP_TILE(bid) >> 1) * 128;
    const bool swp = (hg & 3) == 3;
    const int wcm = hg * 80 + (swp ? 16 : 0), wcr = hg * 80 + (swp ? 0 : 64);
    if (warp == 0) {
        if (elect_one()) {
#pragma unroll
            for (int i = 0; i < 4; i++) mbar_init(SM_BAR + i * 8, 1);
            asm volatile("fence.mbarrier_init.release.cluster;" ::: "memory");
            if (bid < NCTA) {
                mbar_expect_tx(B_FULL, 15360 + 8192);
                tma_3d(SM_X + 8192, mx, B_FULL, 0, par, p0 + 64);
                tma_3d(SM_W, mx + 2, B_FULL, wcm, 0, 0);
                tma_3d(SM_W + 12288, mx + 3, B_FULL, wcr, 0, 0);
                TS(40);
                mbar_expect_tx(B_XL0, 8192);
                tma_3d(SM_X, mx, B_XL0, 0, par, p0);
                mbar_expect_tx(B_FULL + 8, 15360);
                tma_3d(SM_W + 15360, mx + 2, B_FULL + 8, wcm, 32, 0);
                tma_3d(SM_W + 15360 + 12288, mx + 3, B_FULL + 8, wcr, 32, 0);
            }
        }
    }
    if ((unsigned)(warp - 1) < 6 && elect_one()) {
#pragma unroll
        for (int i = 0; i < 4; i++) mbar_init(SM_BAR + warp * 32 + i * 8, warp < 4 ? 1 : warp < 6 ? 2 : 4);
        asm volatile("fence.mbarrier_init.release.cluster;" ::: "memory");
    }
    asm volatile("" : "+r"(bid));
    const int role = bid >= NCTA ? -1 : warp, e = sm & 3;
    const int tile = MAP_TILE(bid), cid = tile * 8 + hg;
    uint4* const sc = g_sc + cid * SC_SIZE;
    __syncthreads();

    if (role < 0) {
        const int half = warp >> 3;
        if (!NFFN) {
            if (tid == 0) red_inc<NCTA / NEXTRA>(g_cnt, 0);
            return;
        }
        uint32_t wf[DN_R][5][4], la[5];
        auto rows = [&](uint32_t l) {
#pragma unroll
            for (int i = 0; i < 5; i++) {
                const uint32_t c = (warp & 7) * 10 + 2 * i + (l >> 3 & 1);
                la[i] = SB + half * 20480 + (c >> 3) * 2048 + (l & 7) * 128 + (l >> 4) * 1024 + (((c ^ l) & 7) << 4);
            }
        };
        rows(lane);
        auto fetch = [&](int j, int n, uint32_t bar) {
#pragma unroll 1
            for (int h = 0; h < n; h++) {
                pace(t_start, min(DN_T0 + (j * 20 + h * 10 + warp) * DN_DT, DN_T1 + (j * 20 + h * 10 + warp) * DN_D1));
                tma_2d(SB + (j % 5) * 40960 + h * 20480 + warp * 2048, &P.down, bar, warp * 64, e * 272 + (j + h * 9) * 16);
            }
        };
        if (warp < 10 && elect_one()) {
            if (warp <= DN_R) mbar_expect_tx(B_FULL + warp * 8, warp < DN_R ? 40960 : (17 - 2 * DN_R) * 20480);
#pragma unroll 1
            for (int j = 0; j < 5; j++) fetch(j, 2, B_FULL + j * 8);
        }
        const uint32_t tag = (ukeep(ld_relaxed4(g_cnt)) * 8 + 2048) & 0xF800u;
#pragma unroll
        for (int j = 0; j < DN_R; j++) {
            uint32_t any = 0;
            mbar_wait(B_FULL + j * 8, 0);
#pragma unroll
            for (int i = 0; i < 5; i++) {
                ldsm_t(wf[j][i], la[i] + j * 40960);
                any ^= wf[j][i][3];
            }
            if (j < 4) {
                if (__syncthreads_count(any == 0) == 1000) fault();
                if (warp < 10 && elect_one()) fetch(j + 5, j < 3 ? 2 : 1, B_FULL + DN_R * 8);
                if (j == 0 && tid == 0) red_inc<NCTA / NEXTRA>(g_cnt, tag);
            }
            TSX(warp == 0 && j == 0 ? 0 : warp == 0 && j == 3 ? 1 : 63);
        }
        if (warp < 9) {
            pace(t_start, H_T - H_C);
            uint4 a[4];
            do {
                a[0] = ld_relaxed16(g_cand + lane * 2);
                a[1] = ld_relaxed16(g_cand + lane * 2 + 64);
            } while (__any_sync(0xffffffffu, ((a[0].x ^ tag) | (a[0].z ^ tag) | (a[1].x ^ tag) | (a[1].z ^ tag)) & 0xF800u));
            const int u = min(tid, 271), f = e * 272 + u;
            pace(t_start, H_T);
            TSX(warp == 0 ? 3 : 63);
            poll<4>(a, g_sc + (f >> 6) * 4 * SC_SIZE + SC_GU + (f & 63), SC_SIZE);
            TSX(warp == 0 ? 4 : warp == 8 ? 5 : 63);
            swiglu(a, SM_RED + (u >> 4) * 64 + (u & 6) * 4 + (u & 8) / 2 + (u & 1) * 2, 32);
        }
        rows(keep(lane));
        mbar_wait(B_FULL + DN_R * 8, 0);
        TSX(warp == 15 ? 2 : 63);
        __syncthreads();
        float c[5][4] = {};
#pragma unroll
        for (int j = 0; j < 9; j++) {
            if (j == 8 && half) break;
            const float2 b = lds8f(SM_RED + half * 576 + j * 64 + (lane & 7) * 8);
            if (j == 1) TSX(warp == 0 ? 6 : 63);
#pragma unroll
            for (int i = 0; i < 5; i++) {
                if (j >= DN_R) ldsm_t(wf[j % DN_R][i], la[i] + (j % 5) * 40960);
                mma16(c[i], wf[j % DN_R][i][0], wf[j % DN_R][i][1], wf[j % DN_R][i][2], wf[j % DN_R][i][3], f2u(b.x), f2u(b.y));
            }
        }
        const uint32_t ra = SB + 7 * 20480 + half * 5248 + (lane & 1) * 2624 + (warp & 7) * 320 + (lane & 2) * 16 + (lane >> 2) * 4;
#pragma unroll
        for (int i = 0; i < 5; i++) sts4(ra + i * 64, f2u((lane & 2) ? ((lane & 1) ? c[i][3] : c[i][2]) : ((lane & 1) ? c[i][1] : c[i][0])));
        TSX(warp == 0 ? 7 : 63);
        __syncthreads();
        if (warp < 10) {
            const uint32_t ya = SB + 7 * 20480 + (warp & 1) * 2624 + (warp >> 1) * 512 + lane * 16;
            const uint4 y0 = lds16(ya), y1 = lds16(ya + 5248);
            st_relaxed16(g_sc + (e * 5 + (warp >> 1)) * SC_SIZE + SC_Y + (tid & 63), f2u(u2f(y0.x) + u2f(y1.x)), f2u(u2f(y0.y) + u2f(y1.y)),
                         f2u(u2f(y0.z) + u2f(y1.z)), f2u(u2f(y0.w) + u2f(y1.w)));
        }
    } else if (role < 8) {
        asm volatile("setmaxnreg.inc.sync.aligned.u32 192;");
        const int wg = warp >> 2;
        const bool leader = (tid & 127) == 0;
        float am[96], ar[24];
        if (wg == 0) mbar_wait(B_XL0, 0);
        bool rel = false;
        uint32_t nb[40];
        const int odd = (hg >> 1) & 1, kba = ukeep(RES_V && wg != HALF ? 99 : ((hg >> 1) * 5 + 1) >> 1), kbr = ukeep(kba + 2 - odd * 3);
        const int kbs = wg ? -1 : (20 - SKEW) / 2;
        const uint32_t xrow = keep(SM_X + (warp * 16 + (lane & 15)) * 128 + (((lane >> 4) ^ (lane & 7)) << 4));
#pragma unroll 1
        for (int kb = 0; kb < 10; kb++) {
            const uint32_t fb = B_FULL + (kb & 3) * 16, wo = (kb & 3) * 1920, ph = (kb >> 2) & 1;
            const uint32_t xo = desc_lo(SM_X, 16) + wg * 512 + (kb & 3) * 1024;
#pragma unroll
            for (int h = 0; h < 2; h++) {
                mbar_wait(fb + h * 8, ph);
                if (kb == 0 && h == 0) TS(warp == 0 ? 0 : warp == 4 ? 16 : 63);
                TS2(warp == P2W ? kb * 2 + h : 63);
                if (RES_V == 2) {
                    const uint32_t xa = (xrow ^ h * 64) + (kb & 3) * 16384;
                    if (kb == kba) ldsm2(nb + h * 8, xa);
                    if (kb == kba + 1) ldsm2(nb + 16 + h * 8, xa);
                    if (h == 0 && kb == kbr) ldsm2(nb + 32, xa ^ (odd * 64));
                } else if (h == 0) {
                    const uint32_t xa = xrow + (kb & 3) * 16384;
                    if (kb == kba) { ldsm2(nb, xa); ldsm2(nb + 8, xa ^ 64); }
                    if (kb == kba + 1) { ldsm2(nb + 16, xa); ldsm2(nb + 24, xa ^ 64); }
                    if (kb == kbr) ldsm2(nb + 32, xa ^ (odd * 64));
                }
                wg_wait<1>();
                if (rel && (h == 0 || kb != kbs)) mbar_arrive(B_EMPTY + ((kb * 16 - 16) & 48) + h * 8);
                if (h == 0 && kb == kbs) {
                    wg_wait<0>();
                    if (rel) mbar_arrive(B_EMPTY + ((19 - SKEW) & 7) * 8);
                    bar_sync(5, 256);
                }
                wg_fence();
                wgmma_main(am, xo + h * 4, desc_lo(SM_W + h * 15360, 4096) + wo, h || kb);
                wgmma_rem(ar, xo + h * 4, desc_lo(SM_W + h * 15360 + 12288, 1024) + wo, h || kb);
                wgmma_main(am, xo + h * 4 + 2, desc_lo(SM_W + h * 15360 + 2048, 4096) + wo, 1);
                wgmma_rem(ar, xo + h * 4 + 2, desc_lo(SM_W + h * 15360 + 12288 + 512, 1024) + wo, 1);
                wg_commit();
            }
            rel = leader;
        }
        if (wg == 1) bar_arrive(5, 256);
        mbar_wait(B_XE + 16, 0);
        mbar_wait(B_RG2, 0);
        mbar_wait(B_EMPTY + 5 * 8, 1);
        wg_wait<0>();
        if (leader) mbar_arrive(B_EMPTY + 3 * 8);
        TS(warp == 0 ? 2 : warp == 4 ? 18 : 63);
        TS2(warp == 0 ? 41 : warp == 4 ? 40 : 63);

        uint32_t kl[10], kh[10], vl[10], vh[10], ql[10], qh[10], kp[10], vp[10];
        if (swp) {
            pack_blocks<true, 1, 2>(kh, am, ar);
            pack_blocks<true, 2, 2>(vh, am, ar);
        } else {
            pack_blocks<false, 1, 2>(kh, am, ar);
            pack_blocks<false, 2, 2>(vh, am, ar);
        }
        const int w4 = warp & 3;
        const uint32_t pbuf = (wg ? SM_HALO1 : SM_HALO) + w4 * 2560 + lane * 16;
        const uint32_t hbuf = warp == 3 ? SM_HALO1 + lane * 16 : pbuf + 2560;
        {
            const uint32_t ex[20] = {kh[0], kh[1], kh[3], kh[4], kh[5], kh[6], kh[8], kh[9], kh[2], kh[7],
                                     vh[0], vh[1], vh[2], vh[3], vh[4], vh[5], vh[6], vh[7], vh[8], vh[9]};
            if (warp == 7) {
                uint4* const hp = sc + SC_HALO + lane;
#pragma unroll
                for (int s = 0; s < 5; s++) st_relaxed16(hp + s * 32, ex[4 * s], ex[4 * s + 1], ex[4 * s + 2], ex[4 * s + 3]);
                bar_arrive(12, 64);
            } else {
#pragma unroll
                for (int s = 0; s < 5; s++) sts16(hbuf + s * 512, ex[4 * s], ex[4 * s + 1], ex[4 * s + 2], ex[4 * s + 3]);
            }
        }
        TS(warp == 7 ? 22 : warp == 3 ? 23 : 63);
        if (warp == 3) bar_arrive(11, 64);
        if (swp) {
            pack_blocks<true, 2, 0>(vl, am, ar);
            pack_blocks<true, 0, 0>(ql, am, ar);
            pack_blocks<true, 0, 2>(qh, am, ar);
            pack_blocks<true, 1, 0>(kl, am, ar);
        } else {
            pack_blocks<false, 2, 0>(vl, am, ar);
            pack_blocks<false, 0, 0>(ql, am, ar);
            pack_blocks<false, 0, 2>(qh, am, ar);
            pack_blocks<false, 1, 0>(kl, am, ar);
        }
#pragma unroll
        for (int t = 0; t < 10; t++) { vl[t] = movm(vl[t]); vh[t] = movm(vh[t]); }
        mbar_wait(B_RS, 0);
        mbar_wait(B_GT, 0);
        const float g0 = bf_hi(lds4(SM_GATE + warp * 64 + (lane & 28))), g1 = bf_hi(lds4(SM_GATE + 32 + warp * 64 + (lane & 28)));

        const int r = lane >> 2, cq = lane & 3;
        const bool no_prev = warp == 0 && tile < 2, low = cq < 2;
        const bool le0 = 2 * cq <= r, le1 = 2 * cq + 1 <= r;
        const uint32_t mle = (le0 ? 0xFFFFu : 0u) | (le1 ? 0xFFFF0000u : 0u);
        const float scl = 0.22360679774997896f * 1.4426950408889634f;
        uint32_t pl[4], ph[4];
        {
            float sl[4][4], sh[4][4], sp[4][4];
            auto exchange = [&]() {
            TSA(warp == 1 ? 26 : 63);
            bar_sync(6 + wg, 128);
            if (w4 == 0) bar_sync(8 + wg * 3, 64);
            {
                const uint4 a = lds16(pbuf), b = lds16(pbuf + 512), c = lds16(pbuf + 1024), d = lds16(pbuf + 1536), e = lds16(pbuf + 2048);
                kp[0] = a.x; kp[1] = a.y; kp[3] = a.z; kp[4] = a.w; kp[5] = b.x; kp[6] = b.y; kp[8] = b.z; kp[9] = b.w;
                kp[2] = c.x; kp[7] = c.y; vp[0] = c.z; vp[1] = c.w; vp[2] = d.x; vp[3] = d.y; vp[4] = d.z; vp[5] = d.w;
                vp[6] = e.x; vp[7] = e.y; vp[8] = e.z; vp[9] = e.w;
            }
            TSA(warp == 0 ? 3 : warp == 4 ? 19 : warp == 5 ? 27 : 63);
            };
            if (EXCH_FIRST) exchange();
#pragma unroll
            for (int h = 0; h < 4; h++) {
                const int ta = (h >> 1) * 5 + (h & 1) * 3, tc = (h >> 1) * 5 + 2;
                const uint32_t ml = low != (h & 1) ? ql[tc] : 0u, mh = low != (h & 1) ? qh[tc] : 0u;
#pragma unroll
                for (int e = 0; e < 4; e++) sl[h][e] = sh[h][e] = sp[h][e] = 0.f;
                mma16(sl[h], ql[ta], qh[ta], ql[ta + 1], qh[ta + 1], kl[ta], kl[ta + 1]);
                mma16(sh[h], ql[ta], qh[ta], ql[ta + 1], qh[ta + 1], kh[ta], kh[ta + 1]);
                mma8(sl[h], ml, mh, kl[tc]);
                mma8(sh[h], ml, mh, kh[tc]);
            }
            if (!EXCH_FIRST) exchange();
#pragma unroll
            for (int h = 0; h < 4; h++) {
                const int ta = (h >> 1) * 5 + (h & 1) * 3, tc = (h >> 1) * 5 + 2;
                mma16(sp[h], ql[ta], qh[ta], ql[ta + 1], qh[ta + 1], kp[ta], kp[ta + 1]);
                mma8(sp[h], low != (h & 1) ? ql[tc] : 0u, low != (h & 1) ? qh[tc] : 0u, kp[tc]);
            }
#pragma unroll
            for (int t = 0; t < 10; t++) vp[t] = movm(vp[t]);
#pragma unroll
            for (int h = 0; h < 4; h++) {
                if (no_prev) sp[h][0] = sp[h][1] = -1e9f / 0.22360679774997896f;
                const float a0 = le0 ? sl[h][0] : sp[h][0], a1 = le1 ? sl[h][1] : sp[h][1];
                const float b0 = le0 ? sh[h][2] : sl[h][2], b1 = le1 ? sh[h][3] : sl[h][3];
                float ma = fmaxf(a0, a1), mb = fmaxf(b0, b1);
                ma = fmaxf(ma, __shfl_xor_sync(0xffffffffu, ma, 1));
                mb = fmaxf(mb, __shfl_xor_sync(0xffffffffu, mb, 1));
                ma = fmaxf(ma, __shfl_xor_sync(0xffffffffu, ma, 2)) * -scl;
                mb = fmaxf(mb, __shfl_xor_sync(0xffffffffu, mb, 2)) * -scl;
                pl[h] = pack2(ex2(fmaf(a0, scl, ma)), ex2(fmaf(a1, scl, ma)));
                ph[h] = pack2(ex2(fmaf(b0, scl, mb)), ex2(fmaf(b1, scl, mb)));
            }
        }
        TSA(warp == 0 ? 4 : warp == 4 ? 20 : warp == 5 ? 28 : 63);
        uint32_t ol[10], oh[10];
        {
            uint32_t* const po = reinterpret_cast<uint32_t*>(sc + SC_O + warp * 160) + lane;
            const uint32_t ONES = 0x3F803F80u;
            float o[12][4];
#pragma unroll
            for (int hp = 0; hp < 2; hp++) {
#pragma unroll
                for (int h = hp * 2; h < hp * 2 + 2; h++) {
                    const int ta = (h >> 1) * 5 + (h & 1) * 3, tc = (h >> 1) * 5 + 2;
                    const bool mine = (lane < 16) != (h & 1);
                    const uint32_t a0 = pl[h] & mle, a1 = ph[h] & ~mle, a3 = ph[h] & mle, ap = pl[h] & ~mle;
#pragma unroll
                    for (int i = 0; i < 3; i++) o[h * 3 + i][0] = o[h * 3 + i][1] = o[h * 3 + i][2] = o[h * 3 + i][3] = 0.f;
                    mma16(o[h * 3 + 2], a0, a1, 0u, a3, mine ? vl[tc] : ONES, mine ? vh[tc] : ONES);
                    mma16(o[h * 3], a0, a1, 0u, a3, vl[ta], vh[ta]);
                    mma16(o[h * 3 + 1], a0, a1, 0u, a3, vl[ta + 1], vh[ta + 1]);
                    mma8(o[h * 3 + 2], ap, 0u, mine ? vp[tc] : ONES);
                    mma8(o[h * 3], ap, 0u, vp[ta]);
                    mma8(o[h * 3 + 1], ap, 0u, vp[ta + 1]);
                }
                if (hp && wg != HALF) bar_arrive(2, 256);
                const float (&oa)[4] = o[hp * 6 + 2], (&ob)[4] = o[hp * 6 + 5];
                const float hl = rcp(low ? ob[0] : oa[0]) * g0, hh = rcp(low ? ob[2] : oa[2]) * g1;
                const float gl = __shfl_xor_sync(0xffffffffu, hl, 2), gh = __shfl_xor_sync(0xffffffffu, hh, 2);
                const float ial = low ? gl : hl, iah = low ? gh : hh, ibl = low ? hl : gl, ibh = low ? hh : gh;
#pragma unroll
                for (int i = 0; i < 2; i++) {
                    ol[hp * 5 + i] = pack2(o[hp * 6 + i][0] * ial, o[hp * 6 + i][1] * ial);
                    oh[hp * 5 + i] = pack2(o[hp * 6 + i][2] * iah, o[hp * 6 + i][3] * iah);
                    ol[hp * 5 + 3 + i] = pack2(o[hp * 6 + 3 + i][0] * ibl, o[hp * 6 + 3 + i][1] * ibl);
                    oh[hp * 5 + 3 + i] = pack2(o[hp * 6 + 3 + i][2] * ibh, o[hp * 6 + 3 + i][3] * ibh);
                }
                ol[hp * 5 + 2] = pack2((low ? oa[0] : ob[0]) * gl, (low ? oa[1] : ob[1]) * gl);
                oh[hp * 5 + 2] = pack2((low ? oa[2] : ob[2]) * gh, (low ? oa[3] : ob[3]) * gh);
#pragma unroll
                for (int t = hp * 5; t < hp * 5 + 5; t++) {
                    st_relaxed4(po + t * 32, ol[t]);
                    st_relaxed4(po + 320 + t * 32, oh[t]);
                }
            }
        }
        TS(warp == 0 ? 5 : warp == 4 ? 21 : warp == 5 ? 29 : warp == 1 ? 31 : 63);
        const unsigned t_pub = clock();
        if (lane == 0) mbar_arrive(B_PUB);
        const uint4* ow = sc + (SC_O + HALF * 640 - hg * SC_SIZE);
        mbar_wait(B_INIT, 0);
        if (wg != HALF) {
            mbar_wait(B_PUB, 0);
            const unsigned t0 = F0_T ? t_start + max((unsigned)clock() - t_start + (wg ? F0_D : F1_D), wg ? F0_T : F1_T) : clock() + (wg ? F0_D : F1_D);
            uint32_t ph = 0;
#pragma unroll 1
            for (int i = w4 + 1 + NRS; i < 8; i += 4) {
                const uint4* src = ow + src_of(i, hg) * SC_SIZE;
                const uint32_t buf = o_buf(i), chk = buf + lane * 132;
                pace(t0, (i - 2) * O_DT);
                if (i > 4 + NRS) mbar_wait(B_DF, 0);
                if (i == 1 + NRS) TS(wg ? 3 : 4);
                uint32_t c;
                do {
                    if (elect_one()) {
                        mbar_expect_tx(B_OT + w4 * 8, 10240);
                        bulk_load(buf, src, 10240, B_OT + w4 * 8);
                    }
                    mbar_wait(B_OT + w4 * 8, ph);
                    if (i == 1 + NRS && !ph) TS(wg ? 19 : 20);
                    ph ^= 1;
                    c = max(max(lds4(chk), lds4(chk + 4096)), lds4(chk + 6144));
                } while (__any_sync(0xffffffffu, c == SENT));
                if (lane == 0) mbar_arrive(B_G2 + i * 8);
                TS(i == 2 ? 33 : 32 + i);
            }
            return;
        }

        float oc[80];
        uint32_t af[20];
        auto fetch = [&]() {
            const uint32_t* p = reinterpret_cast<const uint32_t*>(ow + src_of(1, hg) * SC_SIZE + w4 * 160) + lane;
#pragma unroll
            for (int t = 0; t < 20; t++) af[t] = ld_relaxed4(p + t * 32);
        };
        mbar_wait(B_XS, 0);
        const int orow = p0 + wg * 64 + w4 * 16;
        const uint32_t tk1 = ~lds4(SM_KEY + 16 * 4) & 2047, tk2 = ~lds4(SM_KEY + 17 * 4) & 2047;
        const uint32_t sel1 = (tk1 & 1) == par ? (tk1 >> 1) - orow : 99, sel2 = (tk2 & 1) == par ? (tk2 >> 1) - orow : 99;
        const uint32_t n0 = pack2(1.f - g0, 1.f - g0), n1 = pack2(1.f - g1, 1.f - g1);
        const uint32_t stg = SM_OUT + w4 * 5120;
        const uint32_t m128 = keep(stg + (lane & 15) * 128 + (((lane >> 4) ^ (lane & 7)) << 4));
        const uint32_t m64 = keep(stg + 4096 + (lane & 15) * 64 + (((lane >> 4) ^ ((lane >> 1) & 3)) << 4));
        const uint32_t l128 = keep(stg + (lane >> 3) * 128 + (((lane & 7) ^ (lane >> 3)) << 4));
        const uint32_t l64 = keep(stg + 4096 + r * 64 + ((cq ^ (lane >> 3)) << 4));
        char* const o128 = reinterpret_cast<char*>(P.op) + keep(((orow + (lane >> 3)) * 2 + par) * 1280 + kba * 128 + (lane & 7) * 16);
        char* const o64 = reinterpret_cast<char*>(P.op) + keep(((orow + r) * 2 + par) * 1280 + kbr * 128 + odd * 64 + cq * 16);
        if (!SETL) mbar_wait(B_G2, 0), mbar_wait(B_G2 + 8, 0);
        const bool ff = FFV == 1 || (FFV == 2 && cid < NFFN) || (FFV == 3 && wg) || (FFV == 4 && (cid < NFFN || wg));
        if (ff) {
            if (L0_T) pace(t_start, wg ? L1_T : L0_T);
            else pace(t_pub, wg ? L1_D : L0_D);
            fetch();
        }
        if (SETL) mbar_wait(B_G2, 0);
        bar_sync(2, 256);
        TS(w4 == 0 ? 6 : 63);
        wg_fence();
#pragma unroll
        for (int s = 0; s < 5; s++)
            wgmma_own(oc, ol[2 * s], oh[2 * s], ol[2 * s + 1], oh[2 * s + 1], desc_lo(wo_buf(0), 10240) + s * 128, s);
        wg_commit();
        if (!ff) {
            if (LS_T) pace(t_start, LS_T);
            fetch();
        }
        TS(w4 == 0 ? 28 : 63);
        if (OEV == 2) {
            wg_wait<0>();
            if (leader) mbar_arrive(B_OE);
        }
        if (DFV == 0) mbar_wait(B_DF, 0);
        for (;;) {
            uint32_t m = 0;
#pragma unroll
            for (int t = 0; t < 20; t++) m = max(m, af[t]);
            if (!__any_sync(0xffffffffu, m == SENT)) break;
            fetch();
        }
        TS(w4 == 0 ? 7 : 63);
        if (OEV == 0) {
            wg_wait<0>();
            if (leader) mbar_arrive(B_OE);
        }
        wg_fence();
#pragma unroll
        for (int s = 0; s < 5; s++)
            wgmma_own(oc, af[2 * s], af[10 + 2 * s], af[2 * s + 1], af[11 + 2 * s], desc_lo(wo_buf(1), 10240) + s * 128, 1);
        wg_commit();
        if (OEV == 1) {
            wg_wait<1>();
            if (leader) mbar_arrive(B_OE);
        }
        if (DFV == 1) mbar_wait(B_DF, 0);
#pragma unroll 1
        for (int i = 1 + NRS; i < 8; i++) {
            const uint32_t ao = desc_lo(0, 128) + (o_buf(i) >> 4), wo = desc_lo(0, 10240) + (wo_buf(i) >> 4);
            mbar_wait(B_G2 + i * 8, 0);
            TS(w4 == 0 ? (i < 2 ? 6 + i : i < 7 ? 9 + i : 17) : 63);
            wg_fence();
#pragma unroll
            for (int s = 0; s < 5; s++) wgmma_out(oc, ao + s * 16, wo + s * 128, 1);
            wg_commit();
            if (i < 4) {
                wg_wait<1>();
                if (i > 1 && leader) mbar_arrive(B_OE - 8 + i * 8);
            }
        }
        TS(w4 == 0 ? 8 : 63);

        if (min(sel1, sel2) < 16) {
#pragma unroll 1
            for (int j = -PV; j < 2; j++) {
                const uint32_t sel = j > 0 ? sel2 : j ? 16 : sel1;
                if (sel > 16) continue;
                if (j >= 0) mbar_wait(B_MOD, 0);
#pragma unroll
                for (int t = 0; t < 5; t++) {
                    const uint4 v = lds16(SM_U + j * 320 + cq * 80 + t * 16);
                    const uint32_t u[4] = {v.x, v.y, v.z, v.w};
#pragma unroll
                    for (int k = 0; k < 4; k++) {
                        if (sel == r) nb[8 * t + 2 * k] = hadd2(nb[8 * t + 2 * k], u[k]);
                        if (sel == r + 8) nb[8 * t + 2 * k + 1] = hadd2(nb[8 * t + 2 * k + 1], u[k]);
                    }
                }
            }
            TS(26);
        }
        wg_wait<0>();
        TS(w4 == 0 ? 9 : 63);
        const bool nan = oc[0] != oc[0] || oc[2] != oc[2];
#pragma unroll
        for (int part = 0; part < 3; part++) {
            const int s0 = part ? part * 4 - 4 : 8, ns = part ? 4 : 2;
#pragma unroll
            for (int i = 0; i < 4; i++) {
                if (i >= ns) break;
                const int s = s0 + i;
                const uint32_t y0 = hfma2(n0, nb[s * 4], pack2(oc[s * 8 + 0], oc[s * 8 + 1]));
                const uint32_t y1 = hfma2(n1, nb[s * 4 + 1], pack2(oc[s * 8 + 2], oc[s * 8 + 3]));
                const uint32_t y2 = hfma2(n0, nb[s * 4 + 2], pack2(oc[s * 8 + 4], oc[s * 8 + 5]));
                const uint32_t y3 = hfma2(n1, nb[s * 4 + 3], pack2(oc[s * 8 + 6], oc[s * 8 + 7]));
                asm volatile("stmatrix.sync.aligned.m8n8.x4.shared.b16 [%0], {%1,%2,%3,%4};"
                             ::"r"(((s < 8 ? m128 : m64) ^ ((s & 3) * 32)) + (s & 4) * 512 + rk), "r"(y0), "r"(y1), "r"(y2), "r"(y3) : "memory");
            }
            __syncwarp();
            uint4 v[4];
#pragma unroll
            for (int i = 0; i < 4; i++)
                if (i < ns) v[i] = lds16(!part ? l64 + i * 512 : (l128 ^ ((i & 1) * 64)) + i * 512 + s0 * 512);
#pragma unroll
            for (int i = 0; i < 4; i++)
                if (i < ns) *reinterpret_cast<uint4*>(!part ? o64 + i * 8 * 2560 : o128 + i * 4 * 2560 + s0 * 32) = v[i];
            if (part == 0) TS(w4 == 0 ? 1 : 63);
        }
        TS(w4 == 0 ? 10 : 63);
        TSL(w4);
        if (lane == 0) mbar_arrive(B_DONE);
        uint32_t redo;
        asm volatile("{\n.reg .pred p, q;\nsetp.ne.u32 p, %1, 0;\nbar.cta.red.or.pred q, 10, 128, p;\nselp.u32 %0, 1, 0, q;\n}"
                     : "=r"(redo) : "r"((uint32_t)nan) : "memory");
        if (redo) {
            const int cb = hg >> 1;
#pragma unroll 1
            for (int i = 0; i < 8; i++) {
                if (leader) {
                    mbar_expect_tx(B_RE, 25600);
                    tma_3d(SM_W, &P.woa, B_RE, 0, i * 80, (cb * 5 + 1) >> 1);
                    tma_2d(SM_W + 20480, &P.wob, B_RE, cb * 160 + ((cb & 1) ? 0 : 128), i * 80);
                }
#pragma unroll 1
                for (int s = 0; s < 20; s++) {
                    const int w = w4 * 640 + s * 32 + lane;
                    uint32_t v, it = 0;
                    do {
                        v = ld_relaxed4(reinterpret_cast<const uint32_t*>(ow + i * SC_SIZE) + w);
                        if (++it > (1u << 22)) fault();
                    } while ((v >> 16) == 0xFFFFu || (v & 0xFFFFu) == 0xFFFFu);
                    sts4(SM_X + w * 4, v);
                }
                fence_async_smem();
                __syncwarp();
                bar_sync(10, 128);
                mbar_wait(B_RE, i & 1);
                wg_fence();
#pragma unroll
                for (int s = 0; s < 5; s++) wgmma_out(oc, desc_lo(SM_X, 128) + s * 16, desc_lo(SM_W, 10240) + s * 128, s || i);
                wg_commit();
                wg_wait<0>();
                bar_sync(10, 128);
            }
#pragma unroll
            for (int t = 0; t < 40; t++) {
                const int col = (t < 32 ? kba * 64 + (t >> 1) * 8 : kbr * 64 + odd * 32 + ((t - 32) >> 1) * 8) + cq * 2;
                *reinterpret_cast<uint32_t*>(P.op + ((orow + r + (t & 1) * 8) * 2 + par) * 640 + col) =
                    hfma2((t & 1) ? n1 : n0, nb[t], pack2(oc[2 * t], oc[2 * t + 1]));
            }
        }
    } else if (role < 12) {
        asm volatile("setmaxnreg.dec.sync.aligned.u32 96;");
        const int t = tid - 256;
        uint32_t tag = ld_relaxed4(g_cnt);
        float gv = 0.f;
        int grow = hg * 16 + (t >> 3);
        mbar_wait(B_RG, 0);
        TS(warp == 8 ? 48 : 63);
        {
            float r0 = 0.f, r1 = 0.f, g0 = 0.f, g1 = 0.f;
            const uint32_t sw = (t >> 4) * 128 + (((t ^ (t >> 4)) & 7) << 4), hi = (t >> 3) & 1;
            mbar_wait(B_XL0, 0);
            tag = (tag * 8 + 2048) & 0xF800u;
            sts4(SM_KEY + 20 * 4, tag);
#pragma unroll 1
            for (int i = 0; i < 5; i++) {
                const int p = (RG_ORDER >> (i * 4)) & 7, kb = 2 * p + hi;
                mbar_wait(p < 3 ? B_FULL + (p & 1) * 32 : B_RG2, p == 2);
                if (p < 2) mbar_wait(B_FULL + p * 32 + 16, 0);
                const uint32_t xa = sw + (kb < 5 ? SM_X + (kb & 3) * 16384 + hg * 2048 : SM_HALO - 5 * 2048 + kb * 2048);
                const uint4 a = lds16(xa), b = lds16(xa + 1024);
                const uint4 w = lds16(SM_RED + p * 256 + (t & 15) * 16), v = lds16(SM_RED + 1280 + p * 256 + (t & 15) * 16);
                if (__ballot_sync(0xffffffffu, lane == 0 || a.w == b.w) && lane == 0 && p < 3) mbar_arrive(B_XE + p * 8);
                TS5(warp == 8 ? 51 + i : 63);
                const uint32_t as[4] = {a.x, a.y, a.z, a.w}, bs[4] = {b.x, b.y, b.z, b.w};
                const uint32_t ws[4] = {w.x, w.y, w.z, w.w}, vs[4] = {v.x, v.y, v.z, v.w};
#pragma unroll
                for (int e = 0; e < 4; e++) {
                    r0 = fmaf(bf_lo(as[e]), bf_lo(ws[e]), r0);
                    r1 = fmaf(bf_lo(bs[e]), bf_lo(ws[e]), r1);
                    g0 = fmaf(bf_lo(as[e]), bf_lo(vs[e]), g0);
                    g1 = fmaf(bf_lo(bs[e]), bf_lo(vs[e]), g1);
                    r0 = fmaf(bf_hi(as[e]), bf_hi(ws[e]), r0);
                    r1 = fmaf(bf_hi(bs[e]), bf_hi(ws[e]), r1);
                    g0 = fmaf(bf_hi(as[e]), bf_hi(vs[e]), g0);
                    g1 = fmaf(bf_hi(bs[e]), bf_hi(vs[e]), g1);
                }
            }
            const bool up = lane & 4;
            r0 = (hi ? r1 : r0) + __shfl_xor_sync(0xffffffffu, hi ? r0 : r1, 8);
            g0 = (hi ? g1 : g0) + __shfl_xor_sync(0xffffffffu, hi ? g0 : g1, 8);
            float r = (up ? g0 : r0) + __shfl_xor_sync(0xffffffffu, up ? r0 : g0, 4);
            r += __shfl_xor_sync(0xffffffffu, r, 2);
            r = bf_round(r + __shfl_xor_sync(0xffffffffu, r, 1));
            const int row = hg * 16 + (t >> 4) + hi * 8;
            const uint32_t u = f2u(r);
            if (!up) sts4(SM_KEY + (t >> 3) * 4, (((int)u < 0 ? ~u : u | 0x80000000u) & 0xFFFF0000u) | (2047 - (p0 + row) * 2 - par));
            gv = r;
            grow = row;
        }
        TS(warp == 8 ? 63 : 63);
        mbar_wait(B_RG2, 0);
        bar_sync(4, 128);
        if (warp == 8) {
            const uint32_t key = lds4(SM_KEY + (lane & 15) * 4);
            uint32_t k1 = __reduce_max_sync(0xffffffffu, key);
            uint32_t k2 = __reduce_max_sync(0xffffffffu, key == k1 ? 0u : key);
            if (elect_one()) {
                st_relaxed8(g_cand + cid, k1 | tag, k2 | tag);
                red_inc<MAPV == 3 ? 2 : 1>(g_cnt, tag);
            }
            TS(49);
        }
        if ((lane & 7) == 4) st_relaxed4(g_gate + tile * 128 + grow, f2u(bf_round(sigmoidf(gv))) | tag);
        const int cq = lane & 3, w4 = warp & 3;
        const uint32_t la = keep(cq * 256 + (((lane >> 2) ^ cq * 2) << 4));
        const uint32_t sel = keep(0x44444444u ^ (0x54u << (lane >> 2 & 1) * 8 + (lane & 16)));
        if (NFFN) {
            float4 d;
            uint4* dst;
            if (cid < NFFN) {
                float dg[8], du[8];
                mbar_wait(B_GU, 0);
                mbar_wait(B_XS, 0);
                TS(warp == 8 ? 50 : 63);
                if (GW & 1) mbar_wait(B_EMPTY + 3 * 8, 0);
                wg_fence();
#pragma unroll
                for (int i = 0; i < 10; i++) wgmma_vec(dg, desc_lo(SM_F + i * 2048, 16), desc_lo(SM_XS + i * 32, 16), i);
                wg_commit();
                mbar_wait(B_UP, 0);
                TS(warp == 10 ? 58 : 63);
                if (GW & 2) mbar_wait(B_EMPTY + 3 * 8, 0);
                wg_fence();
#pragma unroll
                for (int i = 0; i < 10; i++) wgmma_vec(du, desc_lo(SM_UP + i * 2048, 16), desc_lo(SM_XS + i * 32, 16), i);
                wg_commit();
                wg_wait<0>();
                if (lane == 0) mbar_arrive(B_GUD), mbar_arrive(B_DF);
                TS(warp == 8 ? 54 : warp == 10 ? 59 : 63);
                if (cq == 0) {
                    st_relaxed16(sc + SC_GU + w4 * 16 + (lane >> 2), f2u(dg[0]), f2u(dg[4]), f2u(du[0]), f2u(du[4]));
                    st_relaxed16(sc + SC_GU + w4 * 16 + 8 + (lane >> 2), f2u(dg[2]), f2u(dg[6]), f2u(du[2]), f2u(du[6]));
                }
            } else {
                uint4 wv[2][8], wr[4];
                mbar_wait(B_UP, 0);
                TS(warp == 10 ? 58 : 63);
                if (SP_W) mbar_wait(B_EMPTY + 3 * 8, 0);
#pragma unroll
                for (int i = 0; i < 8; i++) wv[i >> 2][4 + (i & 3)] = lds16((la ^ (i & 1) * 144) + SM_UP + w4 * 4096 + (i >> 1) * 1024);
                if (landed<4>(wv[0] + 4, lane) & landed<4>(wv[1] + 4, lane)) mbar_arrive(B_GUD);
                TS(warp == 8 ? 54 : 63);
                mbar_wait(B_GU, 0);
#pragma unroll
                for (int i = 0; i < 4; i++) wr[i] = lds16((la ^ (i & 1) * 144) + SM_F + 12288 + w4 * 2048 + (i >> 1) * 1024);
                mbar_wait(B_XS, 0);
                if (w4 == 0) {
                    uint4 pq[4];
                    pace(t_start, HS_T);
                    poll<4>(pq, g_sc + ((cid >> 1) * 4 - 148) * SC_SIZE + SC_GU + (cid & 1) * 32 + lane, SC_SIZE);
                    TS(warp == 8 ? 55 : 63);
                    swiglu(pq, SM_H + (lane & 6) * 8 + (lane >> 3) * 4 + (lane & 1) * 2, 64);
                }
                bar_sync(4, 128);
                TS(warp == 8 ? 57 : 63);
                const uint4 h = lds16(SM_H + (lane & 8) * 8 + cq * 16);
                const uint32_t hv[4] = {h.x, h.y, h.z, h.w}, hr[2] = {(w4 & 1) ? h.z : h.x, (w4 & 1) ? h.w : h.y};
                d = vec_mma<4>(wr, hr, sel);
                dst = g_sc + (cid * 5 - 520 + w4) * SC_SIZE + SC_Y + (lane & 1) * 32 + (lane >> 1);
                float c[2][2][4] = {};
                const uint32_t s2 = sel + ((sel & 0x10101010u) >> 3) * 17;
#pragma unroll
                for (int i = 7; i >= 0; i--) {
                    const uint32_t x0 = prmt(hv[i >> 1], (i & 1) ? s2 : sel), x1 = prmt(hv[i >> 1], ((i & 1) ? s2 : sel) >> 16);
#pragma unroll
                    for (int n = 0; n < 2; n++) {
                        if (i >= 4) wv[n][i - 4] = lds16((la ^ (i & 1) * 144) + SM_F - 6144 + w4 * 4096 + n * 2048 + (i >> 1) * 1024);
                        mma16(c[n][i & 1], wv[n][i].x, wv[n][i].y, wv[n][i].z, wv[n][i].w, x0, x1);
                    }
                }
#pragma unroll
                for (int n = 0; n < 2; n++)
                    st_relaxed16(dst + n * 16, f2u(c[n][0][0] + c[n][1][0]), f2u(c[n][0][1] + c[n][1][1]), f2u(c[n][0][2] + c[n][1][2]),
                                 f2u(c[n][0][3] + c[n][1][3]));
                dst += (4 - w4) * SC_SIZE + w4 * 8;
                TS(warp == 8 ? 30 : 63);
                if (lane == 0 && f2u(d.x) != SENT) mbar_arrive(B_DF);
                if (w4 & 1) {
                    sts16(SM_RED + 512 + (w4 & 2) * 256 + lane * 16, f2u(d.x), f2u(d.y), f2u(d.z), f2u(d.w));
                    bar_arrive(13 + (w4 >> 1), 64);
                } else {
                    bar_sync(13 + (w4 >> 1), 64);
                    const uint4 o = lds16(SM_RED + 512 + (w4 & 2) * 256 + lane * 16);
                    st_relaxed16(dst, f2u(d.x + u2f(o.x)), f2u(d.y + u2f(o.y)), f2u(d.z + u2f(o.z)), f2u(d.w + u2f(o.w)));
                }
            }
        } else {
            if (t < 4) mbar_arrive(B_GUD);
            if (t < 4) mbar_arrive(B_DF);
            mbar_wait(B_XS, 0);
        }
        TS(warp == 8 ? 51 : 63);
        const uint32_t k1 = lds4(SM_KEY + 16 * 4), k2 = lds4(SM_KEY + 17 * 4);
        const uint32_t mine = (tile >> 1) * 256 + HALF * 128 + par;
        const bool own1 = (~k1 & 0x781) == mine, own2 = (~k2 & 0x781) == mine;
        if ((own1 || own2) && NFFN) {
            const int rg = min(t / 40, 2), un = (hg >> 1) * 40 + t % 40, up = (hg >> 1) * 80 + min(t, 79);
            mbar_wait(B_RS, 0);
            pace(t_start, Y_T);
            TS(warp == 8 ? 60 : 63);
#pragma unroll 1
            for (int j = !own1; j <= own2; j++) {
                const uint4* p = g_sc + (rg * 5 + 20 + (un >> 5)) * SC_SIZE + SC_Y + j * 32 + (un & 31);
                float y[4];
                bool bad;
                do {
                    uint4 yp[7];
#pragma unroll
                    for (int i = 0; i < 7; i++) yp[i] = i < 6 || rg < 2 ? ld_relaxed16(p + i * 15 * SC_SIZE) : make_uint4(0, 0, 0, 0);
                    y[0] = y[1] = y[2] = y[3] = 0.f;
                    bad = false;
#pragma unroll
                    for (int i = 0; i < 7; i++) {
                        y[0] += u2f(yp[i].x); y[1] += u2f(yp[i].y); y[2] += u2f(yp[i].z); y[3] += u2f(yp[i].w);
                        bad |= yp[i].w == SENT;
                    }
                } while (__any_sync(0xffffffffu, bad));
                TS(warp == 8 ? 53 : 63);
                sts16(SM_SENT + j * 2048 + t * 16, f2u(y[0]), f2u(y[1]), f2u(y[2]), f2u(y[3]));
                bar_sync(4, 128);
                if (w4 < 3) {
                    const uint32_t key = j ? k2 : k1, ya = SM_SENT + j * 2048 + t * 8;
                    const float rs = bf_round(sigmoidf(u2f(((int)key < 0 ? key & 0x7FFFFFFFu : ~key) & 0xFFFF0000u)));
                    const float2 y0 = lds8f(ya), y1 = lds8f(ya + 640), y2 = lds8f(ya + 1280);
                    const uint2* q = reinterpret_cast<const uint2*>(g_sc + (up >> 6) * SC_SIZE + SC_Y + j * 32) + (up & 63);
                    const float sx = y0.x + y1.x + y2.x, sy = y0.y + y1.y + y2.y;
                    uint2 z[4];
                    pace(t_start, Y2_T);
                    do {
#pragma unroll
                        for (int i = 0; i < 4; i++) z[i] = ld_relaxed8(q + i * 10 * SC_SIZE);
                    } while (__any_sync(0xffffffffu, max(max(z[0].y, z[1].y), max(z[2].y, z[3].y)) == SENT));
                    TS(warp == 8 ? 62 : 63);
                    if (t < 80)
                        sts4(SM_U + j * 320 + (t & 3) * 80 + ((t >> 2) + (hg & 2) * 8) % 20 * 4, pack2(bf_round(sx + (u2f(z[0].x) + u2f(z[1].x)) + (u2f(z[2].x) + u2f(z[3].x))) * rs,
                                                           bf_round(sy + (u2f(z[0].y) + u2f(z[1].y)) + (u2f(z[2].y) + u2f(z[3].y))) * rs));
                }
            }
        }
        __syncwarp();
        if (lane == 0) mbar_arrive(B_MOD);
        TS(warp == 8 ? 52 : 63);
    } else {
        asm volatile("setmaxnreg.dec.sync.aligned.u32 32;");
        if (warp == 15) {
            if (EPF_M) {
                pace(t_start, EPF_T);
                if (lane < (EPF_M << EPF_H)) l2_prefetch(P.wp + (EPF_N * 132 + (lane >> EPF_H) * 128 + bid) * 64 + (lane & EPF_H) * 32);
            }
#pragma unroll 1
            for (int i = PF_0; i < PF_N; i++) {
                pace(t_start, (i < 6 ? PF_UP : PF_DN) + i * PF_DT);
                const int ln = (i * 128 + cid) * 32 + lane;
                l2_prefetch((ln < 17280 ? P.upp : ln < 23680 ? P.wop - 17280 * 64 : P.dp - 23680 * 64) + ln * 64);
            }
            if (elect_one()) {
#pragma unroll 1
                for (int i = 0; i < (!NFFN ? 0 : cid < NFFN ? 8 : 12); i++) {
                    pace(t_start, GU_T0 + i * (cid < NFFN ? GU_DT : GU_DS) + (cid & 7) * GU_ST);
                    if (cid < NFFN) tma_2d(SM_F + i * 2560, &P.gate, B_GU, (cid >> 2) * 64, (cid & 3) * 160 + i * 20);
                    else tma_2d(SM_F - 4096 + i * 2048, &P.down, B_GU, min(i, 4 + (i >> 1)) * 64, cid * 32 - 2368 + (i > 8 ? (i & 1) * 16 : 0));
                }
            }
            __syncwarp();
            int it = (smem_u32(smem_raw) & 0xFFFFFF) == SB ? 0 : 1 << 20;
            while (!mbar_try(B_DONE, 0) || !mbar_try(B_MOD, 0))
                if (++it > (1 << 20)) fault();
        } else if (warp == 13) {
#pragma unroll 1
            for (int i = 0; i < 10; i++) sts16(SM_SENT + i * 512 + lane * 16, SENT, SENT, SENT, SENT);
            fence_async_smem();
            __syncwarp();
            if (elect_one()) {
                if (!RW_REG) mbar_expect_tx(B_RG, 2560);
                mbar_expect_tx(B_GU, cid < NFFN ? 20480 : 24576);
                asm volatile("mbarrier.expect_tx.relaxed.cta.shared::cta.b64 [%0], 10240;" ::"r"(B_RG2 + rk) : "memory");
                pace(t_start, RW1_T);
                bulk_load(SM_RED, P.w_r, 1280, B_RG);
                bulk_load(SM_RED + 1280, P.gate_w, 1280, B_RG);
#pragma unroll 1
                for (int i = 0; i < 5; i++) {
                    pace(t_start, RG1_T0 + i * RG1_DT);
                    tma_3d(SM_HALO + i * 2048, &P.xg, B_RG2, 320 + i * 64, par, p0 + hg * 16);
                }
#pragma unroll
                for (int i = 0; i < 23; i++) mbar_init(B_GUD + i * 8, i == 10 ? 8 : i == 22 || i == 9 || !i ? 4 : i < 16 ? 1 : 2);
                bulk_store(sc + SC_HALO, SM_SENT, 5120);
                asm volatile("cp.async.bulk.commit_group;\ncp.async.bulk.wait_group 0;" ::: "memory");
                mbar_arrive(B_RG2);
                TS(43);
                const unsigned goal = (ld_relaxed4(g_cnt + 32) | (NCTA - 1)) + 1;
#pragma unroll 1
                for (int i = RS_E; i < RS_N; i++) {
                    pace(t_start, RS_T0 + (i - RS_E) * RS_DT + (cid & 7) * RS_S);
                    bulk_store(sc + i * (1280 / RS_N), SM_SENT, 20480 / RS_N);
                }
                asm volatile("cp.async.bulk.commit_group;\ncp.async.bulk.wait_group 0;" ::: "memory");
                red_inc(g_cnt + 32, goal);
                mbar_arrive(B_RS);
                TS(44);
                while (ld_relaxed4(g_cnt + 32) - goal > 0x80000000u) {}
                mbar_arrive(B_INIT);
                TS(45);
            }
        } else if (warp == 14) {
            if (elect_one()) {
#pragma unroll 1
                for (int kb = 1; kb < 10; kb++) {
                    const uint32_t fb = B_FULL + (kb & 3) * 16, dst = SM_X + (kb & 3) * 16384;
                    mbar_wait(fb + (B_EMPTY - B_FULL + 8), ~(kb >> 2) & 1);
                    if (kb >= 4) mbar_wait(B_XE + (kb - 4 >> 1) * 8, 0);
                    pace(t_start, max(PACE_A - PACE_B / 2 + 2 * kb * PACE_B, PACE_W0 - X_OFF + (2 * kb + 1) * PACE));
                    tma_3d(dst, &P.x2, fb, kb * 64, par, p0);
                    TS5(41 + kb);
                }
            }
            __syncwarp();
            pace(t_start, CAND_T);
            {
                const uint32_t tag = lds4(SM_KEY + 20 * 4);
                uint4 c[2], v;
                do {
                    c[0] = ld_relaxed16(g_cand + lane * 2);
                    c[1] = ld_relaxed16(g_cand + lane * 2 + 64);
                    v = ld_relaxed16(g_gate + tile * 128 + lane * 4);
                } while (__any_sync(0xffffffffu, ((c[0].x ^ tag) | (c[0].z ^ tag) | (c[1].x ^ tag) | (c[1].z ^ tag) | (v.x ^ tag) |
                                                  (v.y ^ tag) | (v.z ^ tag) | (v.w ^ tag)) & 0xF800u));
                const uint32_t a1 = max(c[0].x, c[0].z), b1 = max(c[1].x, c[1].z), l1 = max(a1, b1);
                const uint32_t l2 = max(max(max(c[0].y, c[0].w), max(c[1].y, c[1].w)),
                                        max(max(min(c[0].x, c[0].z), min(c[1].x, c[1].z)), min(a1, b1)));
                const uint32_t k1 = __reduce_max_sync(0xffffffffu, l1);
                const uint32_t k2 = __reduce_max_sync(0xffffffffu, l1 == k1 ? l2 : l1);
                sts16(SM_GATE + lane * 16, v.x, v.y, v.z, v.w);
                __syncwarp();
                if (elect_one()) {
                    bulk_load(SM_XS, P.xp + (~k1 & 2047) * 640 + (cid & 3) * 160, 320, B_XS);
                    bulk_load(SM_XS + 320, P.xp + (~k2 & 2047) * 640 + (cid & 3) * 160, 320, B_XS);
                    sts16(SM_KEY + 16 * 4, k1, k2, 0, 0);
                    mbar_expect_tx(B_XS, 640);
                    mbar_arrive(B_GT);
                    TS(56);
                }
            }
            bar_sync(12, 64);
            pace(t_start, 0);
            pace(clock(), HALO_D);
            TS(24);
            uint4 hv[5];
            poll<5>(hv, sc + (SC_HALO - (tile < 2 ? 0 : 16 * SC_SIZE) + lane), 32);
#pragma unroll
            for (int s = 0; s < 5; s++) sts16(SM_HALO + s * 512 + lane * 16, hv[s].x, hv[s].y, hv[s].z, hv[s].w);
            bar_arrive(8, 64);
            TS(25);
        } else {
            if (elect_one()) {
#pragma unroll 1
                for (int s = W_S0; s < 20; s++) {
                    const uint32_t fb = B_FULL + (s & 7) * 8, dst = SM_W + (s & 7) * 15360;
                    mbar_wait(fb + (B_EMPTY - B_FULL), ~(s >> 3) & 1);
                    pace(t_start, max(PACE_A + s * PACE_B, PACE_W0 + s * PACE));
                    mbar_expect_tx(fb, (s & 1) ? 15360 : 15360 + 16384);
                    tma_3d(dst, &P.w, fb, wcm, s * 32, 0);
                    tma_3d(dst + 12288, &P.wr, fb, wcr, s * 32, 0);
                    TS2(20 + s);
                    if (s == W_S0) TS(41);
                }
                mbar_wait(B_RG2, 0);
                if (NFFN) {
                    mbar_wait(B_EMPTY + 5 * 8, 1);
                    mbar_expect_tx(B_UP, cid < NFFN ? 20480 : 16384);
                    TS(46);
                    if (cid < NFFN) tma_2d(SM_UP, &P.up, B_UP, (cid >> 2) * 64, (cid & 3) * 160);
                    else
#pragma unroll 1
                        for (int i = 0; i < 8; i++) tma_2d(SM_UP + i * 2048, &P.down, B_UP, i * 64, cid * 32 - 2352);
                }
                const int cb = hg >> 1, ca = (cb * 5 + 1) >> 1, cr = cb * 160 + ((cb & 1) ? 0 : 128);
                if (C0_T) pace(t_start, C0_T);
#pragma unroll 1
                for (int j = 0; j < 8; j++) {
                    const int i = j ^ (j == 3 || j == 4 ? 7 : 0);
                    if (j != 3) mbar_wait(j < 3 ? B_EMPTY + ((2 * j + 7) & 7) * 8 : B_GUD + (j - 4) * 8, j == 0);
                    if (j >= 5) {
                        if (C5_T) pace(t_start, (j == 5 ? C5_T : j == 6 ? C6_T : C7_T) - HALF * C_O);
                        else pace(clock(), j == 5 ? C5_D : C6_D);
                    }
                    const uint32_t dst = wo_buf(i), gb = B_G2 + i * 8;
                    mbar_expect_tx(gb, 25600);
                    tma_3d(dst, &P.woa, gb, 0, src_of(i, hg) * 80, ca);
                    tma_2d(dst + 20480, &P.wob, gb, cr, src_of(i, hg) * 80);
                }
            }
        }
    }
}

typedef CUresult (*EncodeFn)(CUtensorMap*, CUtensorMapDataType, cuuint32_t, void*, const cuuint64_t*, const cuuint64_t*,
                             const cuuint32_t*, const cuuint32_t*, CUtensorMapInterleave, CUtensorMapSwizzle,
                             CUtensorMapL2promotion, CUtensorMapFloatOOBfill);

void encode(EncodeFn fn, CUtensorMap* m, const void* ptr, int rank, const cuuint64_t* dims, const cuuint64_t* strides,
            const cuuint32_t* box, CUtensorMapSwizzle swz) {
    const cuuint32_t es[4] = {1, 1, 1, 1};
    fn(m, CU_TENSOR_MAP_DATA_TYPE_BFLOAT16, rank, const_cast<void*>(ptr), dims, strides, box, es,
       CU_TENSOR_MAP_INTERLEAVE_NONE, swz, CU_TENSOR_MAP_L2_PROMOTION_L2_128B, CU_TENSOR_MAP_FLOAT_OOB_FILL_NONE);
}

}

extern "C" void kernel_launch(void* const* d_in, const int* in_sizes, int n_in, void* d_out, int out_size) {
    (void)in_sizes; (void)n_in; (void)out_size;
    Params P;
    P.xp = (const __nv_bfloat16*)d_in[0];
    P.wp = (const __nv_bfloat16*)d_in[1];
    P.wop = (const __nv_bfloat16*)d_in[2];
    P.dp = (const __nv_bfloat16*)d_in[7];
    P.upp = (const __nv_bfloat16*)d_in[6];
    P.op = (__nv_bfloat16*)d_out;
    P.w_r = (const __nv_bfloat16*)d_in[4];
    P.gate_w = (const __nv_bfloat16*)d_in[8];

    void* fp = nullptr;
    cudaDriverEntryPointQueryResult st;
    cudaGetDriverEntryPoint("cuTensorMapEncodeTiled", &fp, cudaEnableDefault, &st);
    EncodeFn fn = (EncodeFn)fp;
    const cuuint64_t xd[3] = {640, 2, 1024}, xs[2] = {1280, 2560};
    const cuuint32_t bx[3] = {64, 1, 64}, bx2[3] = {64, 1, 128};
    encode(fn, &P.x2, d_in[0], 3, xd, xs, bx2, CU_TENSOR_MAP_SWIZZLE_128B);
    encode(fn, &P.x, d_in[0], 3, xd, xs, bx, CU_TENSOR_MAP_SWIZZLE_128B);
    const cuuint64_t wd[3] = {640, 640, 3}, ws[2] = {3840, 1280};
    const cuuint32_t bw[3] = {64, 32, 3}, bwr[3] = {16, 32, 3};
    encode(fn, &P.w, d_in[1], 3, wd, ws, bw, CU_TENSOR_MAP_SWIZZLE_128B);
    encode(fn, &P.wr, d_in[1], 3, wd, ws, bwr, CU_TENSOR_MAP_SWIZZLE_32B);
    const cuuint64_t ad[3] = {64, 640, 10}, as[2] = {1280, 128}, bd[2] = {640, 640};
    const cuuint32_t ba[3] = {64, 80, 2}, bb[2] = {32, 80};
    encode(fn, &P.woa, d_in[2], 3, ad, as, ba, CU_TENSOR_MAP_SWIZZLE_128B);
    encode(fn, &P.wob, d_in[2], 2, bd, as, bb, CU_TENSOR_MAP_SWIZZLE_128B);
    const cuuint64_t gd[2] = {1728, 640}, gs[1] = {3456}, dd[2] = {640, 1728};
    const cuuint32_t bg[2] = {64, 20}, bu[2] = {64, 160}, bdn[2] = {64, 16}, bxg[3] = {64, 1, 16};
    encode(fn, &P.xg, d_in[0], 3, xd, xs, bxg, CU_TENSOR_MAP_SWIZZLE_128B);
    encode(fn, &P.gate, d_in[5], 2, gd, gs, bg, CU_TENSOR_MAP_SWIZZLE_128B);
    encode(fn, &P.up, d_in[6], 2, gd, gs, bu, CU_TENSOR_MAP_SWIZZLE_128B);
    encode(fn, &P.up2, d_in[6], 2, gd, gs, bg, CU_TENSOR_MAP_SWIZZLE_128B);
    encode(fn, &P.down, d_in[7], 2, dd, as, bdn, CU_TENSOR_MAP_SWIZZLE_128B);

    cudaFuncSetAttribute(fused_kernel, cudaFuncAttributeMaxDynamicSharedMemorySize, SM_TOTAL);
    fused_kernel<<<NCTA + (MAPV == 3 ? 0 : NEXTRA), 512, SM_TOTAL, cudaStreamPerThread>>>(P);
}
```

```cpp
#include <cuda_runtime.h>
#include <cuda_bf16.h>
#include <cuda.h>
#include <stdint.h>

namespace {

constexpr int NCTA = 128, NEXTRA = 4;
constexpr int NFFN = 108;
constexpr uint32_t SENT = 0xFFFFFFFFu;

constexpr uint32_t SB = 1024;
constexpr uint32_t SM_W = SB;
constexpr uint32_t SM_X = SB + 122880;
constexpr uint32_t SM_F = SB + 192512;
constexpr uint32_t SM_HALO = SB + 212992;
constexpr uint32_t SM_BAR = SB + 223232;
constexpr uint32_t SM_PROF = SB + 223744;
constexpr uint32_t SM_KEY = SB + 224000;
constexpr uint32_t SM_RED = SB + 224128;
constexpr uint32_t SM_XS = SB + 226688;
constexpr uint32_t SM_SENT = SB + 227328;
constexpr uint32_t SM_U = SM_RED + 1920;
constexpr uint32_t SM_H = SM_RED + 1536;
constexpr uint32_t SM_GATE = SM_RED;
constexpr uint32_t SM_TOTAL = 232448;
constexpr uint32_t SM_HALO1 = SM_X + 32768;
constexpr uint32_t SM_UP = SM_W + 61440;
constexpr uint32_t SM_OUT = SM_W + 61440;

constexpr uint32_t B_XL0 = SM_BAR, B_FULL = SM_BAR + 8, B_GT = SM_BAR + 72, B_RG = SM_BAR + 80, B_RG2 = SM_BAR + 88,
                   B_XS = SM_BAR + 96, B_EMPTY = SM_BAR + 128, B_DONE = SM_BAR + 192, B_XE = SM_BAR + 200,
                   B_GUD = SM_BAR + 224, B_OE = SM_BAR + 232, B_OT = SM_BAR + 264, B_MOD = SM_BAR + 296,
                   B_GU = SM_BAR + 104, B_UP = SM_BAR + 112, B_RS = SM_BAR + 312, B_INIT = SM_BAR + 320,
                   B_RE = SM_BAR + 328, B_PUB = SM_BAR + 304, B_G2 = SM_BAR + 336, B_DF = SM_BAR + 400;

struct Params {
    CUtensorMap x, x2, w, wr, woa, wob, xg, gate, up, down, up2;
    __nv_bfloat16* op;
    const __nv_bfloat16 *xp, *wp, *dp, *upp, *wop, *w_r, *gate_w;
};

constexpr int SC_O = 0;
constexpr int SC_HALO = 1280;
constexpr int SC_GU = 1440;
constexpr int SC_Y = 1504;
constexpr int SC_SIZE = 1600;
__device__ __align__(128) uint4 g_sc[NCTA * SC_SIZE];
__device__ __align__(128) uint2 g_cand[NCTA];
__device__ __align__(16) uint32_t g_gate[2048];
__device__ __align__(128) unsigned g_cnt[64];
#define TS(i) do { } while (0)
#define TS2(i) do { } while (0)
#define TSX(i) do { } while (0)

#define TSL(i) do { } while (0)
#define TS5(i) do { } while (0)
__device__ __forceinline__ uint32_t smem_u32(const void* p) { return (uint32_t)__cvta_generic_to_shared(p); }
__device__ __forceinline__ void fault() { asm volatile("st.shared.u32 [%0], %0;" ::"r"(0x100001) : "memory"); }
__device__ __forceinline__ void mbar_init(uint32_t bar, uint32_t cnt) {
    asm volatile("mbarrier.init.shared::cta.b64 [%0], %1;" ::"r"(bar), "r"(cnt) : "memory");
}
__device__ __forceinline__ void mbar_expect_tx(uint32_t bar, uint32_t bytes) {
    asm volatile("mbarrier.arrive.expect_tx.shared::cta.b64 _, [%0], %1;" ::"r"(bar), "r"(bytes) : "memory");
}
__device__ __forceinline__ void mbar_arrive(uint32_t bar) {
    asm volatile("mbarrier.arrive.shared::cta.b64 _, [%0];" ::"r"(bar) : "memory");
}
__device__ __forceinline__ bool mbar_try(uint32_t bar, uint32_t parity) {
    uint32_t ok;
    asm volatile("{\n.reg .pred p;\nmbarrier.try_wait.parity.shared::cta.b64 p, [%1], %2;\nselp.u32 %0, 1, 0, p;\n}"
                 : "=r"(ok) : "r"(bar), "r"(parity) : "memory");
    return ok;
}
__device__ __forceinline__ void mbar_wait(uint32_t bar, uint32_t parity) {
    asm volatile("{\n.reg .pred p;\nAGAIN:\nmbarrier.try_wait.parity.shared::cta.b64 p, [%0], %1;\n@!p bra AGAIN;\n}"
                 ::"r"(bar), "r"(parity) : "memory");
}
__device__ __forceinline__ void tma_2d(uint32_t dst, const CUtensorMap* m, uint32_t bar, int c0, int c1) {
    asm volatile("cp.async.bulk.tensor.2d.shared::cluster.global.mbarrier::complete_tx::bytes [%0], [%1, {%3, %4}], [%2];"
                 ::"r"(dst), "l"(m), "r"(bar), "r"(c0), "r"(c1) : "memory");
}
__device__ __forceinline__ void bulk_load(uint32_t dst, const void* src, uint32_t bytes, uint32_t bar) {
    asm volatile("cp.async.bulk.shared::cluster.global.mbarrier::complete_tx::bytes [%0], [%1], %2, [%3];"
                 ::"r"(dst), "l"(src), "r"(bytes), "r"(bar) : "memory");
}
__device__ __forceinline__ void bulk_store(void* dst, uint32_t src, uint32_t bytes) {
    asm volatile("cp.async.bulk.global.shared::cta.bulk_group [%0], [%1], %2;" ::"l"(dst), "r"(src), "r"(bytes) : "memory");
}
__device__ __forceinline__ void tma_3d(uint32_t dst, const CUtensorMap* m, uint32_t bar, int c0, int c1, int c2) {
    asm volatile("cp.async.bulk.tensor.3d.shared::cluster.global.mbarrier::complete_tx::bytes [%0], [%1, {%3, %4, %5}], [%2];"
                 ::"r"(dst), "l"(m), "r"(bar), "r"(c0), "r"(c1), "r"(c2) : "memory");
}
__device__ __forceinline__ void fence_async_smem() { asm volatile("fence.proxy.async.shared::cta;" ::: "memory"); }
__device__ __forceinline__ void wg_fence() { asm volatile("wgmma.fence.sync.aligned;" ::: "memory"); }
__device__ __forceinline__ void wg_commit() { asm volatile("wgmma.commit_group.sync.aligned;" ::: "memory"); }
template <int N> __device__ __forceinline__ void wg_wait() { asm volatile("wgmma.wait_group.sync.aligned %0;" ::"n"(N) : "memory"); }
__device__ __forceinline__ void bar_sync(int id, int n) { asm volatile("bar.cta.sync %0, %1;" ::"r"(id), "r"(n) : "memory"); }
__device__ __forceinline__ void bar_arrive(int id, int n) { asm volatile("bar.cta.arrive %0, %1;" ::"r"(id), "r"(n) : "memory"); }

__device__ constexpr uint32_t desc_lo(uint32_t addr, uint32_t lbo) { return (addr >> 4) | ((lbo >> 4) << 16); }
__device__ __forceinline__ bool elect_one() {
    uint32_t p;
    asm volatile("{\n.reg .pred p;\nelect.sync _|p, 0xffffffff;\nselp.u32 %0, 1, 0, p;\n}" : "=r"(p));
    return p;
}
__device__ __forceinline__ uint32_t ld_relaxed4(const void* p) {
    uint32_t v;
    asm volatile("ld.relaxed.gpu.global.u32 %0, [%1];" : "=r"(v) : "l"(p) : "memory");
    return v;
}
__device__ __forceinline__ void st_relaxed4(void* p, uint32_t v) {
    asm volatile("st.relaxed.gpu.global.u32 [%0], %1;" ::"l"(p), "r"(v) : "memory");
}
template <int N = 1>
__device__ __forceinline__ void red_inc(unsigned* p, unsigned after) {
    asm volatile("red.relaxed.gpu.global.add.u32 [%0], %2;" ::"l"(p), "r"(after), "n"(N) : "memory");
}
__device__ __forceinline__ uint32_t lds4(uint32_t a) {
    uint32_t v;
    asm volatile("ld.shared.u32 %0, [%1];" : "=r"(v) : "r"(a) : "memory");
    return v;
}
__device__ __forceinline__ float2 lds8f(uint32_t a) {
    float2 v;
    asm volatile("ld.shared.v2.f32 {%0, %1}, [%2];" : "=f"(v.x), "=f"(v.y) : "r"(a) : "memory");
    return v;
}
__device__ __forceinline__ void sts4(uint32_t a, uint32_t v) { asm volatile("st.shared.u32 [%0], %1;" ::"r"(a), "r"(v) : "memory"); }
__device__ __forceinline__ uint32_t hmul2(uint32_t a, uint32_t b) {
    uint32_t d;
    asm("mul.rn.bf16x2 %0, %1, %2;" : "=r"(d) : "r"(a), "r"(b));
    return d;
}
__device__ __forceinline__ uint32_t hadd2(uint32_t a, uint32_t b) {
    uint32_t d;
    asm("add.rn.bf16x2 %0, %1, %2;" : "=r"(d) : "r"(a), "r"(b));
    return d;
}
__device__ __forceinline__ uint32_t hfma2(uint32_t a, uint32_t b, uint32_t c) {
    uint32_t d;
    asm("fma.rn.bf16x2 %0, %1, %2, %3;" : "=r"(d) : "r"(a), "r"(b), "r"(c));
    return d;
}
__device__ __forceinline__ uint4 ld_relaxed16(const void* p) {
    uint4 v;
    asm volatile("{\n.reg .b128 t;\n.reg .b64 lo, hi;\nld.relaxed.gpu.global.b128 t, [%4];\nmov.b128 {lo, hi}, t;\n"
                 "mov.b64 {%0, %1}, lo;\nmov.b64 {%2, %3}, hi;\n}" : "=r"(v.x), "=r"(v.y), "=r"(v.z), "=r"(v.w) : "l"(p) : "memory");
    return v;
}
__device__ __forceinline__ void st_relaxed16(void* p, uint32_t a, uint32_t b, uint32_t c, uint32_t d) {
    uint64_t lo = (uint64_t)a | ((uint64_t)b << 32), hi = (uint64_t)c | ((uint64_t)d << 32);
    asm volatile("{\n.reg .b128 t;\nmov.b128 t, {%1, %2};\nst.relaxed.gpu.global.b128 [%0], t;\n}" ::"l"(p), "l"(lo), "l"(hi) : "memory");
}
__device__ __forceinline__ void st_relaxed8(void* p, uint32_t a, uint32_t b) {
    asm volatile("{\n.reg .b64 t;\nmov.b64 t, {%1, %2};\nst.relaxed.gpu.global.b64 [%0], t;\n}" ::"l"(p), "r"(a), "r"(b) : "memory");
}
__device__ __forceinline__ uint2 ld_relaxed8(const void* p) {
    uint2 v;
    asm volatile("{\n.reg .b64 t;\nld.relaxed.gpu.global.b64 t, [%2];\nmov.b64 {%0, %1}, t;\n}" : "=r"(v.x), "=r"(v.y) : "l"(p) : "memory");
    return v;
}
__device__ __forceinline__ uint4 ld_nc16(const void* p) {
    uint4 v;
    asm volatile("ld.global.L1::no_allocate.v4.u32 {%0, %1, %2, %3}, [%4];" : "=r"(v.x), "=r"(v.y), "=r"(v.z), "=r"(v.w) : "l"(p) : "memory");
    return v;
}
__device__ __forceinline__ uint2 ld_nc8(const void* p) {
    uint2 v;
    asm volatile("ld.global.nc.L1::no_allocate.v2.u32 {%0, %1}, [%2];" : "=r"(v.x), "=r"(v.y) : "l"(p));
    return v;
}
__device__ __forceinline__ uint4 lds16(uint32_t a) {
    uint4 v;
    asm volatile("ld.shared.v4.u32 {%0, %1, %2, %3}, [%4];" : "=r"(v.x), "=r"(v.y), "=r"(v.z), "=r"(v.w) : "r"(a) : "memory");
    return v;
}
__device__ __forceinline__ void sts16(uint32_t a, uint32_t x, uint32_t y, uint32_t z, uint32_t w) {
    asm volatile("st.shared.v4.u32 [%0], {%1, %2, %3, %4};" ::"r"(a), "r"(x), "r"(y), "r"(z), "r"(w) : "memory");
}
__device__ __forceinline__ uint32_t pack2(float lo, float hi) {
    uint32_t r;
    asm("cvt.rn.bf16x2.f32 %0, %1, %2;" : "=r"(r) : "f"(hi), "f"(lo));
    return r;
}
__device__ __forceinline__ uint32_t pack2v(float lo, float hi) {
    uint32_t r;
    asm volatile("cvt.rn.bf16x2.f32 %0, %1, %2;" : "=r"(r) : "f"(hi), "f"(lo));
    return r;
}
__device__ __forceinline__ float bf_lo(uint32_t u) { return __uint_as_float(u << 16); }
__device__ __forceinline__ float bf_hi(uint32_t u) { return __uint_as_float(u & 0xFFFF0000u); }
__device__ __forceinline__ float bf_round(float f) { return __bfloat162float(__float2bfloat16_rn(f)); }
__device__ __forceinline__ uint32_t prmt(uint32_t a, uint32_t sel) {
    uint32_t d;
    asm("prmt.b32 %0, %1, 0, %2;" : "=r"(d) : "r"(a), "r"(sel));
    return d;
}
__device__ __forceinline__ uint32_t movm(uint32_t a) {
    uint32_t d;
    asm volatile("movmatrix.sync.aligned.m8n8.trans.b16 %0, %1;" : "=r"(d) : "r"(a));
    return d;
}
__device__ __forceinline__ void mma16(float (&c)[4], uint32_t a0, uint32_t a1, uint32_t a2, uint32_t a3, uint32_t b0, uint32_t b1) {
    asm volatile("mma.sync.aligned.m16n8k16.row.col.f32.bf16.bf16.f32 {%0,%1,%2,%3}, {%4,%5,%6,%7}, {%8,%9}, {%0,%1,%2,%3};"
                 : "+f"(c[0]), "+f"(c[1]), "+f"(c[2]), "+f"(c[3]) : "r"(a0), "r"(a1), "r"(a2), "r"(a3), "r"(b0), "r"(b1));
}
__device__ __forceinline__ void mma8(float (&c)[4], uint32_t a0, uint32_t a1, uint32_t b0) {
    asm volatile("mma.sync.aligned.m16n8k8.row.col.f32.bf16.bf16.f32 {%0,%1,%2,%3}, {%4,%5}, {%6}, {%0,%1,%2,%3};"
                 : "+f"(c[0]), "+f"(c[1]), "+f"(c[2]), "+f"(c[3]) : "r"(a0), "r"(a1), "r"(b0));
}
__device__ __forceinline__ float ex2(float x) { float y; asm("ex2.approx.ftz.f32 %0, %1;" : "=f"(y) : "f"(x)); return y; }
__device__ __forceinline__ float rcp(float x) { float y; asm("rcp.approx.ftz.f32 %0, %1;" : "=f"(y) : "f"(x)); return y; }
__device__ __forceinline__ float sigmoidf(float z) { return rcp(1.0f + ex2(z * -1.4426950408889634f)); }
__device__ __forceinline__ float u2f(uint32_t u) { return __uint_as_float(u); }
__device__ __forceinline__ uint32_t f2u(float f) { return __float_as_uint(f); }

__device__ __forceinline__ void wgmma_main(float (&d)[96], uint32_t a, uint32_t b, int scale_d) {
    asm volatile("{\n.reg .pred p;\n.reg .b64 da, db;\nsetp.ne.b32 p, %98, 0;\n"
        "mov.b64 da, {%96, 0x40000040};\nmov.b64 db, {%97, 0x40000040};\n"
        "wgmma.mma_async.sync.aligned.m64n192k16.f32.bf16.bf16 "
        "{%0, %1, %2, %3, %4, %5, %6, %7, %8, %9, %10, %11, %12, %13, %14, %15, "
        "%16, %17, %18, %19, %20, %21, %22, %23, %24, %25, %26, %27, %28, %29, %30, %31, "
        "%32, %33, %34, %35, %36, %37, %38, %39, %40, %41, %42, %43, %44, %45, %46, %47, "
        "%48, %49, %50, %51, %52, %53, %54, %55, %56, %57, %58, %59, %60, %61, %62, %63, "
        "%64, %65, %66, %67, %68, %69, %70, %71, %72, %73, %74, %75, %76, %77, %78, %79, "
        "%80, %81, %82, %83, %84, %85, %86, %87, %88, %89, %90, %91, %92, %93, %94, %95}, "
        "da, db, p, 1, 1, 0, 1;\n}\n"
        : "+f"(d[0]), "+f"(d[1]), "+f"(d[2]), "+f"(d[3]), "+f"(d[4]), "+f"(d[5]), "+f"(d[6]), "+f"(d[7]),
          "+f"(d[8]), "+f"(d[9]), "+f"(d[10]), "+f"(d[11]), "+f"(d[12]), "+f"(d[13]), "+f"(d[14]), "+f"(d[15]),
          "+f"(d[16]), "+f"(d[17]), "+f"(d[18]), "+f"(d[19]), "+f"(d[20]), "+f"(d[21]), "+f"(d[22]), "+f"(d[23]),
          "+f"(d[24]), "+f"(d[25]), "+f"(d[26]), "+f"(d[27]), "+f"(d[28]), "+f"(d[29]), "+f"(d[30]), "+f"(d[31]),
          "+f"(d[32]), "+f"(d[33]), "+f"(d[34]), "+f"(d[35]), "+f"(d[36]), "+f"(d[37]), "+f"(d[38]), "+f"(d[39]),
          "+f"(d[40]), "+f"(d[41]), "+f"(d[42]), "+f"(d[43]), "+f"(d[44]), "+f"(d[45]), "+f"(d[46]), "+f"(d[47]),
          "+f"(d[48]), "+f"(d[49]), "+f"(d[50]), "+f"(d[51]), "+f"(d[52]), "+f"(d[53]), "+f"(d[54]), "+f"(d[55]),
          "+f"(d[56]), "+f"(d[57]), "+f"(d[58]), "+f"(d[59]), "+f"(d[60]), "+f"(d[61]), "+f"(d[62]), "+f"(d[63]),
          "+f"(d[64]), "+f"(d[65]), "+f"(d[66]), "+f"(d[67]), "+f"(d[68]), "+f"(d[69]), "+f"(d[70]), "+f"(d[71]),
          "+f"(d[72]), "+f"(d[73]), "+f"(d[74]), "+f"(d[75]), "+f"(d[76]), "+f"(d[77]), "+f"(d[78]), "+f"(d[79]),
          "+f"(d[80]), "+f"(d[81]), "+f"(d[82]), "+f"(d[83]), "+f"(d[84]), "+f"(d[85]), "+f"(d[86]), "+f"(d[87]),
          "+f"(d[88]), "+f"(d[89]), "+f"(d[90]), "+f"(d[91]), "+f"(d[92]), "+f"(d[93]), "+f"(d[94]), "+f"(d[95])
        : "r"(a), "r"(b), "r"(scale_d));
}

__device__ __forceinline__ void wgmma_rem(float (&d)[24], uint32_t a, uint32_t b, int scale_d) {
    asm volatile("{\n.reg .pred p;\n.reg .b64 da, db;\nsetp.ne.b32 p, %26, 0;\n"
        "mov.b64 da, {%24, 0x40000040};\nmov.b64 db, {%25, 0xC0000010};\n"
        "wgmma.mma_async.sync.aligned.m64n48k16.f32.bf16.bf16 "
        "{%0, %1, %2, %3, %4, %5, %6, %7, %8, %9, %10, %11, %12, %13, %14, %15, "
        "%16, %17, %18, %19, %20, %21, %22, %23}, "
        "da, db, p, 1, 1, 0, 1;\n}\n"
        : "+f"(d[0]), "+f"(d[1]), "+f"(d[2]), "+f"(d[3]), "+f"(d[4]), "+f"(d[5]), "+f"(d[6]), "+f"(d[7]),
          "+f"(d[8]), "+f"(d[9]), "+f"(d[10]), "+f"(d[11]), "+f"(d[12]), "+f"(d[13]), "+f"(d[14]), "+f"(d[15]),
          "+f"(d[16]), "+f"(d[17]), "+f"(d[18]), "+f"(d[19]), "+f"(d[20]), "+f"(d[21]), "+f"(d[22]), "+f"(d[23])
        : "r"(a), "r"(b), "r"(scale_d));
}

__device__ __forceinline__ void wgmma_out(float (&d)[80], uint32_t a, uint32_t b, int scale_d) {
    asm volatile("{\n.reg .pred p;\n.reg .b64 da, db;\nsetp.ne.b32 p, %82, 0;\n"
        "mov.b64 da, {%80, 0x50};\nmov.b64 db, {%81, 0x40000040};\n"
        "wgmma.mma_async.sync.aligned.m64n160k16.f32.bf16.bf16 "
        "{%0, %1, %2, %3, %4, %5, %6, %7, %8, %9, %10, %11, %12, %13, %14, %15, "
        "%16, %17, %18, %19, %20, %21, %22, %23, %24, %25, %26, %27, %28, %29, %30, %31, "
        "%32, %33, %34, %35, %36, %37, %38, %39, %40, %41, %42, %43, %44, %45, %46, %47, "
        "%48, %49, %50, %51, %52, %53, %54, %55, %56, %57, %58, %59, %60, %61, %62, %63, "
        "%64, %65, %66, %67, %68, %69, %70, %71, %72, %73, %74, %75, %76, %77, %78, %79}, "
        "da, db, p, 1, 1, 0, 1;\n}\n"
        : "+f"(d[0]), "+f"(d[1]), "+f"(d[2]), "+f"(d[3]), "+f"(d[4]), "+f"(d[5]), "+f"(d[6]), "+f"(d[7]),
          "+f"(d[8]), "+f"(d[9]), "+f"(d[10]), "+f"(d[11]), "+f"(d[12]), "+f"(d[13]), "+f"(d[14]), "+f"(d[15]),
          "+f"(d[16]), "+f"(d[17]), "+f"(d[18]), "+f"(d[19]), "+f"(d[20]), "+f"(d[21]), "+f"(d[22]), "+f"(d[23]),
          "+f"(d[24]), "+f"(d[25]), "+f"(d[26]), "+f"(d[27]), "+f"(d[28]), "+f"(d[29]), "+f"(d[30]), "+f"(d[31]),
          "+f"(d[32]), "+f"(d[33]), "+f"(d[34]), "+f"(d[35]), "+f"(d[36]), "+f"(d[37]), "+f"(d[38]), "+f"(d[39]),
          "+f"(d[40]), "+f"(d[41]), "+f"(d[42]), "+f"(d[43]), "+f"(d[44]), "+f"(d[45]), "+f"(d[46]), "+f"(d[47]),
          "+f"(d[48]), "+f"(d[49]), "+f"(d[50]), "+f"(d[51]), "+f"(d[52]), "+f"(d[53]), "+f"(d[54]), "+f"(d[55]),
          "+f"(d[56]), "+f"(d[57]), "+f"(d[58]), "+f"(d[59]), "+f"(d[60]), "+f"(d[61]), "+f"(d[62]), "+f"(d[63]),
          "+f"(d[64]), "+f"(d[65]), "+f"(d[66]), "+f"(d[67]), "+f"(d[68]), "+f"(d[69]), "+f"(d[70]), "+f"(d[71]),
          "+f"(d[72]), "+f"(d[73]), "+f"(d[74]), "+f"(d[75]), "+f"(d[76]), "+f"(d[77]), "+f"(d[78]), "+f"(d[79])
        : "r"(a), "r"(b), "r"(scale_d));
}

__device__ __forceinline__ void wgmma_own(float (&d)[80], uint32_t a0, uint32_t a1, uint32_t a2, uint32_t a3, uint32_t b, int scale_d) {
    asm volatile("{\n.reg .pred p;\n.reg .b64 db;\nsetp.ne.b32 p, %85, 0;\nmov.b64 db, {%84, 0x40000040};\n"
        "wgmma.mma_async.sync.aligned.m64n160k16.f32.bf16.bf16 "
        "{%0, %1, %2, %3, %4, %5, %6, %7, %8, %9, %10, %11, %12, %13, %14, %15, "
        "%16, %17, %18, %19, %20, %21, %22, %23, %24, %25, %26, %27, %28, %29, %30, %31, "
        "%32, %33, %34, %35, %36, %37, %38, %39, %40, %41, %42, %43, %44, %45, %46, %47, "
        "%48, %49, %50, %51, %52, %53, %54, %55, %56, %57, %58, %59, %60, %61, %62, %63, "
        "%64, %65, %66, %67, %68, %69, %70, %71, %72, %73, %74, %75, %76, %77, %78, %79}, "
        "{%80, %81, %82, %83}, db, p, 1, 1, 1;\n}\n"
        : "+f"(d[0]), "+f"(d[1]), "+f"(d[2]), "+f"(d[3]), "+f"(d[4]), "+f"(d[5]), "+f"(d[6]), "+f"(d[7]),
          "+f"(d[8]), "+f"(d[9]), "+f"(d[10]), "+f"(d[11]), "+f"(d[12]), "+f"(d[13]), "+f"(d[14]), "+f"(d[15]),
          "+f"(d[16]), "+f"(d[17]), "+f"(d[18]), "+f"(d[19]), "+f"(d[20]), "+f"(d[21]), "+f"(d[22]), "+f"(d[23]),
          "+f"(d[24]), "+f"(d[25]), "+f"(d[26]), "+f"(d[27]), "+f"(d[28]), "+f"(d[29]), "+f"(d[30]), "+f"(d[31]),
          "+f"(d[32]), "+f"(d[33]), "+f"(d[34]), "+f"(d[35]), "+f"(d[36]), "+f"(d[37]), "+f"(d[38]), "+f"(d[39]),
          "+f"(d[40]), "+f"(d[41]), "+f"(d[42]), "+f"(d[43]), "+f"(d[44]), "+f"(d[45]), "+f"(d[46]), "+f"(d[47]),
          "+f"(d[48]), "+f"(d[49]), "+f"(d[50]), "+f"(d[51]), "+f"(d[52]), "+f"(d[53]), "+f"(d[54]), "+f"(d[55]),
          "+f"(d[56]), "+f"(d[57]), "+f"(d[58]), "+f"(d[59]), "+f"(d[60]), "+f"(d[61]), "+f"(d[62]), "+f"(d[63]),
          "+f"(d[64]), "+f"(d[65]), "+f"(d[66]), "+f"(d[67]), "+f"(d[68]), "+f"(d[69]), "+f"(d[70]), "+f"(d[71]),
          "+f"(d[72]), "+f"(d[73]), "+f"(d[74]), "+f"(d[75]), "+f"(d[76]), "+f"(d[77]), "+f"(d[78]), "+f"(d[79])
        : "r"(a0), "r"(a1), "r"(a2), "r"(a3), "r"(b), "r"(scale_d));
}

__device__ __forceinline__ void wgmma_vec(float (&d)[8], uint32_t a, uint32_t b, int scale_d) {
    asm volatile("{\n.reg .pred p;\n.reg .b64 da, db;\nsetp.ne.b32 p, %10, 0;\n"
        "mov.b64 da, {%8, 0x40000040};\nmov.b64 db, {%9, 0x14};\n"
        "wgmma.mma_async.sync.aligned.m64n16k16.f32.bf16.bf16 {%0, %1, %2, %3, %4, %5, %6, %7}, da, db, p, 1, 1, 1, 0;\n}\n"
        : "+f"(d[0]), "+f"(d[1]), "+f"(d[2]), "+f"(d[3]), "+f"(d[4]), "+f"(d[5]), "+f"(d[6]), "+f"(d[7])
        : "r"(a), "r"(b), "r"(scale_d));
}

#define TSA(i) do { } while (0)
#define MAP_TILE(b) ((((b) >> 1) & 14) | ((b) & 1))
#define MAP_HG(b) (((b) >> 4 & 14) | ((b) >> 1 & 1))
#define SRCV 4
#define L1_D 300
#define L0_D 300
#define F1_D 0
#define F0_D 200
#define HALFV 0
#define HALF (int)(HALFV == 0 ? bid >> 1 & 1 : HALFV == 1 ? (bid >> 1 ^ bid) & 1 : (bid >> 1 ^ bid >> 4) & 1)
#define GM 0x78A0
#define H_C 1000
#define PV 0
#define LS_T 14450
#define BX 0
#define SETL 0
#define L0_T 14450
#define L1_T 14050
#define F0_T 14650
#define F1_T 14300
#define C5_T 0
#define C6_T (C5_T + 450)
#define C7_T (C6_T + 400)
#define C_O 250
#define FFV 2
#define DFV 0
#define OEV 1
#define B_OFF 0
#define W_S0 2
#define E_V 0
#define MAPV 4
#define GW 0
#define GU_DS (GU_DT * 7 / 11)
#define GU_ST 90
#define X_OFF 350
#define RW_REG 0
#define P2W 4
#define RES_V 2
#define Y2_T 17000
#define ENT_V 0
#define TPF 1
#define SKEW 4
#define PACE 500
#define PACE_W0 (-600)
#define PACE_A 250
#define PACE_B 450
#define RG_ORDER 0x24130
#define GU_T0 3600
#define GU_DT 750
#define RS_T0 9000
#define RS_DT 120
#define EXCH_FIRST 1
#define HALO_D 450
#define PF_UP 4200
#define O_D 0
#define O_DT 300
#define PF_DN 4200
#define PF_DT 450
#define GX_NS 200
#define NRS 1
#define C5_D 0
#define C6_D 100
#define PF_N 4
#define PF_0 4
#define EPF_N 15
#define EPF_M 15
#define EPF_T 900
#define RG1_T0 1700
#define RG1_DT 200
#define RW1_T 0
#define Y_T 15500
#define GL_T 0
#define DN_T0 500
#define DN_DT 68
#define DN_T1 100000
#define DN_D1 45
#define DN_R 5
#define H_T 13300
#define HS_T 13300
#define GL_N 16
#define C1_T 0
#define C0_T 11100
#define RS_N 10
#define SP_W 1
#define PF2_N 0
#define C2_T 0
#define C3_T 0
#define C4_T 0
#define EPF_G 0
#define EPF_H 0
#define UPF 0
#define UPF_D 700
#define UPF_T 3200
#define UPF_S 90
#define RS_E 0
#define RS_D 0
#define GL15 1
#define RS_S 0
#define CAND_T 9000

__device__ __forceinline__ uint32_t keep(uint32_t v) { return __shfl_xor_sync(0xffffffffu, v, 0); }
__device__ __forceinline__ uint32_t ukeep(uint32_t v) { return __shfl_sync(0xffffffffu, v, 0); }
__device__ __forceinline__ void ldsm2(uint32_t* d, uint32_t a) {
    asm volatile("ldmatrix.sync.aligned.m8n8.x4.shared.b16 {%0,%1,%2,%3}, [%8];\nldmatrix.sync.aligned.m8n8.x4.shared.b16 {%4,%5,%6,%7}, [%9];"
                 : "=r"(d[0]), "=r"(d[1]), "=r"(d[2]), "=r"(d[3]), "=r"(d[4]), "=r"(d[5]), "=r"(d[6]), "=r"(d[7])
                 : "r"(a), "r"(a ^ 32) : "memory");
}
__device__ __forceinline__ void ldsm_t(uint32_t (&d)[4], uint32_t a) {
    asm volatile("ldmatrix.sync.aligned.m8n8.x4.trans.shared.b16 {%0,%1,%2,%3}, [%4];"
                 : "=r"(d[0]), "=r"(d[1]), "=r"(d[2]), "=r"(d[3]) : "r"(a) : "memory");
}
template <bool SWP, int SEG, int E>
__device__ __forceinline__ void pack_blocks(uint32_t (&d)[10], const float (&am)[96], const float (&ar)[24]) {
#pragma unroll
    for (int t = 0; t < 10; t++) {
        const float* p = (SWP ? t < 2 : t >= 8) ? ar + (SEG * 2 + (t & 1)) * 4 + E : am + (SEG * 8 + t - (SWP ? 2 : 0)) * 4 + E;
        d[t] = pack2v(p[0], p[1]);
    }
}
__device__ __forceinline__ int src_of(int i, int hg) {
    return i == 0 ? hg : (0x75316240u >> (i - (i <= (hg >> 2 | hg & 2))) * 4 & 7) ^ (hg & 1);
}

__device__ __forceinline__ uint32_t o_buf(int i) { return __byte_perm(0xD199ADA3u, 0xC7BDu, i - 1 - NRS | 0x7770) << 10; }
__device__ constexpr uint32_t wo_buf(int i) { return SM_W + ((0x10342103u >> i * 4) & 7) * 30720; }

template <int N>
__device__ __forceinline__ void poll(uint4 (&a)[N], const uint4* p, int stride) {
    bool bad;
    do {
        bad = false;
#pragma unroll
        for (int s = 0; s < N; s++) a[s] = ld_relaxed16(p + s * stride);
#pragma unroll
        for (int s = 0; s < N; s++) bad |= a[s].w == SENT;
    } while (__any_sync(0xffffffffu, bad));
}
__device__ __forceinline__ void pace(unsigned t0, int t) {
    asm volatile("{\n.reg .pred p;\n.reg .s32 d;\nAGAIN:\nmov.u32 d, %%clock;\nsub.s32 d, d, %0;\nsetp.lt.s32 p, d, 0;\n"
                 "@p nanosleep.u32 20;\n@p bra AGAIN;\n}" ::"r"(t0 + t) : "memory");
}
__device__ __forceinline__ void l2_prefetch(const void* p) { asm volatile("prefetch.global.L2 [%0];" ::"l"(p) : "memory"); }

template <int N>
__device__ __forceinline__ bool landed(const uint4* w, int lane) {
    uint32_t a = 0;
#pragma unroll
    for (int i = 0; i < N; i++) a ^= w[i].w;
    return __ballot_sync(0xffffffffu, lane == 0 || a == 0) && lane == 0;
}
__device__ __forceinline__ void swiglu(const uint4 (&a)[4], uint32_t dst, uint32_t stride) {
    const float g0 = bf_round((u2f(a[0].x) + u2f(a[1].x)) + (u2f(a[2].x) + u2f(a[3].x)));
    const float g1 = bf_round((u2f(a[0].y) + u2f(a[1].y)) + (u2f(a[2].y) + u2f(a[3].y)));
    const float u0 = bf_round((u2f(a[0].z) + u2f(a[1].z)) + (u2f(a[2].z) + u2f(a[3].z)));
    const float u1 = bf_round((u2f(a[0].w) + u2f(a[1].w)) + (u2f(a[2].w) + u2f(a[3].w)));
    const uint32_t h = pack2(bf_round(g0 * sigmoidf(g0)) * u0, bf_round(g1 * sigmoidf(g1)) * u1);
    asm volatile("st.shared.u16 [%0], %2;\nst.shared.u16 [%1], %3;" ::"r"(dst), "r"(dst + stride), "h"((uint16_t)h), "h"((uint16_t)(h >> 16)) : "memory");
}
template <int N>
__device__ __forceinline__ float4 vec_mma(const uint4 (&w)[N], const uint32_t* x, uint32_t sel) {
    float c[4][4] = {};
    const uint32_t s[4] = {sel, sel >> 16, sel + ((sel & 0x10101010u) >> 3) * 17, (sel + ((sel & 0x10101010u) >> 3) * 17) >> 16};
#pragma unroll
    for (int i = 0; i < N; i++)
        mma16(c[i & 3], w[i].x, w[i].y, w[i].z, w[i].w, prmt(x[i >> 1], s[(i & 1) * 2]), prmt(x[i >> 1], s[(i & 1) * 2 + 1]));
    return make_float4((c[0][0] + c[1][0]) + (c[2][0] + c[3][0]), (c[0][1] + c[1][1]) + (c[2][1] + c[3][1]),
                       (c[0][2] + c[1][2]) + (c[2][2] + c[3][2]), (c[0][3] + c[1][3]) + (c[2][3] + c[3][3]));
}

__global__ void __launch_bounds__(512, 1) fused_kernel(const __grid_constant__ Params P) {
    extern __shared__ __align__(1024) uint8_t smem_raw[];
    const unsigned t_start = clock();
    const int tid = threadIdx.x, lane = tid & 31;
    unsigned sm, bid;
    asm("mov.u32 %0, %%smid;" : "=r"(sm));
    const CUtensorMap* mx = &P.x;
    asm volatile("" : "+l"(mx));
    if ((unsigned)(tid - 480) < EPF_N) l2_prefetch(P.wp + (tid * 132 + sm) * 64 - 480 * 132 * 64);
    const int warp = __shfl_sync(0xffffffffu, threadIdx.x >> 5, 0);
    constexpr uint32_t rk = 0;
    asm("{\n.reg .pred p;\n.reg .b32 t, u;\nshr.u32 t, %1, 1;\nmad.lo.s32 u, t, 14, -928;\nmad.lo.s32 t, t, 37, -925;\nmax.s32 t, t, 0;\n"
        "shr.u32 t, t, 7;\nand.b32 t, t, 14;\nsetp.ge.u32 p, %1, 124;\nselp.b32 t, u, t, p;\nadd.s32 %0, %1, t;\n}" : "=r"(bid) : "r"(sm));
    bid ^= (GM >> (bid & 14) & 6) ^ BX;
    const int hg = MAP_HG(bid), par = bid & 1, p0 = (MAP_TILE(bid) >> 1) * 128;
    const bool swp = (hg & 3) == 3;
    const int wcm = hg * 80 + (swp ? 16 : 0), wcr = hg * 80 + (swp ? 0 : 64);
    if (warp == 0) {
        if (elect_one()) {
#pragma unroll
            for (int i = 0; i < 4; i++) mbar_init(SM_BAR + i * 8, 1);
            asm volatile("fence.mbarrier_init.release.cluster;" ::: "memory");
            if (bid < NCTA) {
                mbar_expect_tx(B_FULL, 15360 + 8192);
                tma_3d(SM_X + 8192, mx, B_FULL, 0, par, p0 + 64);
                tma_3d(SM_W, mx + 2, B_FULL, wcm, 0, 0);
                tma_3d(SM_W + 12288, mx + 3, B_FULL, wcr, 0, 0);
                TS(40);
                mbar_expect_tx(B_XL0, 8192);
                tma_3d(SM_X, mx, B_XL0, 0, par, p0);
                mbar_expect_tx(B_FULL + 8, 15360);
                tma_3d(SM_W + 15360, mx + 2, B_FULL + 8, wcm, 32, 0);
                tma_3d(SM_W + 15360 + 12288, mx + 3, B_FULL + 8, wcr, 32, 0);
            }
        }
    }
    if ((unsigned)(warp - 1) < 6 && elect_one()) {
#pragma unroll
        for (int i = 0; i < 4; i++) mbar_init(SM_BAR + warp * 32 + i * 8, warp < 4 ? 1 : warp < 6 ? 2 : 4);
        asm volatile("fence.mbarrier_init.release.cluster;" ::: "memory");
    }
    asm volatile("" : "+r"(bid));
    const int role = bid >= NCTA ? -1 : warp, e = sm & 3;
    const int tile = MAP_TILE(bid), cid = tile * 8 + hg;
    uint4* const sc = g_sc + cid * SC_SIZE;
    __syncthreads();

    if (role < 0) {
        const int half = warp >> 3;
        if (!NFFN) {
            if (tid == 0) red_inc<NCTA / NEXTRA>(g_cnt, 0);
            return;
        }
        uint32_t wf[DN_R][5][4], la[5];
        auto rows = [&](uint32_t l) {
#pragma unroll
            for (int i = 0; i < 5; i++) {
                const uint32_t c = (warp & 7) * 10 + 2 * i + (l >> 3 & 1);
                la[i] = SB + half * 20480 + (c >> 3) * 2048 + (l & 7) * 128 + (l >> 4) * 1024 + (((c ^ l) & 7) << 4);
            }
        };
        rows(lane);
        auto fetch = [&](int j, int n, uint32_t bar) {
#pragma unroll 1
            for (int h = 0; h < n; h++) {
                pace(t_start, min(DN_T0 + (j * 20 + h * 10 + warp) * DN_DT, DN_T1 + (j * 20 + h * 10 + warp) * DN_D1));
                tma_2d(SB + (j % 5) * 40960 + h * 20480 + warp * 2048, &P.down, bar, warp * 64, e * 272 + (j + h * 9) * 16);
            }
        };
        if (warp < 10 && elect_one()) {
            if (warp <= DN_R) mbar_expect_tx(B_FULL + warp * 8, warp < DN_R ? 40960 : (17 - 2 * DN_R) * 20480);
#pragma unroll 1
            for (int j = 0; j < 5; j++) fetch(j, 2, B_FULL + j * 8);
        }
        const uint32_t tag = (ukeep(ld_relaxed4(g_cnt)) * 8 + 2048) & 0xF800u;
#pragma unroll
        for (int j = 0; j < DN_R; j++) {
            uint32_t any = 0;
            mbar_wait(B_FULL + j * 8, 0);
#pragma unroll
            for (int i = 0; i < 5; i++) {
                ldsm_t(wf[j][i], la[i] + j * 40960);
                any ^= wf[j][i][3];
            }
            if (j < 4) {
                if (__syncthreads_count(any == 0) == 1000) fault();
                if (warp < 10 && elect_one()) fetch(j + 5, j < 3 ? 2 : 1, B_FULL + DN_R * 8);
                if (j == 0 && tid == 0) red_inc<NCTA / NEXTRA>(g_cnt, tag);
            }
            TSX(warp == 0 && j == 0 ? 0 : warp == 0 && j == 3 ? 1 : 63);
        }
        if (warp < 9) {
            pace(t_start, H_T - H_C);
            uint4 a[4];
            do {
                a[0] = ld_relaxed16(g_cand + lane * 2);
                a[1] = ld_relaxed16(g_cand + lane * 2 + 64);
            } while (__any_sync(0xffffffffu, ((a[0].x ^ tag) | (a[0].z ^ tag) | (a[1].x ^ tag) | (a[1].z ^ tag)) & 0xF800u));
            const int u = min(tid, 271), f = e * 272 + u;
            pace(t_start, H_T);
            TSX(warp == 0 ? 3 : 63);
            poll<4>(a, g_sc + (f >> 6) * 4 * SC_SIZE + SC_GU + (f & 63), SC_SIZE);
            TSX(warp == 0 ? 4 : warp == 8 ? 5 : 63);
            swiglu(a, SM_RED + (u >> 4) * 64 + (u & 6) * 4 + (u & 8) / 2 + (u & 1) * 2, 32);
        }
        rows(keep(lane));
        mbar_wait(B_FULL + DN_R * 8, 0);
        TSX(warp == 15 ? 2 : 63);
        __syncthreads();
        float c[5][4] = {};
#pragma unroll
        for (int j = 0; j < 9; j++) {
            if (j == 8 && half) break;
            const float2 b = lds8f(SM_RED + half * 576 + j * 64 + (lane & 7) * 8);
            if (j == 1) TSX(warp == 0 ? 6 : 63);
#pragma unroll
            for (int i = 0; i < 5; i++) {
                if (j >= DN_R) ldsm_t(wf[j % DN_R][i], la[i] + (j % 5) * 40960);
                mma16(c[i], wf[j % DN_R][i][0], wf[j % DN_R][i][1], wf[j % DN_R][i][2], wf[j % DN_R][i][3], f2u(b.x), f2u(b.y));
            }
        }
        const uint32_t ra = SB + 7 * 20480 + half * 5248 + (lane & 1) * 2624 + (warp & 7) * 320 + (lane & 2) * 16 + (lane >> 2) * 4;
#pragma unroll
        for (int i = 0; i < 5; i++) sts4(ra + i * 64, f2u((lane & 2) ? ((lane & 1) ? c[i][3] : c[i][2]) : ((lane & 1) ? c[i][1] : c[i][0])));
        TSX(warp == 0 ? 7 : 63);
        __syncthreads();
        if (warp < 10) {
            const uint32_t ya = SB + 7 * 20480 + (warp & 1) * 2624 + (warp >> 1) * 512 + lane * 16;
            const uint4 y0 = lds16(ya), y1 = lds16(ya + 5248);
            st_relaxed16(g_sc + (e * 5 + (warp >> 1)) * SC_SIZE + SC_Y + (tid & 63), f2u(u2f(y0.x) + u2f(y1.x)), f2u(u2f(y0.y) + u2f(y1.y)),
                         f2u(u2f(y0.z) + u2f(y1.z)), f2u(u2f(y0.w) + u2f(y1.w)));
        }
    } else if (role < 8) {
        asm volatile("setmaxnreg.inc.sync.aligned.u32 192;");
        const int wg = warp >> 2;
        const bool leader = (tid & 127) == 0;
        float am[96], ar[24];
        if (wg == 0) mbar_wait(B_XL0, 0);
        bool rel = false;
        uint32_t nb[40];
        const int odd = (hg >> 1) & 1, kba = ukeep(RES_V && wg != HALF ? 99 : ((hg >> 1) * 5 + 1) >> 1), kbr = ukeep(kba + 2 - odd * 3);
        const int kbs = wg ? -1 : (20 - SKEW) / 2;
        const uint32_t xrow = keep(SM_X + (warp * 16 + (lane & 15)) * 128 + (((lane >> 4) ^ (lane & 7)) << 4));
#pragma unroll 1
        for (int kb = 0; kb < 10; kb++) {
            const uint32_t fb = B_FULL + (kb & 3) * 16, wo = (kb & 3) * 1920, ph = (kb >> 2) & 1;
            const uint32_t xo = desc_lo(SM_X, 16) + wg * 512 + (kb & 3) * 1024;
#pragma unroll
            for (int h = 0; h < 2; h++) {
                mbar_wait(fb + h * 8, ph);
                if (kb == 0 && h == 0) TS(warp == 0 ? 0 : warp == 4 ? 16 : 63);
                TS2(warp == P2W ? kb * 2 + h : 63);
                if (RES_V == 2) {
                    const uint32_t xa = (xrow ^ h * 64) + (kb & 3) * 16384;
                    if (kb == kba) ldsm2(nb + h * 8, xa);
                    if (kb == kba + 1) ldsm2(nb + 16 + h * 8, xa);
                    if (h == 0 && kb == kbr) ldsm2(nb + 32, xa ^ (odd * 64));
                } else if (h == 0) {
                    const uint32_t xa = xrow + (kb & 3) * 16384;
                    if (kb == kba) { ldsm2(nb, xa); ldsm2(nb + 8, xa ^ 64); }
                    if (kb == kba + 1) { ldsm2(nb + 16, xa); ldsm2(nb + 24, xa ^ 64); }
                    if (kb == kbr) ldsm2(nb + 32, xa ^ (odd * 64));
                }
                wg_wait<1>();
                if (rel && (h == 0 || kb != kbs)) mbar_arrive(B_EMPTY + ((kb * 16 - 16) & 48) + h * 8);
                if (h == 0 && kb == kbs) {
                    wg_wait<0>();
                    if (rel) mbar_arrive(B_EMPTY + ((19 - SKEW) & 7) * 8);
                    bar_sync(5, 256);
                }
                wg_fence();
                wgmma_main(am, xo + h * 4, desc_lo(SM_W + h * 15360, 4096) + wo, h || kb);
                wgmma_rem(ar, xo + h * 4, desc_lo(SM_W + h * 15360 + 12288, 1024) + wo, h || kb);
                wgmma_main(am, xo + h * 4 + 2, desc_lo(SM_W + h * 15360 + 2048, 4096) + wo, 1);
                wgmma_rem(ar, xo + h * 4 + 2, desc_lo(SM_W + h * 15360 + 12288 + 512, 1024) + wo, 1);
                wg_commit();
            }
            rel = leader;
        }
        if (wg == 1) bar_arrive(5, 256);
        mbar_wait(B_XE + 16, 0);
        mbar_wait(B_RG2, 0);
        mbar_wait(B_EMPTY + 5 * 8, 1);
        wg_wait<0>();
        if (leader) mbar_arrive(B_EMPTY + 3 * 8);
        TS(warp == 0 ? 2 : warp == 4 ? 18 : 63);
        TS2(warp == 0 ? 41 : warp == 4 ? 40 : 63);

        uint32_t kl[10], kh[10], vl[10], vh[10], ql[10], qh[10], kp[10], vp[10];
        if (swp) {
            pack_blocks<true, 1, 2>(kh, am, ar);
            pack_blocks<true, 2, 2>(vh, am, ar);
        } else {
            pack_blocks<false, 1, 2>(kh, am, ar);
            pack_blocks<false, 2, 2>(vh, am, ar);
        }
        const int w4 = warp & 3;
        const uint32_t pbuf = (wg ? SM_HALO1 : SM_HALO) + w4 * 2560 + lane * 16;
        const uint32_t hbuf = warp == 3 ? SM_HALO1 + lane * 16 : pbuf + 2560;
        {
            const uint32_t ex[20] = {kh[0], kh[1], kh[3], kh[4], kh[5], kh[6], kh[8], kh[9], kh[2], kh[7],
                                     vh[0], vh[1], vh[2], vh[3], vh[4], vh[5], vh[6], vh[7], vh[8], vh[9]};
            if (warp == 7) {
                uint4* const hp = sc + SC_HALO + lane;
#pragma unroll
                for (int s = 0; s < 5; s++) st_relaxed16(hp + s * 32, ex[4 * s], ex[4 * s + 1], ex[4 * s + 2], ex[4 * s + 3]);
                bar_arrive(12, 64);
            } else {
#pragma unroll
                for (int s = 0; s < 5; s++) sts16(hbuf + s * 512, ex[4 * s], ex[4 * s + 1], ex[4 * s + 2], ex[4 * s + 3]);
            }
        }
        TS(warp == 7 ? 22 : warp == 3 ? 23 : 63);
        if (warp == 3) bar_arrive(11, 64);
        if (swp) {
            pack_blocks<true, 2, 0>(vl, am, ar);
            pack_blocks<true, 0, 0>(ql, am, ar);
            pack_blocks<true, 0, 2>(qh, am, ar);
            pack_blocks<true, 1, 0>(kl, am, ar);
        } else {
            pack_blocks<false, 2, 0>(vl, am, ar);
            pack_blocks<false, 0, 0>(ql, am, ar);
            pack_blocks<false, 0, 2>(qh, am, ar);
            pack_blocks<false, 1, 0>(kl, am, ar);
        }
#pragma unroll
        for (int t = 0; t < 10; t++) { vl[t] = movm(vl[t]); vh[t] = movm(vh[t]); }
        mbar_wait(B_RS, 0);
        mbar_wait(B_GT, 0);
        const float g0 = bf_hi(lds4(SM_GATE + warp * 64 + (lane & 28))), g1 = bf_hi(lds4(SM_GATE + 32 + warp * 64 + (lane & 28)));

        const int r = lane >> 2, cq = lane & 3;
        const bool no_prev = warp == 0 && tile < 2, low = cq < 2;
        const bool le0 = 2 * cq <= r, le1 = 2 * cq + 1 <= r;
        const uint32_t mle = (le0 ? 0xFFFFu : 0u) | (le1 ? 0xFFFF0000u : 0u);
        const float scl = 0.22360679774997896f * 1.4426950408889634f;
        uint32_t pl[4], ph[4];
        {
            float sl[4][4], sh[4][4], sp[4][4];
            auto exchange = [&]() {
            TSA(warp == 1 ? 26 : 63);
            bar_sync(6 + wg, 128);
            if (w4 == 0) bar_sync(8 + wg * 3, 64);
            {
                const uint4 a = lds16(pbuf), b = lds16(pbuf + 512), c = lds16(pbuf + 1024), d = lds16(pbuf + 1536), e = lds16(pbuf + 2048);
                kp[0] = a.x; kp[1] = a.y; kp[3] = a.z; kp[4] = a.w; kp[5] = b.x; kp[6] = b.y; kp[8] = b.z; kp[9] = b.w;
                kp[2] = c.x; kp[7] = c.y; vp[0] = c.z; vp[1] = c.w; vp[2] = d.x; vp[3] = d.y; vp[4] = d.z; vp[5] = d.w;
                vp[6] = e.x; vp[7] = e.y; vp[8] = e.z; vp[9] = e.w;
            }
            TSA(warp == 0 ? 3 : warp == 4 ? 19 : warp == 5 ? 27 : 63);
            };
            if (EXCH_FIRST) exchange();
#pragma unroll
            for (int h = 0; h < 4; h++) {
                const int ta = (h >> 1) * 5 + (h & 1) * 3, tc = (h >> 1) * 5 + 2;
                const uint32_t ml = low != (h & 1) ? ql[tc] : 0u, mh = low != (h & 1) ? qh[tc] : 0u;
#pragma unroll
                for (int e = 0; e < 4; e++) sl[h][e] = sh[h][e] = sp[h][e] = 0.f;
                mma16(sl[h], ql[ta], qh[ta], ql[ta + 1], qh[ta + 1], kl[ta], kl[ta + 1]);
                mma16(sh[h], ql[ta], qh[ta], ql[ta + 1], qh[ta + 1], kh[ta], kh[ta + 1]);
                mma8(sl[h], ml, mh, kl[tc]);
                mma8(sh[h], ml, mh, kh[tc]);
            }
            if (!EXCH_FIRST) exchange();
#pragma unroll
            for (int h = 0; h < 4; h++) {
                const int ta = (h >> 1) * 5 + (h & 1) * 3, tc = (h >> 1) * 5 + 2;
                mma16(sp[h], ql[ta], qh[ta], ql[ta + 1], qh[ta + 1], kp[ta], kp[ta + 1]);
                mma8(sp[h], low != (h & 1) ? ql[tc] : 0u, low != (h & 1) ? qh[tc] : 0u, kp[tc]);
            }
#pragma unroll
            for (int t = 0; t < 10; t++) vp[t] = movm(vp[t]);
#pragma unroll
            for (int h = 0; h < 4; h++) {
                if (no_prev) sp[h][0] = sp[h][1] = -1e9f / 0.22360679774997896f;
                const float a0 = le0 ? sl[h][0] : sp[h][0], a1 = le1 ? sl[h][1] : sp[h][1];
                const float b0 = le0 ? sh[h][2] : sl[h][2], b1 = le1 ? sh[h][3] : sl[h][3];
                float ma = fmaxf(a0, a1), mb = fmaxf(b0, b1);
                ma = fmaxf(ma, __shfl_xor_sync(0xffffffffu, ma, 1));
                mb = fmaxf(mb, __shfl_xor_sync(0xffffffffu, mb, 1));
                ma = fmaxf(ma, __shfl_xor_sync(0xffffffffu, ma, 2)) * -scl;
                mb = fmaxf(mb, __shfl_xor_sync(0xffffffffu, mb, 2)) * -scl;
                pl[h] = pack2(ex2(fmaf(a0, scl, ma)), ex2(fmaf(a1, scl, ma)));
                ph[h] = pack2(ex2(fmaf(b0, scl, mb)), ex2(fmaf(b1, scl, mb)));
            }
        }
        TSA(warp == 0 ? 4 : warp == 4 ? 20 : warp == 5 ? 28 : 63);
        uint32_t ol[10], oh[10];
        {
            uint32_t* const po = reinterpret_cast<uint32_t*>(sc + SC_O + warp * 160) + lane;
            const uint32_t ONES = 0x3F803F80u;
            float o[12][4];
#pragma unroll
            for (int hp = 0; hp < 2; hp++) {
#pragma unroll
                for (int h = hp * 2; h < hp * 2 + 2; h++) {
                    const int ta = (h >> 1) * 5 + (h & 1) * 3, tc = (h >> 1) * 5 + 2;
                    const bool mine = (lane < 16) != (h & 1);
                    const uint32_t a0 = pl[h] & mle, a1 = ph[h] & ~mle, a3 = ph[h] & mle, ap = pl[h] & ~mle;
#pragma unroll
                    for (int i = 0; i < 3; i++) o[h * 3 + i][0] = o[h * 3 + i][1] = o[h * 3 + i][2] = o[h * 3 + i][3] = 0.f;
                    mma16(o[h * 3 + 2], a0, a1, 0u, a3, mine ? vl[tc] : ONES, mine ? vh[tc] : ONES);
                    mma16(o[h * 3], a0, a1, 0u, a3, vl[ta], vh[ta]);
                    mma16(o[h * 3 + 1], a0, a1, 0u, a3, vl[ta + 1], vh[ta + 1]);
                    mma8(o[h * 3 + 2], ap, 0u, mine ? vp[tc] : ONES);
                    mma8(o[h * 3], ap, 0u, vp[ta]);
                    mma8(o[h * 3 + 1], ap, 0u, vp[ta + 1]);
                }
                if (hp && wg != HALF) bar_arrive(2, 256);
                const float (&oa)[4] = o[hp * 6 + 2], (&ob)[4] = o[hp * 6 + 5];
                const float hl = rcp(low ? ob[0] : oa[0]) * g0, hh = rcp(low ? ob[2] : oa[2]) * g1;
                const float gl = __shfl_xor_sync(0xffffffffu, hl, 2), gh = __shfl_xor_sync(0xffffffffu, hh, 2);
                const float ial = low ? gl : hl, iah = low ? gh : hh, ibl = low ? hl : gl, ibh = low ? hh : gh;
#pragma unroll
                for (int i = 0; i < 2; i++) {
                    ol[hp * 5 + i] = pack2(o[hp * 6 + i][0] * ial, o[hp * 6 + i][1] * ial);
                    oh[hp * 5 + i] = pack2(o[hp * 6 + i][2] * iah, o[hp * 6 + i][3] * iah);
                    ol[hp * 5 + 3 + i] = pack2(o[hp * 6 + 3 + i][0] * ibl, o[hp * 6 + 3 + i][1] * ibl);
                    oh[hp * 5 + 3 + i] = pack2(o[hp * 6 + 3 + i][2] * ibh, o[hp * 6 + 3 + i][3] * ibh);
                }
                ol[hp * 5 + 2] = pack2((low ? oa[0] : ob[0]) * gl, (low ? oa[1] : ob[1]) * gl);
                oh[hp * 5 + 2] = pack2((low ? oa[2] : ob[2]) * gh, (low ? oa[3] : ob[3]) * gh);
#pragma unroll
                for (int t = hp * 5; t < hp * 5 + 5; t++) {
                    st_relaxed4(po + t * 32, ol[t]);
                    st_relaxed4(po + 320 + t * 32, oh[t]);
                }
            }
        }
        TS(warp == 0 ? 5 : warp == 4 ? 21 : warp == 5 ? 29 : warp == 1 ? 31 : 63);
        const unsigned t_pub = clock();
        if (lane == 0) mbar_arrive(B_PUB);
        const uint4* ow = sc + (SC_O + HALF * 640 - hg * SC_SIZE);
        mbar_wait(B_INIT, 0);
        if (wg != HALF) {
            mbar_wait(B_PUB, 0);
            const unsigned t0 = F0_T ? t_start + max((unsigned)clock() - t_start + (wg ? F0_D : F1_D), wg ? F0_T : F1_T) : clock() + (wg ? F0_D : F1_D);
            uint32_t ph = 0;
#pragma unroll 1
            for (int i = w4 + 1 + NRS; i < 8; i += 4) {
                const uint4* src = ow + src_of(i, hg) * SC_SIZE;
                const uint32_t buf = o_buf(i), chk = buf + lane * 132;
                pace(t0, (i - 2) * O_DT);
                if (i > 4 + NRS) mbar_wait(B_DF, 0);
                if (i == 1 + NRS) TS(wg ? 3 : 4);
                uint32_t c;
                do {
                    if (elect_one()) {
                        mbar_expect_tx(B_OT + w4 * 8, 10240);
                        bulk_load(buf, src, 10240, B_OT + w4 * 8);
                    }
                    mbar_wait(B_OT + w4 * 8, ph);
                    if (i == 1 + NRS && !ph) TS(wg ? 19 : 20);
                    ph ^= 1;
                    c = max(max(lds4(chk), lds4(chk + 4096)), lds4(chk + 6144));
                } while (__any_sync(0xffffffffu, c == SENT));
                if (lane == 0) mbar_arrive(B_G2 + i * 8);
                TS(i == 2 ? 33 : 32 + i);
            }
            return;
        }

        float oc[80];
        uint32_t af[20];
        auto fetch = [&]() {
            const uint32_t* p = reinterpret_cast<const uint32_t*>(ow + src_of(1, hg) * SC_SIZE + w4 * 160) + lane;
#pragma unroll
            for (int t = 0; t < 20; t++) af[t] = ld_relaxed4(p + t * 32);
        };
        mbar_wait(B_XS, 0);
        const int orow = p0 + wg * 64 + w4 * 16;
        const uint32_t tk1 = ~lds4(SM_KEY + 16 * 4) & 2047, tk2 = ~lds4(SM_KEY + 17 * 4) & 2047;
        const uint32_t sel1 = (tk1 & 1) == par ? (tk1 >> 1) - orow : 99, sel2 = (tk2 & 1) == par ? (tk2 >> 1) - orow : 99;
        const uint32_t n0 = pack2(1.f - g0, 1.f - g0), n1 = pack2(1.f - g1, 1.f - g1);
        const uint32_t stg = SM_OUT + w4 * 5120;
        const uint32_t m128 = keep(stg + (lane & 15) * 128 + (((lane >> 4) ^ (lane & 7)) << 4));
        const uint32_t m64 = keep(stg + 4096 + (lane & 15) * 64 + (((lane >> 4) ^ ((lane >> 1) & 3)) << 4));
        const uint32_t l128 = keep(stg + (lane >> 3) * 128 + (((lane & 7) ^ (lane >> 3)) << 4));
        const uint32_t l64 = keep(stg + 4096 + r * 64 + ((cq ^ (lane >> 3)) << 4));
        char* const o128 = reinterpret_cast<char*>(P.op) + keep(((orow + (lane >> 3)) * 2 + par) * 1280 + kba * 128 + (lane & 7) * 16);
        char* const o64 = reinterpret_cast<char*>(P.op) + keep(((orow + r) * 2 + par) * 1280 + kbr * 128 + odd * 64 + cq * 16);
        if (!SETL) mbar_wait(B_G2, 0), mbar_wait(B_G2 + 8, 0);
        const bool ff = FFV == 1 || (FFV == 2 && cid < NFFN) || (FFV == 3 && wg) || (FFV == 4 && (cid < NFFN || wg));
        if (ff) {
            if (L0_T) pace(t_start, wg ? L1_T : L0_T);
            else pace(t_pub, wg ? L1_D : L0_D);
            fetch();
        }
        if (SETL) mbar_wait(B_G2, 0);
        bar_sync(2, 256);
        TS(w4 == 0 ? 6 : 63);
        wg_fence();
#pragma unroll
        for (int s = 0; s < 5; s++)
            wgmma_own(oc, ol[2 * s], oh[2 * s], ol[2 * s + 1], oh[2 * s + 1], desc_lo(wo_buf(0), 10240) + s * 128, s);
        wg_commit();
        if (!ff) {
            if (LS_T) pace(t_start, LS_T);
            fetch();
        }
        TS(w4 == 0 ? 28 : 63);
        if (OEV == 2) {
            wg_wait<0>();
            if (leader) mbar_arrive(B_OE);
        }
        if (DFV == 0) mbar_wait(B_DF, 0);
        for (;;) {
            uint32_t m = 0;
#pragma unroll
            for (int t = 0; t < 20; t++) m = max(m, af[t]);
            if (!__any_sync(0xffffffffu, m == SENT)) break;
            fetch();
        }
        TS(w4 == 0 ? 7 : 63);
        if (OEV == 0) {
            wg_wait<0>();
            if (leader) mbar_arrive(B_OE);
        }
        wg_fence();
#pragma unroll
        for (int s = 0; s < 5; s++)
            wgmma_own(oc, af[2 * s], af[10 + 2 * s], af[2 * s + 1], af[11 + 2 * s], desc_lo(wo_buf(1), 10240) + s * 128, 1);
        wg_commit();
        if (OEV == 1) {
            wg_wait<1>();
            if (leader) mbar_arrive(B_OE);
        }
        if (DFV == 1) mbar_wait(B_DF, 0);
#pragma unroll 1
        for (int i = 1 + NRS; i < 8; i++) {
            const uint32_t ao = desc_lo(0, 128) + (o_buf(i) >> 4), wo = desc_lo(0, 10240) + (wo_buf(i) >> 4);
            mbar_wait(B_G2 + i * 8, 0);
            TS(w4 == 0 ? (i < 2 ? 6 + i : i < 7 ? 9 + i : 17) : 63);
            wg_fence();
#pragma unroll
            for (int s = 0; s < 5; s++) wgmma_out(oc, ao + s * 16, wo + s * 128, 1);
            wg_commit();
            if (i < 4) {
                wg_wait<1>();
                if (i > 1 && leader) mbar_arrive(B_OE - 8 + i * 8);
            }
        }
        TS(w4 == 0 ? 8 : 63);

        if (min(sel1, sel2) < 16) {
#pragma unroll 1
            for (int j = -PV; j < 2; j++) {
                const uint32_t sel = j > 0 ? sel2 : j ? 16 : sel1;
                if (sel > 16) continue;
                if (j >= 0) mbar_wait(B_MOD, 0);
#pragma unroll
                for (int t = 0; t < 5; t++) {
                    const uint4 v = lds16(SM_U + j * 320 + cq * 80 + t * 16);
                    const uint32_t u[4] = {v.x, v.y, v.z, v.w};
#pragma unroll
                    for (int k = 0; k < 4; k++) {
                        if (sel == r) nb[8 * t + 2 * k] = hadd2(nb[8 * t + 2 * k], u[k]);
                        if (sel == r + 8) nb[8 * t + 2 * k + 1] = hadd2(nb[8 * t + 2 * k + 1], u[k]);
                    }
                }
            }
            TS(26);
        }
        wg_wait<0>();
        TS(w4 == 0 ? 9 : 63);
        const bool nan = oc[0] != oc[0] || oc[2] != oc[2];
#pragma unroll
        for (int part = 0; part < 3; part++) {
            const int s0 = part ? part * 4 - 4 : 8, ns = part ? 4 : 2;
#pragma unroll
            for (int i = 0; i < 4; i++) {
                if (i >= ns) break;
                const int s = s0 + i;
                const uint32_t y0 = hfma2(n0, nb[s * 4], pack2(oc[s * 8 + 0], oc[s * 8 + 1]));
                const uint32_t y1 = hfma2(n1, nb[s * 4 + 1], pack2(oc[s * 8 + 2], oc[s * 8 + 3]));
                const uint32_t y2 = hfma2(n0, nb[s * 4 + 2], pack2(oc[s * 8 + 4], oc[s * 8 + 5]));
                const uint32_t y3 = hfma2(n1, nb[s * 4 + 3], pack2(oc[s * 8 + 6], oc[s * 8 + 7]));
                asm volatile("stmatrix.sync.aligned.m8n8.x4.shared.b16 [%0], {%1,%2,%3,%4};"
                             ::"r"(((s < 8 ? m128 : m64) ^ ((s & 3) * 32)) + (s & 4) * 512 + rk), "r"(y0), "r"(y1), "r"(y2), "r"(y3) : "memory");
            }
            __syncwarp();
            uint4 v[4];
#pragma unroll
            for (int i = 0; i < 4; i++)
                if (i < ns) v[i] = lds16(!part ? l64 + i * 512 : (l128 ^ ((i & 1) * 64)) + i * 512 + s0 * 512);
#pragma unroll
            for (int i = 0; i < 4; i++)
                if (i < ns) *reinterpret_cast<uint4*>(!part ? o64 + i * 8 * 2560 : o128 + i * 4 * 2560 + s0 * 32) = v[i];
            if (part == 0) TS(w4 == 0 ? 1 : 63);
        }
        TS(w4 == 0 ? 10 : 63);
        TSL(w4);
        if (lane == 0) mbar_arrive(B_DONE);
        uint32_t redo;
        asm volatile("{\n.reg .pred p, q;\nsetp.ne.u32 p, %1, 0;\nbar.cta.red.or.pred q, 10, 128, p;\nselp.u32 %0, 1, 0, q;\n}"
                     : "=r"(redo) : "r"((uint32_t)nan) : "memory");
        if (redo) {
            const int cb = hg >> 1;
#pragma unroll 1
            for (int i = 0; i < 8; i++) {
                if (leader) {
                    mbar_expect_tx(B_RE, 25600);
                    tma_3d(SM_W, &P.woa, B_RE, 0, i * 80, (cb * 5 + 1) >> 1);
                    tma_2d(SM_W + 20480, &P.wob, B_RE, cb * 160 + ((cb & 1) ? 0 : 128), i * 80);
                }
#pragma unroll 1
                for (int s = 0; s < 20; s++) {
                    const int w = w4 * 640 + s * 32 + lane;
                    uint32_t v, it = 0;
                    do {
                        v = ld_relaxed4(reinterpret_cast<const uint32_t*>(ow + i * SC_SIZE) + w);
                        if (++it > (1u << 22)) fault();
                    } while ((v >> 16) == 0xFFFFu || (v & 0xFFFFu) == 0xFFFFu);
                    sts4(SM_X + w * 4, v);
                }
                fence_async_smem();
                __syncwarp();
                bar_sync(10, 128);
                mbar_wait(B_RE, i & 1);
                wg_fence();
#pragma unroll
                for (int s = 0; s < 5; s++) wgmma_out(oc, desc_lo(SM_X, 128) + s * 16, desc_lo(SM_W, 10240) + s * 128, s || i);
                wg_commit();
                wg_wait<0>();
                bar_sync(10, 128);
            }
#pragma unroll
            for (int t = 0; t < 40; t++) {
                const int col = (t < 32 ? kba * 64 + (t >> 1) * 8 : kbr * 64 + odd * 32 + ((t - 32) >> 1) * 8) + cq * 2;
                *reinterpret_cast<uint32_t*>(P.op + ((orow + r + (t & 1) * 8) * 2 + par) * 640 + col) =
                    hfma2((t & 1) ? n1 : n0, nb[t], pack2(oc[2 * t], oc[2 * t + 1]));
            }
        }
    } else if (role < 12) {
        asm volatile("setmaxnreg.dec.sync.aligned.u32 96;");
        const int t = tid - 256;
        uint32_t tag = ld_relaxed4(g_cnt);
        float gv = 0.f;
        int grow = hg * 16 + (t >> 3);
        mbar_wait(B_RG, 0);
        TS(warp == 8 ? 48 : 63);
        {
            float r0 = 0.f, r1 = 0.f, g0 = 0.f, g1 = 0.f;
            const uint32_t sw = (t >> 4) * 128 + (((t ^ (t >> 4)) & 7) << 4), hi = (t >> 3) & 1;
            mbar_wait(B_XL0, 0);
            tag = (tag * 8 + 2048) & 0xF800u;
            sts4(SM_KEY + 20 * 4, tag);
#pragma unroll 1
            for (int i = 0; i < 5; i++) {
                const int p = (RG_ORDER >> (i * 4)) & 7, kb = 2 * p + hi;
                mbar_wait(p < 3 ? B_FULL + (p & 1) * 32 : B_RG2, p == 2);
                if (p < 2) mbar_wait(B_FULL + p * 32 + 16, 0);
                const uint32_t xa = sw + (kb < 5 ? SM_X + (kb & 3) * 16384 + hg * 2048 : SM_HALO - 5 * 2048 + kb * 2048);
                const uint4 a = lds16(xa), b = lds16(xa + 1024);
                const uint4 w = lds16(SM_RED + p * 256 + (t & 15) * 16), v = lds16(SM_RED + 1280 + p * 256 + (t & 15) * 16);
                if (__ballot_sync(0xffffffffu, lane == 0 || a.w == b.w) && lane == 0 && p < 3) mbar_arrive(B_XE + p * 8);
                TS5(warp == 8 ? 51 + i : 63);
                const uint32_t as[4] = {a.x, a.y, a.z, a.w}, bs[4] = {b.x, b.y, b.z, b.w};
                const uint32_t ws[4] = {w.x, w.y, w.z, w.w}, vs[4] = {v.x, v.y, v.z, v.w};
#pragma unroll
                for (int e = 0; e < 4; e++) {
                    r0 = fmaf(bf_lo(as[e]), bf_lo(ws[e]), r0);
                    r1 = fmaf(bf_lo(bs[e]), bf_lo(ws[e]), r1);
                    g0 = fmaf(bf_lo(as[e]), bf_lo(vs[e]), g0);
                    g1 = fmaf(bf_lo(bs[e]), bf_lo(vs[e]), g1);
                    r0 = fmaf(bf_hi(as[e]), bf_hi(ws[e]), r0);
                    r1 = fmaf(bf_hi(bs[e]), bf_hi(ws[e]), r1);
                    g0 = fmaf(bf_hi(as[e]), bf_hi(vs[e]), g0);
                    g1 = fmaf(bf_hi(bs[e]), bf_hi(vs[e]), g1);
                }
            }
            const bool up = lane & 4;
            r0 = (hi ? r1 : r0) + __shfl_xor_sync(0xffffffffu, hi ? r0 : r1, 8);
            g0 = (hi ? g1 : g0) + __shfl_xor_sync(0xffffffffu, hi ? g0 : g1, 8);
            float r = (up ? g0 : r0) + __shfl_xor_sync(0xffffffffu, up ? r0 : g0, 4);
            r += __shfl_xor_sync(0xffffffffu, r, 2);
            r = bf_round(r + __shfl_xor_sync(0xffffffffu, r, 1));
            const int row = hg * 16 + (t >> 4) + hi * 8;
            const uint32_t u = f2u(r);
            if (!up) sts4(SM_KEY + (t >> 3) * 4, (((int)u < 0 ? ~u : u | 0x80000000u) & 0xFFFF0000u) | (2047 - (p0 + row) * 2 - par));
            gv = r;
            grow = row;
        }
        TS(warp == 8 ? 63 : 63);
        mbar_wait(B_RG2, 0);
        bar_sync(4, 128);
        if (warp == 8) {
            const uint32_t key = lds4(SM_KEY + (lane & 15) * 4);
            uint32_t k1 = __reduce_max_sync(0xffffffffu, key);
            uint32_t k2 = __reduce_max_sync(0xffffffffu, key == k1 ? 0u : key);
            if (elect_one()) {
                st_relaxed8(g_cand + cid, k1 | tag, k2 | tag);
                red_inc<MAPV == 3 ? 2 : 1>(g_cnt, tag);
            }
            TS(49);
        }
        if ((lane & 7) == 4) st_relaxed4(g_gate + tile * 128 + grow, f2u(bf_round(sigmoidf(gv))) | tag);
        const int cq = lane & 3, w4 = warp & 3;
        const uint32_t la = keep(cq * 256 + (((lane >> 2) ^ cq * 2) << 4));
        const uint32_t sel = keep(0x44444444u ^ (0x54u << (lane >> 2 & 1) * 8 + (lane & 16)));
        if (NFFN) {
            float4 d;
            uint4* dst;
            if (cid < NFFN) {
                float dg[8], du[8];
                mbar_wait(B_GU, 0);
                mbar_wait(B_XS, 0);
                TS(warp == 8 ? 50 : 63);
                if (GW & 1) mbar_wait(B_EMPTY + 3 * 8, 0);
                wg_fence();
#pragma unroll
                for (int i = 0; i < 10; i++) wgmma_vec(dg, desc_lo(SM_F + i * 2048, 16), desc_lo(SM_XS + i * 32, 16), i);
                wg_commit();
                mbar_wait(B_UP, 0);
                TS(warp == 10 ? 58 : 63);
                if (GW & 2) mbar_wait(B_EMPTY + 3 * 8, 0);
                wg_fence();
#pragma unroll
                for (int i = 0; i < 10; i++) wgmma_vec(du, desc_lo(SM_UP + i * 2048, 16), desc_lo(SM_XS + i * 32, 16), i);
                wg_commit();
                wg_wait<0>();
                if (lane == 0) mbar_arrive(B_GUD), mbar_arrive(B_DF);
                TS(warp == 8 ? 54 : warp == 10 ? 59 : 63);
                if (cq == 0) {
                    st_relaxed16(sc + SC_GU + w4 * 16 + (lane >> 2), f2u(dg[0]), f2u(dg[4]), f2u(du[0]), f2u(du[4]));
                    st_relaxed16(sc + SC_GU + w4 * 16 + 8 + (lane >> 2), f2u(dg[2]), f2u(dg[6]), f2u(du[2]), f2u(du[6]));
                }
            } else {
                uint4 wv[2][8], wr[4];
                mbar_wait(B_UP, 0);
                TS(warp == 10 ? 58 : 63);
                if (SP_W) mbar_wait(B_EMPTY + 3 * 8, 0);
#pragma unroll
                for (int i = 0; i < 8; i++) wv[i >> 2][4 + (i & 3)] = lds16((la ^ (i & 1) * 144) + SM_UP + w4 * 4096 + (i >> 1) * 1024);
                if (landed<4>(wv[0] + 4, lane) & landed<4>(wv[1] + 4, lane)) mbar_arrive(B_GUD);
                TS(warp == 8 ? 54 : 63);
                mbar_wait(B_GU, 0);
#pragma unroll
                for (int i = 0; i < 4; i++) wr[i] = lds16((la ^ (i & 1) * 144) + SM_F + 12288 + w4 * 2048 + (i >> 1) * 1024);
                mbar_wait(B_XS, 0);
                if (w4 == 0) {
                    uint4 pq[4];
                    pace(t_start, HS_T);
                    poll<4>(pq, g_sc + ((cid >> 1) * 4 - 148) * SC_SIZE + SC_GU + (cid & 1) * 32 + lane, SC_SIZE);
                    TS(warp == 8 ? 55 : 63);
                    swiglu(pq, SM_H + (lane & 6) * 8 + (lane >> 3) * 4 + (lane & 1) * 2, 64);
                }
                bar_sync(4, 128);
                TS(warp == 8 ? 57 : 63);
                const uint4 h = lds16(SM_H + (lane & 8) * 8 + cq * 16);
                const uint32_t hv[4] = {h.x, h.y, h.z, h.w}, hr[2] = {(w4 & 1) ? h.z : h.x, (w4 & 1) ? h.w : h.y};
                d = vec_mma<4>(wr, hr, sel);
                dst = g_sc + (cid * 5 - 520 + w4) * SC_SIZE + SC_Y + (lane & 1) * 32 + (lane >> 1);
                float c[2][2][4] = {};
                const uint32_t s2 = sel + ((sel & 0x10101010u) >> 3) * 17;
#pragma unroll
                for (int i = 7; i >= 0; i--) {
                    const uint32_t x0 = prmt(hv[i >> 1], (i & 1) ? s2 : sel), x1 = prmt(hv[i >> 1], ((i & 1) ? s2 : sel) >> 16);
#pragma unroll
                    for (int n = 0; n < 2; n++) {
                        if (i >= 4) wv[n][i - 4] = lds16((la ^ (i & 1) * 144) + SM_F - 6144 + w4 * 4096 + n * 2048 + (i >> 1) * 1024);
                        mma16(c[n][i & 1], wv[n][i].x, wv[n][i].y, wv[n][i].z, wv[n][i].w, x0, x1);
                    }
                }
#pragma unroll
                for (int n = 0; n < 2; n++)
                    st_relaxed16(dst + n * 16, f2u(c[n][0][0] + c[n][1][0]), f2u(c[n][0][1] + c[n][1][1]), f2u(c[n][0][2] + c[n][1][2]),
                                 f2u(c[n][0][3] + c[n][1][3]));
                dst += (4 - w4) * SC_SIZE + w4 * 8;
                TS(warp == 8 ? 30 : 63);
                if (lane == 0 && f2u(d.x) != SENT) mbar_arrive(B_DF);
                if (w4 & 1) {
                    sts16(SM_RED + 512 + (w4 & 2) * 256 + lane * 16, f2u(d.x), f2u(d.y), f2u(d.z), f2u(d.w));
                    bar_arrive(13 + (w4 >> 1), 64);
                } else {
                    bar_sync(13 + (w4 >> 1), 64);
                    const uint4 o = lds16(SM_RED + 512 + (w4 & 2) * 256 + lane * 16);
                    st_relaxed16(dst, f2u(d.x + u2f(o.x)), f2u(d.y + u2f(o.y)), f2u(d.z + u2f(o.z)), f2u(d.w + u2f(o.w)));
                }
            }
        } else {
            if (t < 4) mbar_arrive(B_GUD);
            if (t < 4) mbar_arrive(B_DF);
            mbar_wait(B_XS, 0);
        }
        TS(warp == 8 ? 51 : 63);
        const uint32_t k1 = lds4(SM_KEY + 16 * 4), k2 = lds4(SM_KEY + 17 * 4);
        const uint32_t mine = (tile >> 1) * 256 + HALF * 128 + par;
        const bool own1 = (~k1 & 0x781) == mine, own2 = (~k2 & 0x781) == mine;
        if ((own1 || own2) && NFFN) {
            const int rg = min(t / 40, 2), un = (hg >> 1) * 40 + t % 40;
            mbar_wait(B_RS, 0);
            pace(t_start, Y_T);
            TS(warp == 8 ? 60 : 63);
#pragma unroll 1
            for (int j = !own1; j <= own2; j++) {
                const uint4* p = g_sc + (rg * 5 + 20 + (un >> 5)) * SC_SIZE + SC_Y + j * 32 + (un & 31);
                float y[4];
                bool bad;
                do {
                    uint4 yp[7];
#pragma unroll
                    for (int i = 0; i < 7; i++) yp[i] = i < 6 || rg < 2 ? ld_relaxed16(p + i * 15 * SC_SIZE) : make_uint4(0, 0, 0, 0);
                    y[0] = y[1] = y[2] = y[3] = 0.f;
                    bad = false;
#pragma unroll
                    for (int i = 0; i < 7; i++) {
                        y[0] += u2f(yp[i].x); y[1] += u2f(yp[i].y); y[2] += u2f(yp[i].z); y[3] += u2f(yp[i].w);
                        bad |= yp[i].w == SENT;
                    }
                } while (__any_sync(0xffffffffu, bad));
                TS(warp == 8 ? 53 : 63);
                sts16(SM_SENT + j * 2048 + t * 16, f2u(y[0]), f2u(y[1]), f2u(y[2]), f2u(y[3]));
            }
            bar_sync(4, 128);
            const int j = w4 >> 1;
            if (j ? own2 : own1) {
                const uint32_t key = j ? k2 : k1, u = min(t & 63, 39), ya = SM_SENT + j * 2048 + u * 16, uq = (hg >> 1) * 40 + u;
                const float rs = bf_round(sigmoidf(u2f(((int)key < 0 ? key & 0x7FFFFFFFu : ~key) & 0xFFFF0000u)));
                const uint4 y0 = lds16(ya), y1 = lds16(ya + 640), y2 = lds16(ya + 1280);
                const uint4* q = g_sc + (uq >> 5) * SC_SIZE + SC_Y + j * 32 + (uq & 31);
                const float sx = u2f(y0.x) + u2f(y1.x) + u2f(y2.x), sy = u2f(y0.y) + u2f(y1.y) + u2f(y2.y);
                const float sz = u2f(y0.z) + u2f(y1.z) + u2f(y2.z), sw = u2f(y0.w) + u2f(y1.w) + u2f(y2.w);
                const uint32_t ua = SM_U + j * 320 + (u & 1) * 160 + ((u >> 1) + (hg & 2) * 8) % 20 * 4;
                uint4 z[4];
                pace(t_start, Y2_T);
                do {
#pragma unroll
                    for (int i = 0; i < 4; i++) z[i] = ld_relaxed16(q + i * 5 * SC_SIZE);
                } while (__any_sync(0xffffffffu, max(max(z[0].w, z[1].w), max(z[2].w, z[3].w)) == SENT));
                TS(warp == 8 ? 62 : 63);
                if ((t & 63) < 40) {
                    sts4(ua, pack2(bf_round(sx + (u2f(z[0].x) + u2f(z[1].x)) + (u2f(z[2].x) + u2f(z[3].x))) * rs,
                                   bf_round(sy + (u2f(z[0].y) + u2f(z[1].y)) + (u2f(z[2].y) + u2f(z[3].y))) * rs));
                    sts4(ua + 80, pack2(bf_round(sz + (u2f(z[0].z) + u2f(z[1].z)) + (u2f(z[2].z) + u2f(z[3].z))) * rs,
                                        bf_round(sw + (u2f(z[0].w) + u2f(z[1].w)) + (u2f(z[2].w) + u2f(z[3].w))) * rs));
                }
            }
        }
        __syncwarp();
        if (lane == 0) mbar_arrive(B_MOD);
        TS(warp == 8 ? 52 : 63);
    } else {
        asm volatile("setmaxnreg.dec.sync.aligned.u32 32;");
        if (warp == 15) {
            if (EPF_M) {
                pace(t_start, EPF_T);
                if (lane < (EPF_M << EPF_H)) l2_prefetch(P.wp + (EPF_N * 132 + (lane >> EPF_H) * 128 + bid) * 64 + (lane & EPF_H) * 32);
            }
#pragma unroll 1
            for (int i = PF_0; i < PF_N; i++) {
                pace(t_start, (i < 6 ? PF_UP : PF_DN) + i * PF_DT);
                const int ln = (i * 128 + cid) * 32 + lane;
                l2_prefetch((ln < 17280 ? P.upp : ln < 23680 ? P.wop - 17280 * 64 : P.dp - 23680 * 64) + ln * 64);
            }
            if (elect_one()) {
#pragma unroll 1
                for (int i = 0; i < (!NFFN ? 0 : cid < NFFN ? 8 : 12); i++) {
                    pace(t_start, GU_T0 + i * (cid < NFFN ? GU_DT : GU_DS) + (cid & 7) * GU_ST);
                    if (cid < NFFN) tma_2d(SM_F + i * 2560, &P.gate, B_GU, (cid >> 2) * 64, (cid & 3) * 160 + i * 20);
                    else tma_2d(SM_F - 4096 + i * 2048, &P.down, B_GU, min(i, 4 + (i >> 1)) * 64, cid * 32 - 2368 + (i > 8 ? (i & 1) * 16 : 0));
                }
            }
            __syncwarp();
            int it = (smem_u32(smem_raw) & 0xFFFFFF) == SB ? 0 : 1 << 20;
            while (!mbar_try(B_DONE, 0) || !mbar_try(B_MOD, 0))
                if (++it > (1 << 20)) fault();
        } else if (warp == 13) {
#pragma unroll 1
            for (int i = 0; i < 10; i++) sts16(SM_SENT + i * 512 + lane * 16, SENT, SENT, SENT, SENT);
            fence_async_smem();
            __syncwarp();
            if (elect_one()) {
                if (!RW_REG) mbar_expect_tx(B_RG, 2560);
                mbar_expect_tx(B_GU, cid < NFFN ? 20480 : 24576);
                asm volatile("mbarrier.expect_tx.relaxed.cta.shared::cta.b64 [%0], 10240;" ::"r"(B_RG2 + rk) : "memory");
                pace(t_start, RW1_T);
                bulk_load(SM_RED, P.w_r, 1280, B_RG);
                bulk_load(SM_RED + 1280, P.gate_w, 1280, B_RG);
#pragma unroll 1
                for (int i = 0; i < 5; i++) {
                    pace(t_start, RG1_T0 + i * RG1_DT);
                    tma_3d(SM_HALO + i * 2048, &P.xg, B_RG2, 320 + i * 64, par, p0 + hg * 16);
                }
#pragma unroll
                for (int i = 0; i < 23; i++) mbar_init(B_GUD + i * 8, i == 10 ? 8 : i == 22 || i == 9 || !i ? 4 : i < 16 ? 1 : 2);
                bulk_store(sc + SC_HALO, SM_SENT, 5120);
                asm volatile("cp.async.bulk.commit_group;\ncp.async.bulk.wait_group 0;" ::: "memory");
                mbar_arrive(B_RG2);
                TS(43);
                const unsigned goal = (ld_relaxed4(g_cnt + 32) | (NCTA - 1)) + 1;
#pragma unroll 1
                for (int i = RS_E; i < RS_N; i++) {
                    pace(t_start, RS_T0 + (i - RS_E) * RS_DT + (cid & 7) * RS_S);
                    bulk_store(sc + i * (1280 / RS_N), SM_SENT, 20480 / RS_N);
                }
                asm volatile("cp.async.bulk.commit_group;\ncp.async.bulk.wait_group 0;" ::: "memory");
                red_inc(g_cnt + 32, goal);
                mbar_arrive(B_RS);
                TS(44);
                while (ld_relaxed4(g_cnt + 32) - goal > 0x80000000u) {}
                mbar_arrive(B_INIT);
                TS(45);
            }
        } else if (warp == 14) {
            if (elect_one()) {
#pragma unroll 1
                for (int kb = 1; kb < 10; kb++) {
                    const uint32_t fb = B_FULL + (kb & 3) * 16, dst = SM_X + (kb & 3) * 16384;
                    mbar_wait(fb + (B_EMPTY - B_FULL + 8), ~(kb >> 2) & 1);
                    if (kb >= 4) mbar_wait(B_XE + (kb - 4 >> 1) * 8, 0);
                    pace(t_start, max(PACE_A - PACE_B / 2 + 2 * kb * PACE_B, PACE_W0 - X_OFF + (2 * kb + 1) * PACE));
                    tma_3d(dst, &P.x2, fb, kb * 64, par, p0);
                    TS5(41 + kb);
                }
            }
            __syncwarp();
            pace(t_start, CAND_T);
            {
                const uint32_t tag = lds4(SM_KEY + 20 * 4);
                uint4 c[2], v;
                do {
                    c[0] = ld_relaxed16(g_cand + lane * 2);
                    c[1] = ld_relaxed16(g_cand + lane * 2 + 64);
                    v = ld_relaxed16(g_gate + tile * 128 + lane * 4);
                } while (__any_sync(0xffffffffu, ((c[0].x ^ tag) | (c[0].z ^ tag) | (c[1].x ^ tag) | (c[1].z ^ tag) | (v.x ^ tag) |
                                                  (v.y ^ tag) | (v.z ^ tag) | (v.w ^ tag)) & 0xF800u));
                const uint32_t a1 = max(c[0].x, c[0].z), b1 = max(c[1].x, c[1].z), l1 = max(a1, b1);
                const uint32_t l2 = max(max(max(c[0].y, c[0].w), max(c[1].y, c[1].w)),
                                        max(max(min(c[0].x, c[0].z), min(c[1].x, c[1].z)), min(a1, b1)));
                const uint32_t k1 = __reduce_max_sync(0xffffffffu, l1);
                const uint32_t k2 = __reduce_max_sync(0xffffffffu, l1 == k1 ? l2 : l1);
                sts16(SM_GATE + lane * 16, v.x, v.y, v.z, v.w);
                __syncwarp();
                if (elect_one()) {
                    bulk_load(SM_XS, P.xp + (~k1 & 2047) * 640 + (cid & 3) * 160, 320, B_XS);
                    bulk_load(SM_XS + 320, P.xp + (~k2 & 2047) * 640 + (cid & 3) * 160, 320, B_XS);
                    sts16(SM_KEY + 16 * 4, k1, k2, 0, 0);
                    mbar_expect_tx(B_XS, 640);
                    mbar_arrive(B_GT);
                    TS(56);
                }
            }
            bar_sync(12, 64);
            pace(t_start, 0);
            pace(clock(), HALO_D);
            TS(24);
            uint4 hv[5];
            poll<5>(hv, sc + (SC_HALO - (tile < 2 ? 0 : 16 * SC_SIZE) + lane), 32);
#pragma unroll
            for (int s = 0; s < 5; s++) sts16(SM_HALO + s * 512 + lane * 16, hv[s].x, hv[s].y, hv[s].z, hv[s].w);
            bar_arrive(8, 64);
            TS(25);
        } else {
            if (elect_one()) {
#pragma unroll 1
                for (int s = W_S0; s < 20; s++) {
                    const uint32_t fb = B_FULL + (s & 7) * 8, dst = SM_W + (s & 7) * 15360;
                    mbar_wait(fb + (B_EMPTY - B_FULL), ~(s >> 3) & 1);
                    pace(t_start, max(PACE_A + s * PACE_B, PACE_W0 + s * PACE));
                    mbar_expect_tx(fb, (s & 1) ? 15360 : 15360 + 16384);
                    tma_3d(dst, &P.w, fb, wcm, s * 32, 0);
                    tma_3d(dst + 12288, &P.wr, fb, wcr, s * 32, 0);
                    TS2(20 + s);
                    if (s == W_S0) TS(41);
                }
                mbar_wait(B_RG2, 0);
                if (NFFN) {
                    mbar_wait(B_EMPTY + 5 * 8, 1);
                    mbar_expect_tx(B_UP, cid < NFFN ? 20480 : 16384);
                    TS(46);
                    if (cid < NFFN) tma_2d(SM_UP, &P.up, B_UP, (cid >> 2) * 64, (cid & 3) * 160);
                    else
#pragma unroll 1
                        for (int i = 0; i < 8; i++) tma_2d(SM_UP + i * 2048, &P.down, B_UP, i * 64, cid * 32 - 2352);
                }
                const int cb = hg >> 1, ca = (cb * 5 + 1) >> 1, cr = cb * 160 + ((cb & 1) ? 0 : 128);
                if (C0_T) pace(t_start, C0_T);
#pragma unroll 1
                for (int j = 0; j < 8; j++) {
                    const int i = j ^ (j == 3 || j == 4 ? 7 : 0);
                    if (j != 3) mbar_wait(j < 3 ? B_EMPTY + ((2 * j + 7) & 7) * 8 : B_GUD + (j - 4) * 8, j == 0);
                    if (j >= 5) {
                        if (C5_T) pace(t_start, (j == 5 ? C5_T : j == 6 ? C6_T : C7_T) - HALF * C_O);
                        else pace(clock(), j == 5 ? C5_D : C6_D);
                    }
                    const uint32_t dst = wo_buf(i), gb = B_G2 + i * 8;
                    mbar_expect_tx(gb, 25600);
                    tma_3d(dst, &P.woa, gb, 0, src_of(i, hg) * 80, ca);
                    tma_2d(dst + 20480, &P.wob, gb, cr, src_of(i, hg) * 80);
                }
            }
        }
    }
}

typedef CUresult (*EncodeFn)(CUtensorMap*, CUtensorMapDataType, cuuint32_t, void*, const cuuint64_t*, const cuuint64_t*,
                             const cuuint32_t*, const cuuint32_t*, CUtensorMapInterleave, CUtensorMapSwizzle,
                             CUtensorMapL2promotion, CUtensorMapFloatOOBfill);

void encode(EncodeFn fn, CUtensorMap* m, const void* ptr, int rank, const cuuint64_t* dims, const cuuint64_t* strides,
            const cuuint32_t* box, CUtensorMapSwizzle swz) {
    const cuuint32_t es[4] = {1, 1, 1, 1};
    fn(m, CU_TENSOR_MAP_DATA_TYPE_BFLOAT16, rank, const_cast<void*>(ptr), dims, strides, box, es,
       CU_TENSOR_MAP_INTERLEAVE_NONE, swz, CU_TENSOR_MAP_L2_PROMOTION_L2_128B, CU_TENSOR_MAP_FLOAT_OOB_FILL_NONE);
}

}

extern "C" void kernel_launch(void* const* d_in, const int* in_sizes, int n_in, void* d_out, int out_size) {
    (void)in_sizes; (void)n_in; (void)out_size;
    Params P;
    P.xp = (const __nv_bfloat16*)d_in[0];
    P.wp = (const __nv_bfloat16*)d_in[1];
    P.wop = (const __nv_bfloat16*)d_in[2];
    P.dp = (const __nv_bfloat16*)d_in[7];
    P.upp = (const __nv_bfloat16*)d_in[6];
    P.op = (__nv_bfloat16*)d_out;
    P.w_r = (const __nv_bfloat16*)d_in[4];
    P.gate_w = (const __nv_bfloat16*)d_in[8];

    void* fp = nullptr;
    cudaDriverEntryPointQueryResult st;
    cudaGetDriverEntryPoint("cuTensorMapEncodeTiled", &fp, cudaEnableDefault, &st);
    EncodeFn fn = (EncodeFn)fp;
    const cuuint64_t xd[3] = {640, 2, 1024}, xs[2] = {1280, 2560};
    const cuuint32_t bx[3] = {64, 1, 64}, bx2[3] = {64, 1, 128};
    encode(fn, &P.x2, d_in[0], 3, xd, xs, bx2, CU_TENSOR_MAP_SWIZZLE_128B);
    encode(fn, &P.x, d_in[0], 3, xd, xs, bx, CU_TENSOR_MAP_SWIZZLE_128B);
    const cuuint64_t wd[3] = {640, 640, 3}, ws[2] = {3840, 1280};
    const cuuint32_t bw[3] = {64, 32, 3}, bwr[3] = {16, 32, 3};
    encode(fn, &P.w, d_in[1], 3, wd, ws, bw, CU_TENSOR_MAP_SWIZZLE_128B);
    encode(fn, &P.wr, d_in[1], 3, wd, ws, bwr, CU_TENSOR_MAP_SWIZZLE_32B);
    const cuuint64_t ad[3] = {64, 640, 10}, as[2] = {1280, 128}, bd[2] = {640, 640};
    const cuuint32_t ba[3] = {64, 80, 2}, bb[2] = {32, 80};
    encode(fn, &P.woa, d_in[2], 3, ad, as, ba, CU_TENSOR_MAP_SWIZZLE_128B);
    encode(fn, &P.wob, d_in[2], 2, bd, as, bb, CU_TENSOR_MAP_SWIZZLE_128B);
    const cuuint64_t gd[2] = {1728, 640}, gs[1] = {3456}, dd[2] = {640, 1728};
    const cuuint32_t bg[2] = {64, 20}, bu[2] = {64, 160}, bdn[2] = {64, 16}, bxg[3] = {64, 1, 16};
    encode(fn, &P.xg, d_in[0], 3, xd, xs, bxg, CU_TENSOR_MAP_SWIZZLE_128B);
    encode(fn, &P.gate, d_in[5], 2, gd, gs, bg, CU_TENSOR_MAP_SWIZZLE_128B);
    encode(fn, &P.up, d_in[6], 2, gd, gs, bu, CU_TENSOR_MAP_SWIZZLE_128B);
    encode(fn, &P.up2, d_in[6], 2, gd, gs, bg, CU_TENSOR_MAP_SWIZZLE_128B);
    encode(fn, &P.down, d_in[7], 2, dd, as, bdn, CU_TENSOR_MAP_SWIZZLE_128B);

    cudaFuncSetAttribute(fused_kernel, cudaFuncAttributeMaxDynamicSharedMemorySize, SM_TOTAL);
    fused_kernel<<<NCTA + (MAPV == 3 ? 0 : NEXTRA), 512, SM_TOTAL, cudaStreamPerThread>>>(P);
}
```

```cpp
#include <cuda_runtime.h>
#include <cuda_bf16.h>
#include <cuda.h>
#include <stdint.h>

namespace {

constexpr int NCTA = 128, NEXTRA = 4;
constexpr int NFFN = 108;
constexpr uint32_t SENT = 0xFFFFFFFFu;

constexpr uint32_t SB = 1024;
constexpr uint32_t SM_W = SB;
constexpr uint32_t SM_X = SB + 122880;
constexpr uint32_t SM_F = SB + 192512;
constexpr uint32_t SM_HALO = SB + 212992;
constexpr uint32_t SM_BAR = SB + 223232;
constexpr uint32_t SM_PROF = SB + 223744;
constexpr uint32_t SM_KEY = SB + 224000;
constexpr uint32_t SM_RED = SB + 224128;
constexpr uint32_t SM_XS = SB + 226688;
constexpr uint32_t SM_SENT = SB + 227328;
constexpr uint32_t SM_U = SM_RED + 1920;
constexpr uint32_t SM_H = SM_RED + 1536;
constexpr uint32_t SM_GATE = SM_RED;
constexpr uint32_t SM_TOTAL = 232448;
constexpr uint32_t SM_HALO1 = SM_X + 32768;
constexpr uint32_t SM_UP = SM_W + 61440;
constexpr uint32_t SM_OUT = SM_W + 61440;

constexpr uint32_t B_XL0 = SM_BAR, B_FULL = SM_BAR + 8, B_GT = SM_BAR + 72, B_RG = SM_BAR + 80, B_RG2 = SM_BAR + 88,
                   B_XS = SM_BAR + 96, B_EMPTY = SM_BAR + 128, B_DONE = SM_BAR + 192, B_XE = SM_BAR + 200,
                   B_GUD = SM_BAR + 224, B_OE = SM_BAR + 232, B_OT = SM_BAR + 264, B_MOD = SM_BAR + 296,
                   B_GU = SM_BAR + 104, B_UP = SM_BAR + 112, B_RS = SM_BAR + 312, B_INIT = SM_BAR + 320,
                   B_RE = SM_BAR + 328, B_PUB = SM_BAR + 304, B_G2 = SM_BAR + 336, B_DF = SM_BAR + 400;

struct Params {
    CUtensorMap x, x2, w, wr, woa, wob, xg, gate, up, down;
    __nv_bfloat16* op;
    const __nv_bfloat16 *xp, *wp, *w_r, *gate_w;
};

constexpr int SC_O = 0;
constexpr int SC_HALO = 1280;
constexpr int SC_GU = 1440;
constexpr int SC_Y = 1504;
constexpr int SC_SIZE = 1600;
__device__ __align__(128) uint4 g_sc[NCTA * SC_SIZE];
__device__ __align__(128) uint2 g_cand[NCTA];
__device__ __align__(16) uint32_t g_gate[2048];
__device__ __align__(128) unsigned g_cnt[64];
#define TS(i) do { } while (0)
#define TS2(i) do { } while (0)
#define TSX(i) do { } while (0)

#define TSL(i) do { } while (0)
#define TS5(i) do { } while (0)
__device__ __forceinline__ uint32_t smem_u32(const void* p) { return (uint32_t)__cvta_generic_to_shared(p); }
__device__ __forceinline__ void fault() { asm volatile("st.shared.u32 [%0], %0;" ::"r"(0x100001) : "memory"); }
__device__ __forceinline__ void mbar_init(uint32_t bar, uint32_t cnt) {
    asm volatile("mbarrier.init.shared::cta.b64 [%0], %1;" ::"r"(bar), "r"(cnt) : "memory");
}
__device__ __forceinline__ void mbar_expect_tx(uint32_t bar, uint32_t bytes) {
    asm volatile("mbarrier.arrive.expect_tx.shared::cta.b64 _, [%0], %1;" ::"r"(bar), "r"(bytes) : "memory");
}
__device__ __forceinline__ void mbar_arrive(uint32_t bar) {
    asm volatile("mbarrier.arrive.shared::cta.b64 _, [%0];" ::"r"(bar) : "memory");
}
__device__ __forceinline__ bool mbar_try(uint32_t bar, uint32_t parity) {
    uint32_t ok;
    asm volatile("{\n.reg .pred p;\nmbarrier.try_wait.parity.shared::cta.b64 p, [%1], %2;\nselp.u32 %0, 1, 0, p;\n}"
                 : "=r"(ok) : "r"(bar), "r"(parity) : "memory");
    return ok;
}
__device__ __forceinline__ void mbar_wait(uint32_t bar, uint32_t parity) {
    asm volatile("{\n.reg .pred p;\nAGAIN:\nmbarrier.try_wait.parity.shared::cta.b64 p, [%0], %1;\n@!p bra AGAIN;\n}"
                 ::"r"(bar), "r"(parity) : "memory");
}
__device__ __forceinline__ void tma_2d(uint32_t dst, const CUtensorMap* m, uint32_t bar, int c0, int c1) {
    asm volatile("cp.async.bulk.tensor.2d.shared::cluster.global.mbarrier::complete_tx::bytes [%0], [%1, {%3, %4}], [%2];"
                 ::"r"(dst), "l"(m), "r"(bar), "r"(c0), "r"(c1) : "memory");
}
__device__ __forceinline__ void bulk_load(uint32_t dst, const void* src, uint32_t bytes, uint32_t bar) {
    asm volatile("cp.async.bulk.shared::cluster.global.mbarrier::complete_tx::bytes [%0], [%1], %2, [%3];"
                 ::"r"(dst), "l"(src), "r"(bytes), "r"(bar) : "memory");
}
__device__ __forceinline__ void bulk_store(void* dst, uint32_t src, uint32_t bytes) {
    asm volatile("cp.async.bulk.global.shared::cta.bulk_group [%0], [%1], %2;" ::"l"(dst), "r"(src), "r"(bytes) : "memory");
}
__device__ __forceinline__ void tma_3d(uint32_t dst, const CUtensorMap* m, uint32_t bar, int c0, int c1, int c2) {
    asm volatile("cp.async.bulk.tensor.3d.shared::cluster.global.mbarrier::complete_tx::bytes [%0], [%1, {%3, %4, %5}], [%2];"
                 ::"r"(dst), "l"(m), "r"(bar), "r"(c0), "r"(c1), "r"(c2) : "memory");
}
__device__ __forceinline__ void fence_async_smem() { asm volatile("fence.proxy.async.shared::cta;" ::: "memory"); }
__device__ __forceinline__ void wg_fence() { asm volatile("wgmma.fence.sync.aligned;" ::: "memory"); }
__device__ __forceinline__ void wg_commit() { asm volatile("wgmma.commit_group.sync.aligned;" ::: "memory"); }
template <int N> __device__ __forceinline__ void wg_wait() { asm volatile("wgmma.wait_group.sync.aligned %0;" ::"n"(N) : "memory"); }
__device__ __forceinline__ void bar_sync(int id, int n) { asm volatile("bar.cta.sync %0, %1;" ::"r"(id), "r"(n) : "memory"); }
__device__ __forceinline__ void bar_arrive(int id, int n) { asm volatile("bar.cta.arrive %0, %1;" ::"r"(id), "r"(n) : "memory"); }

__device__ constexpr uint32_t desc_lo(uint32_t addr, uint32_t lbo) { return (addr >> 4) | ((lbo >> 4) << 16); }
__device__ __forceinline__ bool elect_one() {
    uint32_t p;
    asm volatile("{\n.reg .pred p;\nelect.sync _|p, 0xffffffff;\nselp.u32 %0, 1, 0, p;\n}" : "=r"(p));
    return p;
}
__device__ __forceinline__ uint32_t ld_relaxed4(const void* p) {
    uint32_t v;
    asm volatile("ld.relaxed.gpu.global.u32 %0, [%1];" : "=r"(v) : "l"(p) : "memory");
    return v;
}
__device__ __forceinline__ void st_relaxed4(void* p, uint32_t v) {
    asm volatile("st.relaxed.gpu.global.u32 [%0], %1;" ::"l"(p), "r"(v) : "memory");
}
template <int N = 1>
__device__ __forceinline__ void red_inc(unsigned* p, unsigned after) {
    asm volatile("red.relaxed.gpu.global.add.u32 [%0], %2;" ::"l"(p), "r"(after), "n"(N) : "memory");
}
__device__ __forceinline__ uint32_t lds4(uint32_t a) {
    uint32_t v;
    asm volatile("ld.shared.u32 %0, [%1];" : "=r"(v) : "r"(a) : "memory");
    return v;
}
__device__ __forceinline__ float2 lds8f(uint32_t a) {
    float2 v;
    asm volatile("ld.shared.v2.f32 {%0, %1}, [%2];" : "=f"(v.x), "=f"(v.y) : "r"(a) : "memory");
    return v;
}
__device__ __forceinline__ void sts4(uint32_t a, uint32_t v) { asm volatile("st.shared.u32 [%0], %1;" ::"r"(a), "r"(v) : "memory"); }
__device__ __forceinline__ uint32_t hadd2(uint32_t a, uint32_t b) {
    uint32_t d;
    asm("add.rn.bf16x2 %0, %1, %2;" : "=r"(d) : "r"(a), "r"(b));
    return d;
}
__device__ __forceinline__ uint32_t hfma2(uint32_t a, uint32_t b, uint32_t c) {
    uint32_t d;
    asm("fma.rn.bf16x2 %0, %1, %2, %3;" : "=r"(d) : "r"(a), "r"(b), "r"(c));
    return d;
}
__device__ __forceinline__ uint4 ld_relaxed16(const void* p) {
    uint4 v;
    asm volatile("{\n.reg .b128 t;\n.reg .b64 lo, hi;\nld.relaxed.gpu.global.b128 t, [%4];\nmov.b128 {lo, hi}, t;\n"
                 "mov.b64 {%0, %1}, lo;\nmov.b64 {%2, %3}, hi;\n}" : "=r"(v.x), "=r"(v.y), "=r"(v.z), "=r"(v.w) : "l"(p) : "memory");
    return v;
}
__device__ __forceinline__ void st_relaxed16(void* p, uint32_t a, uint32_t b, uint32_t c, uint32_t d) {
    uint64_t lo = (uint64_t)a | ((uint64_t)b << 32), hi = (uint64_t)c | ((uint64_t)d << 32);
    asm volatile("{\n.reg .b128 t;\nmov.b128 t, {%1, %2};\nst.relaxed.gpu.global.b128 [%0], t;\n}" ::"l"(p), "l"(lo), "l"(hi) : "memory");
}
__device__ __forceinline__ void st_relaxed8(void* p, uint32_t a, uint32_t b) {
    asm volatile("{\n.reg .b64 t;\nmov.b64 t, {%1, %2};\nst.relaxed.gpu.global.b64 [%0], t;\n}" ::"l"(p), "r"(a), "r"(b) : "memory");
}
__device__ __forceinline__ uint4 lds16(uint32_t a) {
    uint4 v;
    asm volatile("ld.shared.v4.u32 {%0, %1, %2, %3}, [%4];" : "=r"(v.x), "=r"(v.y), "=r"(v.z), "=r"(v.w) : "r"(a) : "memory");
    return v;
}
__device__ __forceinline__ void sts16(uint32_t a, uint32_t x, uint32_t y, uint32_t z, uint32_t w) {
    asm volatile("st.shared.v4.u32 [%0], {%1, %2, %3, %4};" ::"r"(a), "r"(x), "r"(y), "r"(z), "r"(w) : "memory");
}
__device__ __forceinline__ uint32_t pack2(float lo, float hi) {
    uint32_t r;
    asm("cvt.rn.bf16x2.f32 %0, %1, %2;" : "=r"(r) : "f"(hi), "f"(lo));
    return r;
}
__device__ __forceinline__ uint32_t pack2v(float lo, float hi) {
    uint32_t r;
    asm volatile("cvt.rn.bf16x2.f32 %0, %1, %2;" : "=r"(r) : "f"(hi), "f"(lo));
    return r;
}
__device__ __forceinline__ float bf_lo(uint32_t u) { return __uint_as_float(u << 16); }
__device__ __forceinline__ float bf_hi(uint32_t u) { return __uint_as_float(u & 0xFFFF0000u); }
__device__ __forceinline__ float bf_round(float f) { return __bfloat162float(__float2bfloat16_rn(f)); }
__device__ __forceinline__ uint32_t prmt(uint32_t a, uint32_t sel) {
    uint32_t d;
    asm("prmt.b32 %0, %1, 0, %2;" : "=r"(d) : "r"(a), "r"(sel));
    return d;
}
__device__ __forceinline__ uint32_t movm(uint32_t a) {
    uint32_t d;
    asm volatile("movmatrix.sync.aligned.m8n8.trans.b16 %0, %1;" : "=r"(d) : "r"(a));
    return d;
}
__device__ __forceinline__ void mma16(float (&c)[4], uint32_t a0, uint32_t a1, uint32_t a2, uint32_t a3, uint32_t b0, uint32_t b1) {
    asm volatile("mma.sync.aligned.m16n8k16.row.col.f32.bf16.bf16.f32 {%0,%1,%2,%3}, {%4,%5,%6,%7}, {%8,%9}, {%0,%1,%2,%3};"
                 : "+f"(c[0]), "+f"(c[1]), "+f"(c[2]), "+f"(c[3]) : "r"(a0), "r"(a1), "r"(a2), "r"(a3), "r"(b0), "r"(b1));
}
__device__ __forceinline__ void mma8(float (&c)[4], uint32_t a0, uint32_t a1, uint32_t b0) {
    asm volatile("mma.sync.aligned.m16n8k8.row.col.f32.bf16.bf16.f32 {%0,%1,%2,%3}, {%4,%5}, {%6}, {%0,%1,%2,%3};"
                 : "+f"(c[0]), "+f"(c[1]), "+f"(c[2]), "+f"(c[3]) : "r"(a0), "r"(a1), "r"(b0));
}
__device__ __forceinline__ float ex2(float x) { float y; asm("ex2.approx.ftz.f32 %0, %1;" : "=f"(y) : "f"(x)); return y; }
__device__ __forceinline__ float rcp(float x) { float y; asm("rcp.approx.ftz.f32 %0, %1;" : "=f"(y) : "f"(x)); return y; }
__device__ __forceinline__ float sigmoidf(float z) { return rcp(1.0f + ex2(z * -1.4426950408889634f)); }
__device__ __forceinline__ float u2f(uint32_t u) { return __uint_as_float(u); }
__device__ __forceinline__ uint32_t f2u(float f) { return __float_as_uint(f); }

__device__ __forceinline__ void wgmma_main(float (&d)[96], uint32_t a, uint32_t b, int scale_d) {
    asm volatile("{\n.reg .pred p;\n.reg .b64 da, db;\nsetp.ne.b32 p, %98, 0;\n"
        "mov.b64 da, {%96, 0x40000040};\nmov.b64 db, {%97, 0x40000040};\n"
        "wgmma.mma_async.sync.aligned.m64n192k16.f32.bf16.bf16 "
        "{%0, %1, %2, %3, %4, %5, %6, %7, %8, %9, %10, %11, %12, %13, %14, %15, "
        "%16, %17, %18, %19, %20, %21, %22, %23, %24, %25, %26, %27, %28, %29, %30, %31, "
        "%32, %33, %34, %35, %36, %37, %38, %39, %40, %41, %42, %43, %44, %45, %46, %47, "
        "%48, %49, %50, %51, %52, %53, %54, %55, %56, %57, %58, %59, %60, %61, %62, %63, "
        "%64, %65, %66, %67, %68, %69, %70, %71, %72, %73, %74, %75, %76, %77, %78, %79, "
        "%80, %81, %82, %83, %84, %85, %86, %87, %88, %89, %90, %91, %92, %93, %94, %95}, "
        "da, db, p, 1, 1, 0, 1;\n}\n"
        : "+f"(d[0]), "+f"(d[1]), "+f"(d[2]), "+f"(d[3]), "+f"(d[4]), "+f"(d[5]), "+f"(d[6]), "+f"(d[7]),
          "+f"(d[8]), "+f"(d[9]), "+f"(d[10]), "+f"(d[11]), "+f"(d[12]), "+f"(d[13]), "+f"(d[14]), "+f"(d[15]),
          "+f"(d[16]), "+f"(d[17]), "+f"(d[18]), "+f"(d[19]), "+f"(d[20]), "+f"(d[21]), "+f"(d[22]), "+f"(d[23]),
          "+f"(d[24]), "+f"(d[25]), "+f"(d[26]), "+f"(d[27]), "+f"(d[28]), "+f"(d[29]), "+f"(d[30]), "+f"(d[31]),
          "+f"(d[32]), "+f"(d[33]), "+f"(d[34]), "+f"(d[35]), "+f"(d[36]), "+f"(d[37]), "+f"(d[38]), "+f"(d[39]),
          "+f"(d[40]), "+f"(d[41]), "+f"(d[42]), "+f"(d[43]), "+f"(d[44]), "+f"(d[45]), "+f"(d[46]), "+f"(d[47]),
          "+f"(d[48]), "+f"(d[49]), "+f"(d[50]), "+f"(d[51]), "+f"(d[52]), "+f"(d[53]), "+f"(d[54]), "+f"(d[55]),
          "+f"(d[56]), "+f"(d[57]), "+f"(d[58]), "+f"(d[59]), "+f"(d[60]), "+f"(d[61]), "+f"(d[62]), "+f"(d[63]),
          "+f"(d[64]), "+f"(d[65]), "+f"(d[66]), "+f"(d[67]), "+f"(d[68]), "+f"(d[69]), "+f"(d[70]), "+f"(d[71]),
          "+f"(d[72]), "+f"(d[73]), "+f"(d[74]), "+f"(d[75]), "+f"(d[76]), "+f"(d[77]), "+f"(d[78]), "+f"(d[79]),
          "+f"(d[80]), "+f"(d[81]), "+f"(d[82]), "+f"(d[83]), "+f"(d[84]), "+f"(d[85]), "+f"(d[86]), "+f"(d[87]),
          "+f"(d[88]), "+f"(d[89]), "+f"(d[90]), "+f"(d[91]), "+f"(d[92]), "+f"(d[93]), "+f"(d[94]), "+f"(d[95])
        : "r"(a), "r"(b), "r"(scale_d));
}

__device__ __forceinline__ void wgmma_rem(float (&d)[24], uint32_t a, uint32_t b, int scale_d) {
    asm volatile("{\n.reg .pred p;\n.reg .b64 da, db;\nsetp.ne.b32 p, %26, 0;\n"
        "mov.b64 da, {%24, 0x40000040};\nmov.b64 db, {%25, 0xC0000010};\n"
        "wgmma.mma_async.sync.aligned.m64n48k16.f32.bf16.bf16 "
        "{%0, %1, %2, %3, %4, %5, %6, %7, %8, %9, %10, %11, %12, %13, %14, %15, "
        "%16, %17, %18, %19, %20, %21, %22, %23}, "
        "da, db, p, 1, 1, 0, 1;\n}\n"
        : "+f"(d[0]), "+f"(d[1]), "+f"(d[2]), "+f"(d[3]), "+f"(d[4]), "+f"(d[5]), "+f"(d[6]), "+f"(d[7]),
          "+f"(d[8]), "+f"(d[9]), "+f"(d[10]), "+f"(d[11]), "+f"(d[12]), "+f"(d[13]), "+f"(d[14]), "+f"(d[15]),
          "+f"(d[16]), "+f"(d[17]), "+f"(d[18]), "+f"(d[19]), "+f"(d[20]), "+f"(d[21]), "+f"(d[22]), "+f"(d[23])
        : "r"(a), "r"(b), "r"(scale_d));
}

__device__ __forceinline__ void wgmma_out(float (&d)[80], uint32_t a, uint32_t b, int scale_d) {
    asm volatile("{\n.reg .pred p;\n.reg .b64 da, db;\nsetp.ne.b32 p, %82, 0;\n"
        "mov.b64 da, {%80, 0x50};\nmov.b64 db, {%81, 0x40000040};\n"
        "wgmma.mma_async.sync.aligned.m64n160k16.f32.bf16.bf16 "
        "{%0, %1, %2, %3, %4, %5, %6, %7, %8, %9, %10, %11, %12, %13, %14, %15, "
        "%16, %17, %18, %19, %20, %21, %22, %23, %24, %25, %26, %27, %28, %29, %30, %31, "
        "%32, %33, %34, %35, %36, %37, %38, %39, %40, %41, %42, %43, %44, %45, %46, %47, "
        "%48, %49, %50, %51, %52, %53, %54, %55, %56, %57, %58, %59, %60, %61, %62, %63, "
        "%64, %65, %66, %67, %68, %69, %70, %71, %72, %73, %74, %75, %76, %77, %78, %79}, "
        "da, db, p, 1, 1, 0, 1;\n}\n"
        : "+f"(d[0]), "+f"(d[1]), "+f"(d[2]), "+f"(d[3]), "+f"(d[4]), "+f"(d[5]), "+f"(d[6]), "+f"(d[7]),
          "+f"(d[8]), "+f"(d[9]), "+f"(d[10]), "+f"(d[11]), "+f"(d[12]), "+f"(d[13]), "+f"(d[14]), "+f"(d[15]),
          "+f"(d[16]), "+f"(d[17]), "+f"(d[18]), "+f"(d[19]), "+f"(d[20]), "+f"(d[21]), "+f"(d[22]), "+f"(d[23]),
          "+f"(d[24]), "+f"(d[25]), "+f"(d[26]), "+f"(d[27]), "+f"(d[28]), "+f"(d[29]), "+f"(d[30]), "+f"(d[31]),
          "+f"(d[32]), "+f"(d[33]), "+f"(d[34]), "+f"(d[35]), "+f"(d[36]), "+f"(d[37]), "+f"(d[38]), "+f"(d[39]),
          "+f"(d[40]), "+f"(d[41]), "+f"(d[42]), "+f"(d[43]), "+f"(d[44]), "+f"(d[45]), "+f"(d[46]), "+f"(d[47]),
          "+f"(d[48]), "+f"(d[49]), "+f"(d[50]), "+f"(d[51]), "+f"(d[52]), "+f"(d[53]), "+f"(d[54]), "+f"(d[55]),
          "+f"(d[56]), "+f"(d[57]), "+f"(d[58]), "+f"(d[59]), "+f"(d[60]), "+f"(d[61]), "+f"(d[62]), "+f"(d[63]),
          "+f"(d[64]), "+f"(d[65]), "+f"(d[66]), "+f"(d[67]), "+f"(d[68]), "+f"(d[69]), "+f"(d[70]), "+f"(d[71]),
          "+f"(d[72]), "+f"(d[73]), "+f"(d[74]), "+f"(d[75]), "+f"(d[76]), "+f"(d[77]), "+f"(d[78]), "+f"(d[79])
        : "r"(a), "r"(b), "r"(scale_d));
}

__device__ __forceinline__ void wgmma_own(float (&d)[80], uint32_t a0, uint32_t a1, uint32_t a2, uint32_t a3, uint32_t b, int scale_d) {
    asm volatile("{\n.reg .pred p;\n.reg .b64 db;\nsetp.ne.b32 p, %85, 0;\nmov.b64 db, {%84, 0x40000040};\n"
        "wgmma.mma_async.sync.aligned.m64n160k16.f32.bf16.bf16 "
        "{%0, %1, %2, %3, %4, %5, %6, %7, %8, %9, %10, %11, %12, %13, %14, %15, "
        "%16, %17, %18, %19, %20, %21, %22, %23, %24, %25, %26, %27, %28, %29, %30, %31, "
        "%32, %33, %34, %35, %36, %37, %38, %39, %40, %41, %42, %43, %44, %45, %46, %47, "
        "%48, %49, %50, %51, %52, %53, %54, %55, %56, %57, %58, %59, %60, %61, %62, %63, "
        "%64, %65, %66, %67, %68, %69, %70, %71, %72, %73, %74, %75, %76, %77, %78, %79}, "
        "{%80, %81, %82, %83}, db, p, 1, 1, 1;\n}\n"
        : "+f"(d[0]), "+f"(d[1]), "+f"(d[2]), "+f"(d[3]), "+f"(d[4]), "+f"(d[5]), "+f"(d[6]), "+f"(d[7]),
          "+f"(d[8]), "+f"(d[9]), "+f"(d[10]), "+f"(d[11]), "+f"(d[12]), "+f"(d[13]), "+f"(d[14]), "+f"(d[15]),
          "+f"(d[16]), "+f"(d[17]), "+f"(d[18]), "+f"(d[19]), "+f"(d[20]), "+f"(d[21]), "+f"(d[22]), "+f"(d[23]),
          "+f"(d[24]), "+f"(d[25]), "+f"(d[26]), "+f"(d[27]), "+f"(d[28]), "+f"(d[29]), "+f"(d[30]), "+f"(d[31]),
          "+f"(d[32]), "+f"(d[33]), "+f"(d[34]), "+f"(d[35]), "+f"(d[36]), "+f"(d[37]), "+f"(d[38]), "+f"(d[39]),
          "+f"(d[40]), "+f"(d[41]), "+f"(d[42]), "+f"(d[43]), "+f"(d[44]), "+f"(d[45]), "+f"(d[46]), "+f"(d[47]),
          "+f"(d[48]), "+f"(d[49]), "+f"(d[50]), "+f"(d[51]), "+f"(d[52]), "+f"(d[53]), "+f"(d[54]), "+f"(d[55]),
          "+f"(d[56]), "+f"(d[57]), "+f"(d[58]), "+f"(d[59]), "+f"(d[60]), "+f"(d[61]), "+f"(d[62]), "+f"(d[63]),
          "+f"(d[64]), "+f"(d[65]), "+f"(d[66]), "+f"(d[67]), "+f"(d[68]), "+f"(d[69]), "+f"(d[70]), "+f"(d[71]),
          "+f"(d[72]), "+f"(d[73]), "+f"(d[74]), "+f"(d[75]), "+f"(d[76]), "+f"(d[77]), "+f"(d[78]), "+f"(d[79])
        : "r"(a0), "r"(a1), "r"(a2), "r"(a3), "r"(b), "r"(scale_d));
}

__device__ __forceinline__ void wgmma_vec(float (&d)[8], uint32_t a, uint32_t b, int scale_d) {
    asm volatile("{\n.reg .pred p;\n.reg .b64 da, db;\nsetp.ne.b32 p, %10, 0;\n"
        "mov.b64 da, {%8, 0x40000040};\nmov.b64 db, {%9, 0x14};\n"
        "wgmma.mma_async.sync.aligned.m64n16k16.f32.bf16.bf16 {%0, %1, %2, %3, %4, %5, %6, %7}, da, db, p, 1, 1, 1, 0;\n}\n"
        : "+f"(d[0]), "+f"(d[1]), "+f"(d[2]), "+f"(d[3]), "+f"(d[4]), "+f"(d[5]), "+f"(d[6]), "+f"(d[7])
        : "r"(a), "r"(b), "r"(scale_d));
}

#define TSA(i) do { } while (0)
#define MAP_TILE(b) ((((b) >> 1) & 14) | ((b) & 1))
#define MAP_HG(b) (((b) >> 4 & 14) | ((b) >> 1 & 1))
#define HALF (int)(bid >> 1 & 1)
#define GM 0x78A0
#define SKEW 4
#define W_S0 2
#define EPF_N 15
#define EPF_M 15
#define RG_ORDER 0x24130
#define RS_N 10
#define DN_R 5
#define P2W 4
#define EPF_T 900
#define PACE_A 250
#define PACE_B 450
#define PACE_W0 (-600)
#define PACE 500
#define X_OFF 350
#define RW1_T 0
#define RG1_T0 1700
#define RG1_DT 200
#define DN_T0 500
#define DN_DT 68
#define DN_T1 100000
#define DN_D1 45
#define GU_T0 3600
#define GU_DT 750
#define GU_DS (GU_DT * 7 / 11)
#define GU_ST 90
#define CAND_T 9000
#define RS_T0 9000
#define RS_DT 120
#define C0_T 11100
#define C5_D 0
#define C6_D 100
#define HALO_D 450
#define H_T 13300
#define H_C 1000
#define HS_T 13300
#define L0_T 14450
#define L1_T 14050
#define LS_T 14450
#define F0_T 14650
#define F1_T 14300
#define F0_D 200
#define F1_D 0
#define O_DT 300
#define Y_T 15500
#define Y2_T 17000

__device__ __forceinline__ uint32_t keep(uint32_t v) { return __shfl_xor_sync(0xffffffffu, v, 0); }
__device__ __forceinline__ uint32_t ukeep(uint32_t v) { return __shfl_sync(0xffffffffu, v, 0); }
__device__ __forceinline__ void ldsm2(uint32_t* d, uint32_t a) {
    asm volatile("ldmatrix.sync.aligned.m8n8.x4.shared.b16 {%0,%1,%2,%3}, [%8];\nldmatrix.sync.aligned.m8n8.x4.shared.b16 {%4,%5,%6,%7}, [%9];"
                 : "=r"(d[0]), "=r"(d[1]), "=r"(d[2]), "=r"(d[3]), "=r"(d[4]), "=r"(d[5]), "=r"(d[6]), "=r"(d[7])
                 : "r"(a), "r"(a ^ 32) : "memory");
}
__device__ __forceinline__ void ldsm_t(uint32_t (&d)[4], uint32_t a) {
    asm volatile("ldmatrix.sync.aligned.m8n8.x4.trans.shared.b16 {%0,%1,%2,%3}, [%4];"
                 : "=r"(d[0]), "=r"(d[1]), "=r"(d[2]), "=r"(d[3]) : "r"(a) : "memory");
}
template <bool SWP, int SEG, int E>
__device__ __forceinline__ void pack_blocks(uint32_t (&d)[10], const float (&am)[96], const float (&ar)[24]) {
#pragma unroll
    for (int t = 0; t < 10; t++) {
        const float* p = (SWP ? t < 2 : t >= 8) ? ar + (SEG * 2 + (t & 1)) * 4 + E : am + (SEG * 8 + t - (SWP ? 2 : 0)) * 4 + E;
        d[t] = pack2v(p[0], p[1]);
    }
}
__device__ __forceinline__ int src_of(int i, int hg) {
    return i == 0 ? hg : (0x75316240u >> (i - (i <= (hg >> 2 | hg & 2))) * 4 & 7) ^ (hg & 1);
}

__device__ __forceinline__ uint32_t o_buf(int i) { return __byte_perm(0xD199ADA3u, 0xC7BDu, i - 2 | 0x7770) << 10; }
__device__ constexpr uint32_t wo_buf(int i) { return SM_W + ((0x10342103u >> i * 4) & 7) * 30720; }

template <int N>
__device__ __forceinline__ void poll(uint4 (&a)[N], const uint4* p, int stride) {
    bool bad;
    do {
        bad = false;
#pragma unroll
        for (int s = 0; s < N; s++) a[s] = ld_relaxed16(p + s * stride);
#pragma unroll
        for (int s = 0; s < N; s++) bad |= a[s].w == SENT;
    } while (__any_sync(0xffffffffu, bad));
}
__device__ __forceinline__ void pace(unsigned t0, int t) {
    asm volatile("{\n.reg .pred p;\n.reg .s32 d;\nAGAIN:\nmov.u32 d, %%clock;\nsub.s32 d, d, %0;\nsetp.lt.s32 p, d, 0;\n"
                 "@p nanosleep.u32 20;\n@p bra AGAIN;\n}" ::"r"(t0 + t) : "memory");
}
__device__ __forceinline__ void l2_prefetch(const void* p) { asm volatile("prefetch.global.L2 [%0];" ::"l"(p) : "memory"); }

template <int N>
__device__ __forceinline__ bool landed(const uint4* w, int lane) {
    uint32_t a = 0;
#pragma unroll
    for (int i = 0; i < N; i++) a ^= w[i].w;
    return __ballot_sync(0xffffffffu, lane == 0 || a == 0) && lane == 0;
}
__device__ __forceinline__ void swiglu(const uint4 (&a)[4], uint32_t dst, uint32_t stride) {
    const float g0 = bf_round((u2f(a[0].x) + u2f(a[1].x)) + (u2f(a[2].x) + u2f(a[3].x)));
    const float g1 = bf_round((u2f(a[0].y) + u2f(a[1].y)) + (u2f(a[2].y) + u2f(a[3].y)));
    const float u0 = bf_round((u2f(a[0].z) + u2f(a[1].z)) + (u2f(a[2].z) + u2f(a[3].z)));
    const float u1 = bf_round((u2f(a[0].w) + u2f(a[1].w)) + (u2f(a[2].w) + u2f(a[3].w)));
    const uint32_t h = pack2(bf_round(g0 * sigmoidf(g0)) * u0, bf_round(g1 * sigmoidf(g1)) * u1);
    asm volatile("st.shared.u16 [%0], %2;\nst.shared.u16 [%1], %3;" ::"r"(dst), "r"(dst + stride), "h"((uint16_t)h), "h"((uint16_t)(h >> 16)) : "memory");
}
template <int N>
__device__ __forceinline__ float4 vec_mma(const uint4 (&w)[N], const uint32_t* x, uint32_t sel) {
    float c[4][4] = {};
    const uint32_t s[4] = {sel, sel >> 16, sel + ((sel & 0x10101010u) >> 3) * 17, (sel + ((sel & 0x10101010u) >> 3) * 17) >> 16};
#pragma unroll
    for (int i = 0; i < N; i++)
        mma16(c[i & 3], w[i].x, w[i].y, w[i].z, w[i].w, prmt(x[i >> 1], s[(i & 1) * 2]), prmt(x[i >> 1], s[(i & 1) * 2 + 1]));
    return make_float4((c[0][0] + c[1][0]) + (c[2][0] + c[3][0]), (c[0][1] + c[1][1]) + (c[2][1] + c[3][1]),
                       (c[0][2] + c[1][2]) + (c[2][2] + c[3][2]), (c[0][3] + c[1][3]) + (c[2][3] + c[3][3]));
}

__global__ void __launch_bounds__(512, 1) fused_kernel(const __grid_constant__ Params P) {
    extern __shared__ __align__(1024) uint8_t smem_raw[];
    const unsigned t_start = clock();
    const int tid = threadIdx.x, lane = tid & 31;
    unsigned sm, bid;
    asm("mov.u32 %0, %%smid;" : "=r"(sm));
    const CUtensorMap* mx = &P.x;
    asm volatile("" : "+l"(mx));
    if ((unsigned)(tid - 480) < EPF_N) l2_prefetch(P.wp + (tid * 132 + sm) * 64 - 480 * 132 * 64);
    const int warp = __shfl_sync(0xffffffffu, threadIdx.x >> 5, 0);
    asm("{\n.reg .pred p;\n.reg .b32 t, u;\nshr.u32 t, %1, 1;\nmad.lo.s32 u, t, 14, -928;\nmad.lo.s32 t, t, 37, -925;\nmax.s32 t, t, 0;\n"
        "shr.u32 t, t, 7;\nand.b32 t, t, 14;\nsetp.ge.u32 p, %1, 124;\nselp.b32 t, u, t, p;\nadd.s32 %0, %1, t;\n}" : "=r"(bid) : "r"(sm));
    bid ^= GM >> (bid & 14) & 6;
    const int hg = MAP_HG(bid), par = bid & 1, p0 = (MAP_TILE(bid) >> 1) * 128;
    const bool swp = (hg & 3) == 3;
    const int wcm = hg * 80 + (swp ? 16 : 0), wcr = hg * 80 + (swp ? 0 : 64);
    if (warp == 0) {
        if (elect_one()) {
#pragma unroll
            for (int i = 0; i < 4; i++) mbar_init(SM_BAR + i * 8, 1);
            asm volatile("fence.mbarrier_init.release.cluster;" ::: "memory");
            if (bid < NCTA) {
                mbar_expect_tx(B_FULL, 15360 + 8192);
                tma_3d(SM_X + 8192, mx, B_FULL, 0, par, p0 + 64);
                tma_3d(SM_W, mx + 2, B_FULL, wcm, 0, 0);
                tma_3d(SM_W + 12288, mx + 3, B_FULL, wcr, 0, 0);
                TS(40);
                mbar_expect_tx(B_XL0, 8192);
                tma_3d(SM_X, mx, B_XL0, 0, par, p0);
                mbar_expect_tx(B_FULL + 8, 15360);
                tma_3d(SM_W + 15360, mx + 2, B_FULL + 8, wcm, 32, 0);
                tma_3d(SM_W + 15360 + 12288, mx + 3, B_FULL + 8, wcr, 32, 0);
            }
        }
    }
    if ((unsigned)(warp - 1) < 6 && elect_one()) {
#pragma unroll
        for (int i = 0; i < 4; i++) mbar_init(SM_BAR + warp * 32 + i * 8, warp < 4 ? 1 : warp < 6 ? 2 : 4);
        asm volatile("fence.mbarrier_init.release.cluster;" ::: "memory");
    }
    asm volatile("" : "+r"(bid));
    const int role = bid >= NCTA ? -1 : warp, e = sm & 3;
    const int tile = MAP_TILE(bid), cid = tile * 8 + hg;
    uint4* const sc = g_sc + cid * SC_SIZE;
    __syncthreads();

    if (role < 0) {
        const int half = warp >> 3;
        if (!NFFN) {
            if (tid == 0) red_inc<NCTA / NEXTRA>(g_cnt, 0);
            return;
        }
        uint32_t wf[DN_R][5][4], la[5];
        auto rows = [&](uint32_t l) {
#pragma unroll
            for (int i = 0; i < 5; i++) {
                const uint32_t c = (warp & 7) * 10 + 2 * i + (l >> 3 & 1);
                la[i] = SB + half * 20480 + (c >> 3) * 2048 + (l & 7) * 128 + (l >> 4) * 1024 + (((c ^ l) & 7) << 4);
            }
        };
        rows(lane);
        auto fetch = [&](int j, int n, uint32_t bar) {
#pragma unroll 1
            for (int h = 0; h < n; h++) {
                pace(t_start, min(DN_T0 + (j * 20 + h * 10 + warp) * DN_DT, DN_T1 + (j * 20 + h * 10 + warp) * DN_D1));
                tma_2d(SB + (j % 5) * 40960 + h * 20480 + warp * 2048, &P.down, bar, warp * 64, e * 272 + (j + h * 9) * 16);
            }
        };
        if (warp < 10 && elect_one()) {
            if (warp <= DN_R) mbar_expect_tx(B_FULL + warp * 8, warp < DN_R ? 40960 : (17 - 2 * DN_R) * 20480);
#pragma unroll 1
            for (int j = 0; j < 5; j++) fetch(j, 2, B_FULL + j * 8);
        }
        const uint32_t tag = (ukeep(ld_relaxed4(g_cnt)) * 8 + 2048) & 0xF800u;
#pragma unroll
        for (int j = 0; j < DN_R; j++) {
            uint32_t any = 0;
            mbar_wait(B_FULL + j * 8, 0);
#pragma unroll
            for (int i = 0; i < 5; i++) {
                ldsm_t(wf[j][i], la[i] + j * 40960);
                any ^= wf[j][i][3];
            }
            if (j < 4) {
                if (__syncthreads_count(any == 0) == 1000) fault();
                if (warp < 10 && elect_one()) fetch(j + 5, j < 3 ? 2 : 1, B_FULL + DN_R * 8);
                if (j == 0 && tid == 0) red_inc<NCTA / NEXTRA>(g_cnt, tag);
            }
            TSX(warp == 0 && j == 0 ? 0 : warp == 0 && j == 3 ? 1 : 63);
        }
        if (warp < 9) {
            pace(t_start, H_T - H_C);
            uint4 a[4];
            do {
                a[0] = ld_relaxed16(g_cand + lane * 2);
                a[1] = ld_relaxed16(g_cand + lane * 2 + 64);
            } while (__any_sync(0xffffffffu, ((a[0].x ^ tag) | (a[0].z ^ tag) | (a[1].x ^ tag) | (a[1].z ^ tag)) & 0xF800u));
            const int u = min(tid, 271), f = e * 272 + u;
            pace(t_start, H_T);
            TSX(warp == 0 ? 3 : 63);
            poll<4>(a, g_sc + (f >> 6) * 4 * SC_SIZE + SC_GU + (f & 63), SC_SIZE);
            TSX(warp == 0 ? 4 : warp == 8 ? 5 : 63);
            swiglu(a, SM_RED + (u >> 4) * 64 + (u & 6) * 4 + (u & 8) / 2 + (u & 1) * 2, 32);
        }
        rows(keep(lane));
        mbar_wait(B_FULL + DN_R * 8, 0);
        TSX(warp == 15 ? 2 : 63);
        __syncthreads();
        float c[5][4] = {};
#pragma unroll
        for (int j = 0; j < 9; j++) {
            if (j == 8 && half) break;
            const float2 b = lds8f(SM_RED + half * 576 + j * 64 + (lane & 7) * 8);
            if (j == 1) TSX(warp == 0 ? 6 : 63);
#pragma unroll
            for (int i = 0; i < 5; i++) {
                if (j >= DN_R) ldsm_t(wf[j % DN_R][i], la[i] + (j % 5) * 40960);
                mma16(c[i], wf[j % DN_R][i][0], wf[j % DN_R][i][1], wf[j % DN_R][i][2], wf[j % DN_R][i][3], f2u(b.x), f2u(b.y));
            }
        }
        const uint32_t ra = SB + 7 * 20480 + half * 5248 + (lane & 1) * 2624 + (warp & 7) * 320 + (lane & 2) * 16 + (lane >> 2) * 4;
#pragma unroll
        for (int i = 0; i < 5; i++) sts4(ra + i * 64, f2u((lane & 2) ? ((lane & 1) ? c[i][3] : c[i][2]) : ((lane & 1) ? c[i][1] : c[i][0])));
        TSX(warp == 0 ? 7 : 63);
        __syncthreads();
        if (warp < 10) {
            const uint32_t ya = SB + 7 * 20480 + (warp & 1) * 2624 + (warp >> 1) * 512 + lane * 16;
            const uint4 y0 = lds16(ya), y1 = lds16(ya + 5248);
            st_relaxed16(g_sc + (e * 5 + (warp >> 1)) * SC_SIZE + SC_Y + (tid & 63), f2u(u2f(y0.x) + u2f(y1.x)), f2u(u2f(y0.y) + u2f(y1.y)),
                         f2u(u2f(y0.z) + u2f(y1.z)), f2u(u2f(y0.w) + u2f(y1.w)));
        }
    } else if (role < 8) {
        asm volatile("setmaxnreg.inc.sync.aligned.u32 192;");
        const int wg = warp >> 2;
        const bool leader = (tid & 127) == 0;
        float am[96], ar[24];
        if (wg == 0) mbar_wait(B_XL0, 0);
        bool rel = false;
        uint32_t nb[40];
        const int odd = (hg >> 1) & 1, kba = ukeep(wg != HALF ? 99 : ((hg >> 1) * 5 + 1) >> 1), kbr = ukeep(kba + 2 - odd * 3);
        const int kbs = wg ? -1 : (20 - SKEW) / 2;
        const uint32_t xrow = keep(SM_X + (warp * 16 + (lane & 15)) * 128 + (((lane >> 4) ^ (lane & 7)) << 4));
#pragma unroll 1
        for (int kb = 0; kb < 10; kb++) {
            const uint32_t fb = B_FULL + (kb & 3) * 16, wo = (kb & 3) * 1920, ph = (kb >> 2) & 1;
            const uint32_t xo = desc_lo(SM_X, 16) + wg * 512 + (kb & 3) * 1024;
#pragma unroll
            for (int h = 0; h < 2; h++) {
                mbar_wait(fb + h * 8, ph);
                if (kb == 0 && h == 0) TS(warp == 0 ? 0 : warp == 4 ? 16 : 63);
                TS2(warp == P2W ? kb * 2 + h : 63);
                {
                    const uint32_t xa = (xrow ^ h * 64) + (kb & 3) * 16384;
                    if (kb == kba) ldsm2(nb + h * 8, xa);
                    if (kb == kba + 1) ldsm2(nb + 16 + h * 8, xa);
                    if (h == 0 && kb == kbr) ldsm2(nb + 32, xa ^ (odd * 64));
                }
                wg_wait<1>();
                if (rel && (h == 0 || kb != kbs)) mbar_arrive(B_EMPTY + ((kb * 16 - 16) & 48) + h * 8);
                if (h == 0 && kb == kbs) {
                    wg_wait<0>();
                    if (rel) mbar_arrive(B_EMPTY + ((19 - SKEW) & 7) * 8);
                    bar_sync(5, 256);
                }
                wg_fence();
                wgmma_main(am, xo + h * 4, desc_lo(SM_W + h * 15360, 4096) + wo, h || kb);
                wgmma_rem(ar, xo + h * 4, desc_lo(SM_W + h * 15360 + 12288, 1024) + wo, h || kb);
                wgmma_main(am, xo + h * 4 + 2, desc_lo(SM_W + h * 15360 + 2048, 4096) + wo, 1);
                wgmma_rem(ar, xo + h * 4 + 2, desc_lo(SM_W + h * 15360 + 12288 + 512, 1024) + wo, 1);
                wg_commit();
            }
            rel = leader;
        }
        if (wg == 1) bar_arrive(5, 256);
        mbar_wait(B_XE + 16, 0);
        mbar_wait(B_RG2, 0);
        mbar_wait(B_EMPTY + 5 * 8, 1);
        wg_wait<0>();
        if (leader) mbar_arrive(B_EMPTY + 3 * 8);
        TS(warp == 0 ? 2 : warp == 4 ? 18 : 63);
        TS2(warp == 0 ? 41 : warp == 4 ? 40 : 63);

        uint32_t kl[10], kh[10], vl[10], vh[10], ql[10], qh[10], kp[10], vp[10];
        if (swp) {
            pack_blocks<true, 1, 2>(kh, am, ar);
            pack_blocks<true, 2, 2>(vh, am, ar);
        } else {
            pack_blocks<false, 1, 2>(kh, am, ar);
            pack_blocks<false, 2, 2>(vh, am, ar);
        }
        const int w4 = warp & 3;
        const uint32_t pbuf = (wg ? SM_HALO1 : SM_HALO) + w4 * 2560 + lane * 16;
        const uint32_t hbuf = warp == 3 ? SM_HALO1 + lane * 16 : pbuf + 2560;
        {
            const uint32_t ex[20] = {kh[0], kh[1], kh[3], kh[4], kh[5], kh[6], kh[8], kh[9], kh[2], kh[7],
                                     vh[0], vh[1], vh[2], vh[3], vh[4], vh[5], vh[6], vh[7], vh[8], vh[9]};
            if (warp == 7) {
                uint4* const hp = sc + SC_HALO + lane;
#pragma unroll
                for (int s = 0; s < 5; s++) st_relaxed16(hp + s * 32, ex[4 * s], ex[4 * s + 1], ex[4 * s + 2], ex[4 * s + 3]);
                bar_arrive(12, 64);
            } else {
#pragma unroll
                for (int s = 0; s < 5; s++) sts16(hbuf + s * 512, ex[4 * s], ex[4 * s + 1], ex[4 * s + 2], ex[4 * s + 3]);
            }
        }
        TS(warp == 7 ? 22 : warp == 3 ? 23 : 63);
        if (warp == 3) bar_arrive(11, 64);
        if (swp) {
            pack_blocks<true, 2, 0>(vl, am, ar);
            pack_blocks<true, 0, 0>(ql, am, ar);
            pack_blocks<true, 0, 2>(qh, am, ar);
            pack_blocks<true, 1, 0>(kl, am, ar);
        } else {
            pack_blocks<false, 2, 0>(vl, am, ar);
            pack_blocks<false, 0, 0>(ql, am, ar);
            pack_blocks<false, 0, 2>(qh, am, ar);
            pack_blocks<false, 1, 0>(kl, am, ar);
        }
#pragma unroll
        for (int t = 0; t < 10; t++) { vl[t] = movm(vl[t]); vh[t] = movm(vh[t]); }
        mbar_wait(B_RS, 0);
        mbar_wait(B_GT, 0);
        const float g0 = bf_hi(lds4(SM_GATE + warp * 64 + (lane & 28))), g1 = bf_hi(lds4(SM_GATE + 32 + warp * 64 + (lane & 28)));

        const int r = lane >> 2, cq = lane & 3;
        const bool no_prev = warp == 0 && tile < 2, low = cq < 2;
        const bool le0 = 2 * cq <= r, le1 = 2 * cq + 1 <= r;
        const uint32_t mle = (le0 ? 0xFFFFu : 0u) | (le1 ? 0xFFFF0000u : 0u);
        const float scl = 0.22360679774997896f * 1.4426950408889634f;
        uint32_t pl[4], ph[4];
        {
            float sl[4][4], sh[4][4], sp[4][4];
            auto exchange = [&]() {
            TSA(warp == 1 ? 26 : 63);
            bar_sync(6 + wg, 128);
            if (w4 == 0) bar_sync(8 + wg * 3, 64);
            {
                const uint4 a = lds16(pbuf), b = lds16(pbuf + 512), c = lds16(pbuf + 1024), d = lds16(pbuf + 1536), e = lds16(pbuf + 2048);
                kp[0] = a.x; kp[1] = a.y; kp[3] = a.z; kp[4] = a.w; kp[5] = b.x; kp[6] = b.y; kp[8] = b.z; kp[9] = b.w;
                kp[2] = c.x; kp[7] = c.y; vp[0] = c.z; vp[1] = c.w; vp[2] = d.x; vp[3] = d.y; vp[4] = d.z; vp[5] = d.w;
                vp[6] = e.x; vp[7] = e.y; vp[8] = e.z; vp[9] = e.w;
            }
            TSA(warp == 0 ? 3 : warp == 4 ? 19 : warp == 5 ? 27 : 63);
            };
            exchange();
#pragma unroll
            for (int h = 0; h < 4; h++) {
                const int ta = (h >> 1) * 5 + (h & 1) * 3, tc = (h >> 1) * 5 + 2;
                const uint32_t ml = low != (h & 1) ? ql[tc] : 0u, mh = low != (h & 1) ? qh[tc] : 0u;
#pragma unroll
                for (int e = 0; e < 4; e++) sl[h][e] = sh[h][e] = sp[h][e] = 0.f;
                mma16(sl[h], ql[ta], qh[ta], ql[ta + 1], qh[ta + 1], kl[ta], kl[ta + 1]);
                mma16(sh[h], ql[ta], qh[ta], ql[ta + 1], qh[ta + 1], kh[ta], kh[ta + 1]);
                mma8(sl[h], ml, mh, kl[tc]);
                mma8(sh[h], ml, mh, kh[tc]);
            }
#pragma unroll
            for (int h = 0; h < 4; h++) {
                const int ta = (h >> 1) * 5 + (h & 1) * 3, tc = (h >> 1) * 5 + 2;
                mma16(sp[h], ql[ta], qh[ta], ql[ta + 1], qh[ta + 1], kp[ta], kp[ta + 1]);
                mma8(sp[h], low != (h & 1) ? ql[tc] : 0u, low != (h & 1) ? qh[tc] : 0u, kp[tc]);
            }
#pragma unroll
            for (int t = 0; t < 10; t++) vp[t] = movm(vp[t]);
#pragma unroll
            for (int h = 0; h < 4; h++) {
                if (no_prev) sp[h][0] = sp[h][1] = -1e9f / 0.22360679774997896f;
                const float a0 = le0 ? sl[h][0] : sp[h][0], a1 = le1 ? sl[h][1] : sp[h][1];
                const float b0 = le0 ? sh[h][2] : sl[h][2], b1 = le1 ? sh[h][3] : sl[h][3];
                float ma = fmaxf(a0, a1), mb = fmaxf(b0, b1);
                ma = fmaxf(ma, __shfl_xor_sync(0xffffffffu, ma, 1));
                mb = fmaxf(mb, __shfl_xor_sync(0xffffffffu, mb, 1));
                ma = fmaxf(ma, __shfl_xor_sync(0xffffffffu, ma, 2)) * -scl;
                mb = fmaxf(mb, __shfl_xor_sync(0xffffffffu, mb, 2)) * -scl;
                pl[h] = pack2(ex2(fmaf(a0, scl, ma)), ex2(fmaf(a1, scl, ma)));
                ph[h] = pack2(ex2(fmaf(b0, scl, mb)), ex2(fmaf(b1, scl, mb)));
            }
        }
        TSA(warp == 0 ? 4 : warp == 4 ? 20 : warp == 5 ? 28 : 63);
        uint32_t ol[10], oh[10];
        {
            uint32_t* const po = reinterpret_cast<uint32_t*>(sc + SC_O + warp * 160) + lane;
            const uint32_t ONES = 0x3F803F80u;
            float o[12][4];
#pragma unroll
            for (int hp = 0; hp < 2; hp++) {
#pragma unroll
                for (int h = hp * 2; h < hp * 2 + 2; h++) {
                    const int ta = (h >> 1) * 5 + (h & 1) * 3, tc = (h >> 1) * 5 + 2;
                    const bool mine = (lane < 16) != (h & 1);
                    const uint32_t a0 = pl[h] & mle, a1 = ph[h] & ~mle, a3 = ph[h] & mle, ap = pl[h] & ~mle;
#pragma unroll
                    for (int i = 0; i < 3; i++) o[h * 3 + i][0] = o[h * 3 + i][1] = o[h * 3 + i][2] = o[h * 3 + i][3] = 0.f;
                    mma16(o[h * 3 + 2], a0, a1, 0u, a3, mine ? vl[tc] : ONES, mine ? vh[tc] : ONES);
                    mma16(o[h * 3], a0, a1, 0u, a3, vl[ta], vh[ta]);
                    mma16(o[h * 3 + 1], a0, a1, 0u, a3, vl[ta + 1], vh[ta + 1]);
                    mma8(o[h * 3 + 2], ap, 0u, mine ? vp[tc] : ONES);
                    mma8(o[h * 3], ap, 0u, vp[ta]);
                    mma8(o[h * 3 + 1], ap, 0u, vp[ta + 1]);
                }
                if (hp && wg != HALF) bar_arrive(2, 256);
                const float (&oa)[4] = o[hp * 6 + 2], (&ob)[4] = o[hp * 6 + 5];
                const float hl = rcp(low ? ob[0] : oa[0]) * g0, hh = rcp(low ? ob[2] : oa[2]) * g1;
                const float gl = __shfl_xor_sync(0xffffffffu, hl, 2), gh = __shfl_xor_sync(0xffffffffu, hh, 2);
                const float ial = low ? gl : hl, iah = low ? gh : hh, ibl = low ? hl : gl, ibh = low ? hh : gh;
#pragma unroll
                for (int i = 0; i < 2; i++) {
                    ol[hp * 5 + i] = pack2(o[hp * 6 + i][0] * ial, o[hp * 6 + i][1] * ial);
                    oh[hp * 5 + i] = pack2(o[hp * 6 + i][2] * iah, o[hp * 6 + i][3] * iah);
                    ol[hp * 5 + 3 + i] = pack2(o[hp * 6 + 3 + i][0] * ibl, o[hp * 6 + 3 + i][1] * ibl);
                    oh[hp * 5 + 3 + i] = pack2(o[hp * 6 + 3 + i][2] * ibh, o[hp * 6 + 3 + i][3] * ibh);
                }
                ol[hp * 5 + 2] = pack2((low ? oa[0] : ob[0]) * gl, (low ? oa[1] : ob[1]) * gl);
                oh[hp * 5 + 2] = pack2((low ? oa[2] : ob[2]) * gh, (low ? oa[3] : ob[3]) * gh);
#pragma unroll
                for (int t = hp * 5; t < hp * 5 + 5; t++) {
                    st_relaxed4(po + t * 32, ol[t]);
                    st_relaxed4(po + 320 + t * 32, oh[t]);
                }
            }
        }
        TS(warp == 0 ? 5 : warp == 4 ? 21 : warp == 5 ? 29 : warp == 1 ? 31 : 63);
        if (lane == 0) mbar_arrive(B_PUB);
        const uint4* ow = sc + (SC_O + HALF * 640 - hg * SC_SIZE);
        mbar_wait(B_INIT, 0);
        if (wg != HALF) {
            mbar_wait(B_PUB, 0);
            const unsigned t0 = t_start + max((unsigned)clock() - t_start + (wg ? F0_D : F1_D), wg ? F0_T : F1_T);
            uint32_t ph = 0;
#pragma unroll 1
            for (int i = w4 + 2; i < 8; i += 4) {
                const uint4* src = ow + src_of(i, hg) * SC_SIZE;
                const uint32_t buf = o_buf(i), chk = buf + lane * 132;
                pace(t0, (i - 2) * O_DT);
                if (i > 5) mbar_wait(B_DF, 0);
                if (i == 2) TS(wg ? 3 : 4);
                uint32_t c;
                do {
                    if (elect_one()) {
                        mbar_expect_tx(B_OT + w4 * 8, 10240);
                        bulk_load(buf, src, 10240, B_OT + w4 * 8);
                    }
                    mbar_wait(B_OT + w4 * 8, ph);
                    if (i == 2 && !ph) TS(wg ? 19 : 20);
                    ph ^= 1;
                    c = max(max(lds4(chk), lds4(chk + 4096)), lds4(chk + 6144));
                } while (__any_sync(0xffffffffu, c == SENT));
                if (lane == 0) mbar_arrive(B_G2 + i * 8);
                TS(i == 2 ? 33 : 32 + i);
            }
            return;
        }

        float oc[80];
        uint32_t af[20];
        auto fetch = [&]() {
            const uint32_t* p = reinterpret_cast<const uint32_t*>(ow + src_of(1, hg) * SC_SIZE + w4 * 160) + lane;
#pragma unroll
            for (int t = 0; t < 20; t++) af[t] = ld_relaxed4(p + t * 32);
        };
        mbar_wait(B_XS, 0);
        const int orow = p0 + wg * 64 + w4 * 16;
        const uint32_t tk1 = ~lds4(SM_KEY + 16 * 4) & 2047, tk2 = ~lds4(SM_KEY + 17 * 4) & 2047;
        const uint32_t sel1 = (tk1 & 1) == par ? (tk1 >> 1) - orow : 99, sel2 = (tk2 & 1) == par ? (tk2 >> 1) - orow : 99;
        const uint32_t n0 = pack2(1.f - g0, 1.f - g0), n1 = pack2(1.f - g1, 1.f - g1);
        const uint32_t stg = SM_OUT + w4 * 5120;
        const uint32_t m128 = keep(stg + (lane & 15) * 128 + (((lane >> 4) ^ (lane & 7)) << 4));
        const uint32_t m64 = keep(stg + 4096 + (lane & 15) * 64 + (((lane >> 4) ^ ((lane >> 1) & 3)) << 4));
        const uint32_t l128 = keep(stg + (lane >> 3) * 128 + (((lane & 7) ^ (lane >> 3)) << 4));
        const uint32_t l64 = keep(stg + 4096 + r * 64 + ((cq ^ (lane >> 3)) << 4));
        char* const o128 = reinterpret_cast<char*>(P.op) + keep(((orow + (lane >> 3)) * 2 + par) * 1280 + kba * 128 + (lane & 7) * 16);
        char* const o64 = reinterpret_cast<char*>(P.op) + keep(((orow + r) * 2 + par) * 1280 + kbr * 128 + odd * 64 + cq * 16);
        mbar_wait(B_G2, 0);
        mbar_wait(B_G2 + 8, 0);
        const bool ff = cid < NFFN;
        if (ff) {
            pace(t_start, wg ? L1_T : L0_T);
            fetch();
        }
        bar_sync(2, 256);
        TS(w4 == 0 ? 6 : 63);
        wg_fence();
#pragma unroll
        for (int s = 0; s < 5; s++)
            wgmma_own(oc, ol[2 * s], oh[2 * s], ol[2 * s + 1], oh[2 * s + 1], desc_lo(wo_buf(0), 10240) + s * 128, s);
        wg_commit();
        if (!ff) {
            pace(t_start, LS_T);
            fetch();
        }
        TS(w4 == 0 ? 28 : 63);
        mbar_wait(B_DF, 0);
        for (;;) {
            uint32_t m = 0;
#pragma unroll
            for (int t = 0; t < 20; t++) m = max(m, af[t]);
            if (!__any_sync(0xffffffffu, m == SENT)) break;
            fetch();
        }
        TS(w4 == 0 ? 7 : 63);
        wg_fence();
#pragma unroll
        for (int s = 0; s < 5; s++)
            wgmma_own(oc, af[2 * s], af[10 + 2 * s], af[2 * s + 1], af[11 + 2 * s], desc_lo(wo_buf(1), 10240) + s * 128, 1);
        wg_commit();
        wg_wait<1>();
        if (leader) mbar_arrive(B_OE);
#pragma unroll 1
        for (int i = 2; i < 8; i++) {
            const uint32_t ao = desc_lo(0, 128) + (o_buf(i) >> 4), wo = desc_lo(0, 10240) + (wo_buf(i) >> 4);
            mbar_wait(B_G2 + i * 8, 0);
            TS(w4 == 0 ? (i < 2 ? 6 + i : i < 7 ? 9 + i : 17) : 63);
            wg_fence();
#pragma unroll
            for (int s = 0; s < 5; s++) wgmma_out(oc, ao + s * 16, wo + s * 128, 1);
            wg_commit();
            if (i < 4) {
                wg_wait<1>();
                if (i > 1 && leader) mbar_arrive(B_OE - 8 + i * 8);
            }
        }
        TS(w4 == 0 ? 8 : 63);

        if (min(sel1, sel2) < 16) {
#pragma unroll 1
            for (int j = 0; j < 2; j++) {
                const uint32_t sel = j ? sel2 : sel1;
                if (sel > 16) continue;
                mbar_wait(B_MOD, 0);
#pragma unroll
                for (int t = 0; t < 5; t++) {
                    const uint4 v = lds16(SM_U + j * 320 + cq * 80 + t * 16);
                    const uint32_t u[4] = {v.x, v.y, v.z, v.w};
#pragma unroll
                    for (int k = 0; k < 4; k++) {
                        if (sel == r) nb[8 * t + 2 * k] = hadd2(nb[8 * t + 2 * k], u[k]);
                        if (sel == r + 8) nb[8 * t + 2 * k + 1] = hadd2(nb[8 * t + 2 * k + 1], u[k]);
                    }
                }
            }
            TS(26);
        }
        wg_wait<0>();
        TS(w4 == 0 ? 9 : 63);
        const bool nan = oc[0] != oc[0] || oc[2] != oc[2];
#pragma unroll
        for (int part = 0; part < 3; part++) {
            const int s0 = part ? part * 4 - 4 : 8, ns = part ? 4 : 2;
#pragma unroll
            for (int i = 0; i < 4; i++) {
                if (i >= ns) break;
                const int s = s0 + i;
                const uint32_t y0 = hfma2(n0, nb[s * 4], pack2(oc[s * 8 + 0], oc[s * 8 + 1]));
                const uint32_t y1 = hfma2(n1, nb[s * 4 + 1], pack2(oc[s * 8 + 2], oc[s * 8 + 3]));
                const uint32_t y2 = hfma2(n0, nb[s * 4 + 2], pack2(oc[s * 8 + 4], oc[s * 8 + 5]));
                const uint32_t y3 = hfma2(n1, nb[s * 4 + 3], pack2(oc[s * 8 + 6], oc[s * 8 + 7]));
                asm volatile("stmatrix.sync.aligned.m8n8.x4.shared.b16 [%0], {%1,%2,%3,%4};"
                             ::"r"(((s < 8 ? m128 : m64) ^ ((s & 3) * 32)) + (s & 4) * 512), "r"(y0), "r"(y1), "r"(y2), "r"(y3) : "memory");
            }
            __syncwarp();
            uint4 v[4];
#pragma unroll
            for (int i = 0; i < 4; i++)
                if (i < ns) v[i] = lds16(!part ? l64 + i * 512 : (l128 ^ ((i & 1) * 64)) + i * 512 + s0 * 512);
#pragma unroll
            for (int i = 0; i < 4; i++)
                if (i < ns) *reinterpret_cast<uint4*>(!part ? o64 + i * 8 * 2560 : o128 + i * 4 * 2560 + s0 * 32) = v[i];
            if (part == 0) TS(w4 == 0 ? 1 : 63);
        }
        TS(w4 == 0 ? 10 : 63);
        TSL(w4);
        if (lane == 0) mbar_arrive(B_DONE);
        uint32_t redo;
        asm volatile("{\n.reg .pred p, q;\nsetp.ne.u32 p, %1, 0;\nbar.cta.red.or.pred q, 10, 128, p;\nselp.u32 %0, 1, 0, q;\n}"
                     : "=r"(redo) : "r"((uint32_t)nan) : "memory");
        if (redo) {
            const int cb = hg >> 1;
#pragma unroll 1
            for (int i = 0; i < 8; i++) {
                if (leader) {
                    mbar_expect_tx(B_RE, 25600);
                    tma_3d(SM_W, &P.woa, B_RE, 0, i * 80, (cb * 5 + 1) >> 1);
                    tma_2d(SM_W + 20480, &P.wob, B_RE, cb * 160 + ((cb & 1) ? 0 : 128), i * 80);
                }
#pragma unroll 1
                for (int s = 0; s < 20; s++) {
                    const int w = w4 * 640 + s * 32 + lane;
                    uint32_t v, it = 0;
                    do {
                        v = ld_relaxed4(reinterpret_cast<const uint32_t*>(ow + i * SC_SIZE) + w);
                        if (++it > (1u << 22)) fault();
                    } while ((v >> 16) == 0xFFFFu || (v & 0xFFFFu) == 0xFFFFu);
                    sts4(SM_X + w * 4, v);
                }
                fence_async_smem();
                __syncwarp();
                bar_sync(10, 128);
                mbar_wait(B_RE, i & 1);
                wg_fence();
#pragma unroll
                for (int s = 0; s < 5; s++) wgmma_out(oc, desc_lo(SM_X, 128) + s * 16, desc_lo(SM_W, 10240) + s * 128, s || i);
                wg_commit();
                wg_wait<0>();
                bar_sync(10, 128);
            }
#pragma unroll
            for (int t = 0; t < 40; t++) {
                const int col = (t < 32 ? kba * 64 + (t >> 1) * 8 : kbr * 64 + odd * 32 + ((t - 32) >> 1) * 8) + cq * 2;
                *reinterpret_cast<uint32_t*>(P.op + ((orow + r + (t & 1) * 8) * 2 + par) * 640 + col) =
                    hfma2((t & 1) ? n1 : n0, nb[t], pack2(oc[2 * t], oc[2 * t + 1]));
            }
        }
    } else if (role < 12) {
        asm volatile("setmaxnreg.dec.sync.aligned.u32 96;");
        const int t = tid - 256;
        uint32_t tag = ld_relaxed4(g_cnt);
        float gv = 0.f;
        int grow = hg * 16 + (t >> 3);
        mbar_wait(B_RG, 0);
        TS(warp == 8 ? 48 : 63);
        {
            float r0 = 0.f, r1 = 0.f, g0 = 0.f, g1 = 0.f;
            const uint32_t sw = (t >> 4) * 128 + (((t ^ (t >> 4)) & 7) << 4), hi = (t >> 3) & 1;
            mbar_wait(B_XL0, 0);
            tag = (tag * 8 + 2048) & 0xF800u;
            sts4(SM_KEY + 20 * 4, tag);
#pragma unroll 1
            for (int i = 0; i < 5; i++) {
                const int p = (RG_ORDER >> (i * 4)) & 7, kb = 2 * p + hi;
                mbar_wait(p < 3 ? B_FULL + (p & 1) * 32 : B_RG2, p == 2);
                if (p < 2) mbar_wait(B_FULL + p * 32 + 16, 0);
                const uint32_t xa = sw + (kb < 5 ? SM_X + (kb & 3) * 16384 + hg * 2048 : SM_HALO - 5 * 2048 + kb * 2048);
                const uint4 a = lds16(xa), b = lds16(xa + 1024);
                const uint4 w = lds16(SM_RED + p * 256 + (t & 15) * 16), v = lds16(SM_RED + 1280 + p * 256 + (t & 15) * 16);
                if (__ballot_sync(0xffffffffu, lane == 0 || a.w == b.w) && lane == 0 && p < 3) mbar_arrive(B_XE + p * 8);
                TS5(warp == 8 ? 51 + i : 63);
                const uint32_t as[4] = {a.x, a.y, a.z, a.w}, bs[4] = {b.x, b.y, b.z, b.w};
                const uint32_t ws[4] = {w.x, w.y, w.z, w.w}, vs[4] = {v.x, v.y, v.z, v.w};
#pragma unroll
                for (int e = 0; e < 4; e++) {
                    r0 = fmaf(bf_lo(as[e]), bf_lo(ws[e]), r0);
                    r1 = fmaf(bf_lo(bs[e]), bf_lo(ws[e]), r1);
                    g0 = fmaf(bf_lo(as[e]), bf_lo(vs[e]), g0);
                    g1 = fmaf(bf_lo(bs[e]), bf_lo(vs[e]), g1);
                    r0 = fmaf(bf_hi(as[e]), bf_hi(ws[e]), r0);
                    r1 = fmaf(bf_hi(bs[e]), bf_hi(ws[e]), r1);
                    g0 = fmaf(bf_hi(as[e]), bf_hi(vs[e]), g0);
                    g1 = fmaf(bf_hi(bs[e]), bf_hi(vs[e]), g1);
                }
            }
            const bool up = lane & 4;
            r0 = (hi ? r1 : r0) + __shfl_xor_sync(0xffffffffu, hi ? r0 : r1, 8);
            g0 = (hi ? g1 : g0) + __shfl_xor_sync(0xffffffffu, hi ? g0 : g1, 8);
            float r = (up ? g0 : r0) + __shfl_xor_sync(0xffffffffu, up ? r0 : g0, 4);
            r += __shfl_xor_sync(0xffffffffu, r, 2);
            r = bf_round(r + __shfl_xor_sync(0xffffffffu, r, 1));
            const int row = hg * 16 + (t >> 4) + hi * 8;
            const uint32_t u = f2u(r);
            if (!up) sts4(SM_KEY + (t >> 3) * 4, (((int)u < 0 ? ~u : u | 0x80000000u) & 0xFFFF0000u) | (2047 - (p0 + row) * 2 - par));
            gv = r;
            grow = row;
        }
        TS(warp == 8 ? 63 : 63);
        mbar_wait(B_RG2, 0);
        bar_sync(4, 128);
        if (warp == 8) {
            const uint32_t key = lds4(SM_KEY + (lane & 15) * 4);
            uint32_t k1 = __reduce_max_sync(0xffffffffu, key);
            uint32_t k2 = __reduce_max_sync(0xffffffffu, key == k1 ? 0u : key);
            if (elect_one()) {
                st_relaxed8(g_cand + cid, k1 | tag, k2 | tag);
                red_inc<1>(g_cnt, tag);
            }
            TS(49);
        }
        if ((lane & 7) == 4) st_relaxed4(g_gate + tile * 128 + grow, f2u(bf_round(sigmoidf(gv))) | tag);
        const int cq = lane & 3, w4 = warp & 3;
        const uint32_t la = keep(cq * 256 + (((lane >> 2) ^ cq * 2) << 4));
        const uint32_t sel = keep(0x44444444u ^ (0x54u << (lane >> 2 & 1) * 8 + (lane & 16)));
        if (NFFN) {
            float4 d;
            uint4* dst;
            if (cid < NFFN) {
                float dg[8], du[8];
                mbar_wait(B_GU, 0);
                mbar_wait(B_XS, 0);
                TS(warp == 8 ? 50 : 63);
                wg_fence();
#pragma unroll
                for (int i = 0; i < 10; i++) wgmma_vec(dg, desc_lo(SM_F + i * 2048, 16), desc_lo(SM_XS + i * 32, 16), i);
                wg_commit();
                mbar_wait(B_UP, 0);
                TS(warp == 10 ? 58 : 63);
                wg_fence();
#pragma unroll
                for (int i = 0; i < 10; i++) wgmma_vec(du, desc_lo(SM_UP + i * 2048, 16), desc_lo(SM_XS + i * 32, 16), i);
                wg_commit();
                wg_wait<0>();
                if (lane == 0) mbar_arrive(B_GUD), mbar_arrive(B_DF);
                TS(warp == 8 ? 54 : warp == 10 ? 59 : 63);
                if (cq == 0) {
                    st_relaxed16(sc + SC_GU + w4 * 16 + (lane >> 2), f2u(dg[0]), f2u(dg[4]), f2u(du[0]), f2u(du[4]));
                    st_relaxed16(sc + SC_GU + w4 * 16 + 8 + (lane >> 2), f2u(dg[2]), f2u(dg[6]), f2u(du[2]), f2u(du[6]));
                }
            } else {
                uint4 wv[2][8], wr[4];
                mbar_wait(B_UP, 0);
                TS(warp == 10 ? 58 : 63);
                mbar_wait(B_EMPTY + 3 * 8, 0);
#pragma unroll
                for (int i = 0; i < 8; i++) wv[i >> 2][4 + (i & 3)] = lds16((la ^ (i & 1) * 144) + SM_UP + w4 * 4096 + (i >> 1) * 1024);
                if (landed<4>(wv[0] + 4, lane) & landed<4>(wv[1] + 4, lane)) mbar_arrive(B_GUD);
                TS(warp == 8 ? 54 : 63);
                mbar_wait(B_GU, 0);
#pragma unroll
                for (int i = 0; i < 4; i++) wr[i] = lds16((la ^ (i & 1) * 144) + SM_F + 12288 + w4 * 2048 + (i >> 1) * 1024);
                mbar_wait(B_XS, 0);
                if (w4 == 0) {
                    uint4 pq[4];
                    pace(t_start, HS_T);
                    poll<4>(pq, g_sc + ((cid >> 1) * 4 - 148) * SC_SIZE + SC_GU + (cid & 1) * 32 + lane, SC_SIZE);
                    TS(warp == 8 ? 55 : 63);
                    swiglu(pq, SM_H + (lane & 6) * 8 + (lane >> 3) * 4 + (lane & 1) * 2, 64);
                }
                bar_sync(4, 128);
                TS(warp == 8 ? 57 : 63);
                const uint4 h = lds16(SM_H + (lane & 8) * 8 + cq * 16);
                const uint32_t hv[4] = {h.x, h.y, h.z, h.w}, hr[2] = {(w4 & 1) ? h.z : h.x, (w4 & 1) ? h.w : h.y};
                d = vec_mma<4>(wr, hr, sel);
                dst = g_sc + (cid * 5 - 520 + w4) * SC_SIZE + SC_Y + (lane & 1) * 32 + (lane >> 1);
                float c[2][2][4] = {};
                const uint32_t s2 = sel + ((sel & 0x10101010u) >> 3) * 17;
#pragma unroll
                for (int i = 7; i >= 0; i--) {
                    const uint32_t x0 = prmt(hv[i >> 1], (i & 1) ? s2 : sel), x1 = prmt(hv[i >> 1], ((i & 1) ? s2 : sel) >> 16);
#pragma unroll
                    for (int n = 0; n < 2; n++) {
                        if (i >= 4) wv[n][i - 4] = lds16((la ^ (i & 1) * 144) + SM_F - 6144 + w4 * 4096 + n * 2048 + (i >> 1) * 1024);
                        mma16(c[n][i & 1], wv[n][i].x, wv[n][i].y, wv[n][i].z, wv[n][i].w, x0, x1);
                    }
                }
#pragma unroll
                for (int n = 0; n < 2; n++)
                    st_relaxed16(dst + n * 16, f2u(c[n][0][0] + c[n][1][0]), f2u(c[n][0][1] + c[n][1][1]), f2u(c[n][0][2] + c[n][1][2]),
                                 f2u(c[n][0][3] + c[n][1][3]));
                dst += (4 - w4) * SC_SIZE + w4 * 8;
                TS(warp == 8 ? 30 : 63);
                if (lane == 0 && f2u(d.x) != SENT) mbar_arrive(B_DF);
                if (w4 & 1) {
                    sts16(SM_RED + 512 + (w4 & 2) * 256 + lane * 16, f2u(d.x), f2u(d.y), f2u(d.z), f2u(d.w));
                    bar_arrive(13 + (w4 >> 1), 64);
                } else {
                    bar_sync(13 + (w4 >> 1), 64);
                    const uint4 o = lds16(SM_RED + 512 + (w4 & 2) * 256 + lane * 16);
                    st_relaxed16(dst, f2u(d.x + u2f(o.x)), f2u(d.y + u2f(o.y)), f2u(d.z + u2f(o.z)), f2u(d.w + u2f(o.w)));
                }
            }
        } else {
            if (t < 4) mbar_arrive(B_GUD);
            if (t < 4) mbar_arrive(B_DF);
            mbar_wait(B_XS, 0);
        }
        TS(warp == 8 ? 51 : 63);
        const uint32_t k1 = lds4(SM_KEY + 16 * 4), k2 = lds4(SM_KEY + 17 * 4);
        const uint32_t mine = (tile >> 1) * 256 + HALF * 128 + par;
        const bool own1 = (~k1 & 0x781) == mine, own2 = (~k2 & 0x781) == mine;
        if ((own1 || own2) && NFFN) {
            const int rg = min(t / 40, 2), un = (hg >> 1) * 40 + t % 40;
            mbar_wait(B_RS, 0);
            pace(t_start, Y_T);
            TS(warp == 8 ? 60 : 63);
#pragma unroll 1
            for (int j = !own1; j <= own2; j++) {
                const uint4* p = g_sc + (rg * 5 + 20 + (un >> 5)) * SC_SIZE + SC_Y + j * 32 + (un & 31);
                float y[4];
                bool bad;
                do {
                    uint4 yp[7];
#pragma unroll
                    for (int i = 0; i < 7; i++) yp[i] = i < 6 || rg < 2 ? ld_relaxed16(p + i * 15 * SC_SIZE) : make_uint4(0, 0, 0, 0);
                    y[0] = y[1] = y[2] = y[3] = 0.f;
                    bad = false;
#pragma unroll
                    for (int i = 0; i < 7; i++) {
                        y[0] += u2f(yp[i].x); y[1] += u2f(yp[i].y); y[2] += u2f(yp[i].z); y[3] += u2f(yp[i].w);
                        bad |= yp[i].w == SENT;
                    }
                } while (__any_sync(0xffffffffu, bad));
                TS(warp == 8 ? 53 : 63);
                sts16(SM_SENT + j * 2048 + t * 16, f2u(y[0]), f2u(y[1]), f2u(y[2]), f2u(y[3]));
            }
            bar_sync(4, 128);
            const int j = w4 >> 1;
            if (j ? own2 : own1) {
                const uint32_t key = j ? k2 : k1, u = min(t & 63, 39), ya = SM_SENT + j * 2048 + u * 16, uq = (hg >> 1) * 40 + u;
                const float rs = bf_round(sigmoidf(u2f(((int)key < 0 ? key & 0x7FFFFFFFu : ~key) & 0xFFFF0000u)));
                const uint4 y0 = lds16(ya), y1 = lds16(ya + 640), y2 = lds16(ya + 1280);
                const uint4* q = g_sc + (uq >> 5) * SC_SIZE + SC_Y + j * 32 + (uq & 31);
                const float sx = u2f(y0.x) + u2f(y1.x) + u2f(y2.x), sy = u2f(y0.y) + u2f(y1.y) + u2f(y2.y);
                const float sz = u2f(y0.z) + u2f(y1.z) + u2f(y2.z), sw = u2f(y0.w) + u2f(y1.w) + u2f(y2.w);
                const uint32_t ua = SM_U + j * 320 + (u & 1) * 160 + ((u >> 1) + (hg & 2) * 8) % 20 * 4;
                uint4 z[4];
                pace(t_start, Y2_T);
                do {
#pragma unroll
                    for (int i = 0; i < 4; i++) z[i] = ld_relaxed16(q + i * 5 * SC_SIZE);
                } while (__any_sync(0xffffffffu, max(max(z[0].w, z[1].w), max(z[2].w, z[3].w)) == SENT));
                TS(warp == 8 ? 62 : 63);
                if ((t & 63) < 40) {
                    sts4(ua, pack2(bf_round(sx + (u2f(z[0].x) + u2f(z[1].x)) + (u2f(z[2].x) + u2f(z[3].x))) * rs,
                                   bf_round(sy + (u2f(z[0].y) + u2f(z[1].y)) + (u2f(z[2].y) + u2f(z[3].y))) * rs));
                    sts4(ua + 80, pack2(bf_round(sz + (u2f(z[0].z) + u2f(z[1].z)) + (u2f(z[2].z) + u2f(z[3].z))) * rs,
                                        bf_round(sw + (u2f(z[0].w) + u2f(z[1].w)) + (u2f(z[2].w) + u2f(z[3].w))) * rs));
                }
            }
        }
        __syncwarp();
        if (lane == 0) mbar_arrive(B_MOD);
        TS(warp == 8 ? 52 : 63);
    } else {
        asm volatile("setmaxnreg.dec.sync.aligned.u32 32;");
        if (warp == 15) {
            pace(t_start, EPF_T);
            if (lane < EPF_M) l2_prefetch(P.wp + (EPF_N * 132 + lane * 128 + bid) * 64);
            if (elect_one()) {
#pragma unroll 1
                for (int i = 0; i < (!NFFN ? 0 : cid < NFFN ? 8 : 12); i++) {
                    pace(t_start, GU_T0 + i * (cid < NFFN ? GU_DT : GU_DS) + (cid & 7) * GU_ST);
                    if (cid < NFFN) tma_2d(SM_F + i * 2560, &P.gate, B_GU, (cid >> 2) * 64, (cid & 3) * 160 + i * 20);
                    else tma_2d(SM_F - 4096 + i * 2048, &P.down, B_GU, min(i, 4 + (i >> 1)) * 64, cid * 32 - 2368 + (i > 8 ? (i & 1) * 16 : 0));
                }
            }
            __syncwarp();
            int it = (smem_u32(smem_raw) & 0xFFFFFF) == SB ? 0 : 1 << 20;
            while (!mbar_try(B_DONE, 0) || !mbar_try(B_MOD, 0))
                if (++it > (1 << 20)) fault();
        } else if (warp == 13) {
#pragma unroll 1
            for (int i = 0; i < 10; i++) sts16(SM_SENT + i * 512 + lane * 16, SENT, SENT, SENT, SENT);
            fence_async_smem();
            __syncwarp();
            if (elect_one()) {
                mbar_expect_tx(B_RG, 2560);
                mbar_expect_tx(B_GU, cid < NFFN ? 20480 : 24576);
                asm volatile("mbarrier.expect_tx.relaxed.cta.shared::cta.b64 [%0], 10240;" ::"r"(B_RG2) : "memory");
                pace(t_start, RW1_T);
                bulk_load(SM_RED, P.w_r, 1280, B_RG);
                bulk_load(SM_RED + 1280, P.gate_w, 1280, B_RG);
#pragma unroll 1
                for (int i = 0; i < 5; i++) {
                    pace(t_start, RG1_T0 + i * RG1_DT);
                    tma_3d(SM_HALO + i * 2048, &P.xg, B_RG2, 320 + i * 64, par, p0 + hg * 16);
                }
#pragma unroll
                for (int i = 0; i < 23; i++) mbar_init(B_GUD + i * 8, i == 10 ? 8 : i == 22 || i == 9 || !i ? 4 : i < 16 ? 1 : 2);
                bulk_store(sc + SC_HALO, SM_SENT, 5120);
                asm volatile("cp.async.bulk.commit_group;\ncp.async.bulk.wait_group 0;" ::: "memory");
                mbar_arrive(B_RG2);
                TS(43);
                const unsigned goal = (ld_relaxed4(g_cnt + 32) | (NCTA - 1)) + 1;
#pragma unroll 1
                for (int i = 0; i < RS_N; i++) {
                    pace(t_start, RS_T0 + i * RS_DT);
                    bulk_store(sc + i * (1280 / RS_N), SM_SENT, 20480 / RS_N);
                }
                asm volatile("cp.async.bulk.commit_group;\ncp.async.bulk.wait_group 0;" ::: "memory");
                red_inc(g_cnt + 32, goal);
                mbar_arrive(B_RS);
                TS(44);
                while (ld_relaxed4(g_cnt + 32) - goal > 0x80000000u) {}
                mbar_arrive(B_INIT);
                TS(45);
            }
        } else if (warp == 14) {
            if (elect_one()) {
#pragma unroll 1
                for (int kb = 1; kb < 10; kb++) {
                    const uint32_t fb = B_FULL + (kb & 3) * 16, dst = SM_X + (kb & 3) * 16384;
                    mbar_wait(fb + (B_EMPTY - B_FULL + 8), ~(kb >> 2) & 1);
                    if (kb >= 4) mbar_wait(B_XE + (kb - 4 >> 1) * 8, 0);
                    pace(t_start, max(PACE_A - PACE_B / 2 + 2 * kb * PACE_B, PACE_W0 - X_OFF + (2 * kb + 1) * PACE));
                    tma_3d(dst, &P.x2, fb, kb * 64, par, p0);
                    TS5(41 + kb);
                }
            }
            __syncwarp();
            pace(t_start, CAND_T);
            {
                const uint32_t tag = lds4(SM_KEY + 20 * 4);
                uint4 c[2], v;
                do {
                    c[0] = ld_relaxed16(g_cand + lane * 2);
                    c[1] = ld_relaxed16(g_cand + lane * 2 + 64);
                    v = ld_relaxed16(g_gate + tile * 128 + lane * 4);
                } while (__any_sync(0xffffffffu, ((c[0].x ^ tag) | (c[0].z ^ tag) | (c[1].x ^ tag) | (c[1].z ^ tag) | (v.x ^ tag) |
                                                  (v.y ^ tag) | (v.z ^ tag) | (v.w ^ tag)) & 0xF800u));
                const uint32_t a1 = max(c[0].x, c[0].z), b1 = max(c[1].x, c[1].z), l1 = max(a1, b1);
                const uint32_t l2 = max(max(max(c[0].y, c[0].w), max(c[1].y, c[1].w)),
                                        max(max(min(c[0].x, c[0].z), min(c[1].x, c[1].z)), min(a1, b1)));
                const uint32_t k1 = __reduce_max_sync(0xffffffffu, l1);
                const uint32_t k2 = __reduce_max_sync(0xffffffffu, l1 == k1 ? l2 : l1);
                sts16(SM_GATE + lane * 16, v.x, v.y, v.z, v.w);
                __syncwarp();
                if (elect_one()) {
                    bulk_load(SM_XS, P.xp + (~k1 & 2047) * 640 + (cid & 3) * 160, 320, B_XS);
                    bulk_load(SM_XS + 320, P.xp + (~k2 & 2047) * 640 + (cid & 3) * 160, 320, B_XS);
                    sts16(SM_KEY + 16 * 4, k1, k2, 0, 0);
                    mbar_expect_tx(B_XS, 640);
                    mbar_arrive(B_GT);
                    TS(56);
                }
            }
            bar_sync(12, 64);
            pace(t_start, 0);
            pace(clock(), HALO_D);
            TS(24);
            uint4 hv[5];
            poll<5>(hv, sc + (SC_HALO - (tile < 2 ? 0 : 16 * SC_SIZE) + lane), 32);
#pragma unroll
            for (int s = 0; s < 5; s++) sts16(SM_HALO + s * 512 + lane * 16, hv[s].x, hv[s].y, hv[s].z, hv[s].w);
            bar_arrive(8, 64);
            TS(25);
        } else {
            if (elect_one()) {
#pragma unroll 1
                for (int s = W_S0; s < 20; s++) {
                    const uint32_t fb = B_FULL + (s & 7) * 8, dst = SM_W + (s & 7) * 15360;
                    mbar_wait(fb + (B_EMPTY - B_FULL), ~(s >> 3) & 1);
                    pace(t_start, max(PACE_A + s * PACE_B, PACE_W0 + s * PACE));
                    mbar_expect_tx(fb, (s & 1) ? 15360 : 15360 + 16384);
                    tma_3d(dst, &P.w, fb, wcm, s * 32, 0);
                    tma_3d(dst + 12288, &P.wr, fb, wcr, s * 32, 0);
                    TS2(20 + s);
                    if (s == W_S0) TS(41);
                }
                mbar_wait(B_RG2, 0);
                if (NFFN) {
                    mbar_wait(B_EMPTY + 5 * 8, 1);
                    mbar_expect_tx(B_UP, cid < NFFN ? 20480 : 16384);
                    TS(46);
                    if (cid < NFFN) tma_2d(SM_UP, &P.up, B_UP, (cid >> 2) * 64, (cid & 3) * 160);
                    else
#pragma unroll 1
                        for (int i = 0; i < 8; i++) tma_2d(SM_UP + i * 2048, &P.down, B_UP, i * 64, cid * 32 - 2352);
                }
                const int cb = hg >> 1, ca = (cb * 5 + 1) >> 1, cr = cb * 160 + ((cb & 1) ? 0 : 128);
                pace(t_start, C0_T);
#pragma unroll 1
                for (int j = 0; j < 8; j++) {
                    const int i = j ^ (j == 3 || j == 4 ? 7 : 0);
                    if (j != 3) mbar_wait(j < 3 ? B_EMPTY + ((2 * j + 7) & 7) * 8 : B_GUD + (j - 4) * 8, j == 0);
                    if (j >= 5) pace(clock(), j == 5 ? C5_D : C6_D);
                    const uint32_t dst = wo_buf(i), gb = B_G2 + i * 8;
                    mbar_expect_tx(gb, 25600);
                    tma_3d(dst, &P.woa, gb, 0, src_of(i, hg) * 80, ca);
                    tma_2d(dst + 20480, &P.wob, gb, cr, src_of(i, hg) * 80);
                }
            }
        }
    }
}

typedef CUresult (*EncodeFn)(CUtensorMap*, CUtensorMapDataType, cuuint32_t, void*, const cuuint64_t*, const cuuint64_t*,
                             const cuuint32_t*, const cuuint32_t*, CUtensorMapInterleave, CUtensorMapSwizzle,
                             CUtensorMapL2promotion, CUtensorMapFloatOOBfill);

void encode(EncodeFn fn, CUtensorMap* m, const void* ptr, int rank, const cuuint64_t* dims, const cuuint64_t* strides,
            const cuuint32_t* box, CUtensorMapSwizzle swz) {
    const cuuint32_t es[4] = {1, 1, 1, 1};
    fn(m, CU_TENSOR_MAP_DATA_TYPE_BFLOAT16, rank, const_cast<void*>(ptr), dims, strides, box, es,
       CU_TENSOR_MAP_INTERLEAVE_NONE, swz, CU_TENSOR_MAP_L2_PROMOTION_L2_128B, CU_TENSOR_MAP_FLOAT_OOB_FILL_NONE);
}

}

extern "C" void kernel_launch(void* const* d_in, const int* in_sizes, int n_in, void* d_out, int out_size) {
    (void)in_sizes; (void)n_in; (void)out_size;
    Params P;
    P.xp = (const __nv_bfloat16*)d_in[0];
    P.wp = (const __nv_bfloat16*)d_in[1];
    P.op = (__nv_bfloat16*)d_out;
    P.w_r = (const __nv_bfloat16*)d_in[4];
    P.gate_w = (const __nv_bfloat16*)d_in[8];

    void* fp = nullptr;
    cudaDriverEntryPointQueryResult st;
    cudaGetDriverEntryPoint("cuTensorMapEncodeTiled", &fp, cudaEnableDefault, &st);
    EncodeFn fn = (EncodeFn)fp;
    const cuuint64_t xd[3] = {640, 2, 1024}, xs[2] = {1280, 2560};
    const cuuint32_t bx[3] = {64, 1, 64}, bx2[3] = {64, 1, 128};
    encode(fn, &P.x2, d_in[0], 3, xd, xs, bx2, CU_TENSOR_MAP_SWIZZLE_128B);
    encode(fn, &P.x, d_in[0], 3, xd, xs, bx, CU_TENSOR_MAP_SWIZZLE_128B);
    const cuuint64_t wd[3] = {640, 640, 3}, ws[2] = {3840, 1280};
    const cuuint32_t bw[3] = {64, 32, 3}, bwr[3] = {16, 32, 3};
    encode(fn, &P.w, d_in[1], 3, wd, ws, bw, CU_TENSOR_MAP_SWIZZLE_128B);
    encode(fn, &P.wr, d_in[1], 3, wd, ws, bwr, CU_TENSOR_MAP_SWIZZLE_32B);
    const cuuint64_t ad[3] = {64, 640, 10}, as[2] = {1280, 128}, bd[2] = {640, 640};
    const cuuint32_t ba[3] = {64, 80, 2}, bb[2] = {32, 80};
    encode(fn, &P.woa, d_in[2], 3, ad, as, ba, CU_TENSOR_MAP_SWIZZLE_128B);
    encode(fn, &P.wob, d_in[2], 2, bd, as, bb, CU_TENSOR_MAP_SWIZZLE_128B);
    const cuuint64_t gd[2] = {1728, 640}, gs[1] = {3456}, dd[2] = {640, 1728};
    const cuuint32_t bg[2] = {64, 20}, bu[2] = {64, 160}, bdn[2] = {64, 16}, bxg[3] = {64, 1, 16};
    encode(fn, &P.xg, d_in[0], 3, xd, xs, bxg, CU_TENSOR_MAP_SWIZZLE_128B);
    encode(fn, &P.gate, d_in[5], 2, gd, gs, bg, CU_TENSOR_MAP_SWIZZLE_128B);
    encode(fn, &P.up, d_in[6], 2, gd, gs, bu, CU_TENSOR_MAP_SWIZZLE_128B);
    encode(fn, &P.down, d_in[7], 2, dd, as, bdn, CU_TENSOR_MAP_SWIZZLE_128B);

    cudaFuncSetAttribute(fused_kernel, cudaFuncAttributeMaxDynamicSharedMemorySize, SM_TOTAL);
    fused_kernel<<<NCTA + NEXTRA, 512, SM_TOTAL, cudaStreamPerThread>>>(P);
}
```

```cpp
#include <cuda_runtime.h>
#include <cuda_bf16.h>
#include <cuda.h>
#include <stdint.h>

namespace {

constexpr int NCTA = 128, NEXTRA = 4;
constexpr int NFFN = 108;
constexpr uint32_t SENT = 0xFFFFFFFFu;

constexpr uint32_t SB = 1024;
constexpr uint32_t SM_W = SB;
constexpr uint32_t SM_X = SB + 122880;
constexpr uint32_t SM_F = SB + 192512;
constexpr uint32_t SM_HALO = SB + 212992;
constexpr uint32_t SM_BAR = SB + 223232;
constexpr uint32_t SM_PROF = SB + 223744;
constexpr uint32_t SM_KEY = SB + 224000;
constexpr uint32_t SM_RED = SB + 224128;
constexpr uint32_t SM_XS = SB + 226688;
constexpr uint32_t SM_SENT = SB + 227328;
constexpr uint32_t SM_U = SM_RED + 1920;
constexpr uint32_t SM_H = SM_RED + 1536;
constexpr uint32_t SM_GATE = SM_RED;
constexpr uint32_t SM_TOTAL = 232448;
constexpr uint32_t SM_HALO1 = SM_X + 32768;
constexpr uint32_t SM_UP = SM_W + 61440;
constexpr uint32_t SM_OUT = SM_W + 61440;

constexpr uint32_t B_XL0 = SM_BAR, B_FULL = SM_BAR + 8, B_GT = SM_BAR + 72, B_RG = SM_BAR + 80, B_RG2 = SM_BAR + 88,
                   B_XS = SM_BAR + 96, B_EMPTY = SM_BAR + 128, B_DONE = SM_BAR + 192, B_XE = SM_BAR + 200,
                   B_GUD = SM_BAR + 224, B_OE = SM_BAR + 232, B_OT = SM_BAR + 264, B_MOD = SM_BAR + 296,
                   B_GU = SM_BAR + 104, B_UP = SM_BAR + 112, B_RS = SM_BAR + 312, B_INIT = SM_BAR + 320,
                   B_RE = SM_BAR + 328, B_PUB = SM_BAR + 304, B_G2 = SM_BAR + 336, B_DF = SM_BAR + 400;

struct Params {
    CUtensorMap x, x2, w, wr, woa, wob, xg, gate, up, down;
    __nv_bfloat16* op;
    const __nv_bfloat16 *xp, *wp, *w_r, *gate_w;
};

constexpr int SC_O = 0;
constexpr int SC_HALO = 1280;
constexpr int SC_GU = 1440;
constexpr int SC_Y = 1504;
constexpr int SC_SIZE = 1600;
__device__ __align__(128) uint4 g_sc[NCTA * SC_SIZE];
__device__ __align__(128) uint2 g_cand[NCTA];
__device__ __align__(16) uint32_t g_gate[2048];
__device__ __align__(128) unsigned g_cnt[64];
#define TS(i) do { } while (0)
#define TS2(i) do { } while (0)
#define TSX(i) do { } while (0)

#define TSL(i) do { } while (0)
#define TS5(i) do { } while (0)
__device__ __forceinline__ uint32_t smem_u32(const void* p) { return (uint32_t)__cvta_generic_to_shared(p); }
__device__ __forceinline__ void fault() { asm volatile("st.shared.u32 [%0], %0;" ::"r"(0x100001) : "memory"); }
__device__ __forceinline__ void mbar_init(uint32_t bar, uint32_t cnt) {
    asm volatile("mbarrier.init.shared::cta.b64 [%0], %1;" ::"r"(bar), "r"(cnt) : "memory");
}
__device__ __forceinline__ void mbar_expect_tx(uint32_t bar, uint32_t bytes) {
    asm volatile("mbarrier.arrive.expect_tx.shared::cta.b64 _, [%0], %1;" ::"r"(bar), "r"(bytes) : "memory");
}
__device__ __forceinline__ void mbar_arrive(uint32_t bar) {
    asm volatile("mbarrier.arrive.shared::cta.b64 _, [%0];" ::"r"(bar) : "memory");
}
__device__ __forceinline__ bool mbar_try(uint32_t bar, uint32_t parity) {
    uint32_t ok;
    asm volatile("{\n.reg .pred p;\nmbarrier.try_wait.parity.shared::cta.b64 p, [%1], %2;\nselp.u32 %0, 1, 0, p;\n}"
                 : "=r"(ok) : "r"(bar), "r"(parity) : "memory");
    return ok;
}
__device__ __forceinline__ void mbar_wait(uint32_t bar, uint32_t parity) {
    asm volatile("{\n.reg .pred p;\nAGAIN:\nmbarrier.try_wait.parity.shared::cta.b64 p, [%0], %1;\n@!p bra AGAIN;\n}"
                 ::"r"(bar), "r"(parity) : "memory");
}
__device__ __forceinline__ void tma_2d(uint32_t dst, const CUtensorMap* m, uint32_t bar, int c0, int c1) {
    asm volatile("cp.async.bulk.tensor.2d.shared::cluster.global.mbarrier::complete_tx::bytes [%0], [%1, {%3, %4}], [%2];"
                 ::"r"(dst), "l"(m), "r"(bar), "r"(c0), "r"(c1) : "memory");
}
__device__ __forceinline__ void bulk_load(uint32_t dst, const void* src, uint32_t bytes, uint32_t bar) {
    asm volatile("cp.async.bulk.shared::cluster.global.mbarrier::complete_tx::bytes [%0], [%1], %2, [%3];"
                 ::"r"(dst), "l"(src), "r"(bytes), "r"(bar) : "memory");
}
__device__ __forceinline__ void bulk_store(void* dst, uint32_t src, uint32_t bytes) {
    asm volatile("cp.async.bulk.global.shared::cta.bulk_group [%0], [%1], %2;" ::"l"(dst), "r"(src), "r"(bytes) : "memory");
}
__device__ __forceinline__ void tma_3d(uint32_t dst, const CUtensorMap* m, uint32_t bar, int c0, int c1, int c2) {
    asm volatile("cp.async.bulk.tensor.3d.shared::cluster.global.mbarrier::complete_tx::bytes [%0], [%1, {%3, %4, %5}], [%2];"
                 ::"r"(dst), "l"(m), "r"(bar), "r"(c0), "r"(c1), "r"(c2) : "memory");
}
__device__ __forceinline__ void fence_async_smem() { asm volatile("fence.proxy.async.shared::cta;" ::: "memory"); }
__device__ __forceinline__ void wg_fence() { asm volatile("wgmma.fence.sync.aligned;" ::: "memory"); }
__device__ __forceinline__ void wg_commit() { asm volatile("wgmma.commit_group.sync.aligned;" ::: "memory"); }
template <int N> __device__ __forceinline__ void wg_wait() { asm volatile("wgmma.wait_group.sync.aligned %0;" ::"n"(N) : "memory"); }
__device__ __forceinline__ void bar_sync(int id, int n) { asm volatile("bar.cta.sync %0, %1;" ::"r"(id), "r"(n) : "memory"); }
__device__ __forceinline__ void bar_arrive(int id, int n) { asm volatile("bar.cta.arrive %0, %1;" ::"r"(id), "r"(n) : "memory"); }

__device__ constexpr uint32_t desc_lo(uint32_t addr, uint32_t lbo) { return (addr >> 4) | ((lbo >> 4) << 16); }
__device__ __forceinline__ bool elect_one() {
    uint32_t p;
    asm volatile("{\n.reg .pred p;\nelect.sync _|p, 0xffffffff;\nselp.u32 %0, 1, 0, p;\n}" : "=r"(p));
    return p;
}
__device__ __forceinline__ uint32_t ld_relaxed4(const void* p) {
    uint32_t v;
    asm volatile("ld.relaxed.gpu.global.u32 %0, [%1];" : "=r"(v) : "l"(p) : "memory");
    return v;
}
__device__ __forceinline__ void st_relaxed4(void* p, uint32_t v) {
    asm volatile("st.relaxed.gpu.global.u32 [%0], %1;" ::"l"(p), "r"(v) : "memory");
}
template <int N = 1>
__device__ __forceinline__ void red_inc(unsigned* p, unsigned after) {
    asm volatile("red.relaxed.gpu.global.add.u32 [%0], %2;" ::"l"(p), "r"(after), "n"(N) : "memory");
}
__device__ __forceinline__ uint32_t lds4(uint32_t a) {
    uint32_t v;
    asm volatile("ld.shared.u32 %0, [%1];" : "=r"(v) : "r"(a) : "memory");
    return v;
}
__device__ __forceinline__ float2 lds8f(uint32_t a) {
    float2 v;
    asm volatile("ld.shared.v2.f32 {%0, %1}, [%2];" : "=f"(v.x), "=f"(v.y) : "r"(a) : "memory");
    return v;
}
__device__ __forceinline__ void sts4(uint32_t a, uint32_t v) { asm volatile("st.shared.u32 [%0], %1;" ::"r"(a), "r"(v) : "memory"); }
__device__ __forceinline__ uint32_t hadd2(uint32_t a, uint32_t b) {
    uint32_t d;
    asm("add.rn.bf16x2 %0, %1, %2;" : "=r"(d) : "r"(a), "r"(b));
    return d;
}
__device__ __forceinline__ uint32_t hfma2(uint32_t a, uint32_t b, uint32_t c) {
    uint32_t d;
    asm("fma.rn.bf16x2 %0, %1, %2, %3;" : "=r"(d) : "r"(a), "r"(b), "r"(c));
    return d;
}
__device__ __forceinline__ uint4 ld_relaxed16(const void* p) {
    uint4 v;
    asm volatile("{\n.reg .b128 t;\n.reg .b64 lo, hi;\nld.relaxed.gpu.global.b128 t, [%4];\nmov.b128 {lo, hi}, t;\n"
                 "mov.b64 {%0, %1}, lo;\nmov.b64 {%2, %3}, hi;\n}" : "=r"(v.x), "=r"(v.y), "=r"(v.z), "=r"(v.w) : "l"(p) : "memory");
    return v;
}
__device__ __forceinline__ void st_relaxed16(void* p, uint32_t a, uint32_t b, uint32_t c, uint32_t d) {
    uint64_t lo = (uint64_t)a | ((uint64_t)b << 32), hi = (uint64_t)c | ((uint64_t)d << 32);
    asm volatile("{\n.reg .b128 t;\nmov.b128 t, {%1, %2};\nst.relaxed.gpu.global.b128 [%0], t;\n}" ::"l"(p), "l"(lo), "l"(hi) : "memory");
}
__device__ __forceinline__ void st_relaxed8(void* p, uint32_t a, uint32_t b) {
    asm volatile("{\n.reg .b64 t;\nmov.b64 t, {%1, %2};\nst.relaxed.gpu.global.b64 [%0], t;\n}" ::"l"(p), "r"(a), "r"(b) : "memory");
}
__device__ __forceinline__ uint4 lds16(uint32_t a) {
    uint4 v;
    asm volatile("ld.shared.v4.u32 {%0, %1, %2, %3}, [%4];" : "=r"(v.x), "=r"(v.y), "=r"(v.z), "=r"(v.w) : "r"(a) : "memory");
    return v;
}
__device__ __forceinline__ void sts16(uint32_t a, uint32_t x, uint32_t y, uint32_t z, uint32_t w) {
    asm volatile("st.shared.v4.u32 [%0], {%1, %2, %3, %4};" ::"r"(a), "r"(x), "r"(y), "r"(z), "r"(w) : "memory");
}
__device__ __forceinline__ uint32_t pack2(float lo, float hi) {
    uint32_t r;
    asm("cvt.rn.bf16x2.f32 %0, %1, %2;" : "=r"(r) : "f"(hi), "f"(lo));
    return r;
}
__device__ __forceinline__ uint32_t pack2v(float lo, float hi) {
    uint32_t r;
    asm volatile("cvt.rn.bf16x2.f32 %0, %1, %2;" : "=r"(r) : "f"(hi), "f"(lo));
    return r;
}
__device__ __forceinline__ float bf_lo(uint32_t u) { return __uint_as_float(u << 16); }
__device__ __forceinline__ float bf_hi(uint32_t u) { return __uint_as_float(u & 0xFFFF0000u); }
__device__ __forceinline__ float bf_round(float f) { return __bfloat162float(__float2bfloat16_rn(f)); }
__device__ __forceinline__ uint32_t prmt(uint32_t a, uint32_t sel) {
    uint32_t d;
    asm("prmt.b32 %0, %1, 0, %2;" : "=r"(d) : "r"(a), "r"(sel));
    return d;
}
__device__ __forceinline__ uint32_t movm(uint32_t a) {
    uint32_t d;
    asm volatile("movmatrix.sync.aligned.m8n8.trans.b16 %0, %1;" : "=r"(d) : "r"(a));
    return d;
}
__device__ __forceinline__ void mma16(float (&c)[4], uint32_t a0, uint32_t a1, uint32_t a2, uint32_t a3, uint32_t b0, uint32_t b1) {
    asm volatile("mma.sync.aligned.m16n8k16.row.col.f32.bf16.bf16.f32 {%0,%1,%2,%3}, {%4,%5,%6,%7}, {%8,%9}, {%0,%1,%2,%3};"
                 : "+f"(c[0]), "+f"(c[1]), "+f"(c[2]), "+f"(c[3]) : "r"(a0), "r"(a1), "r"(a2), "r"(a3), "r"(b0), "r"(b1));
}
__device__ __forceinline__ void mma8(float (&c)[4], uint32_t a0, uint32_t a1, uint32_t b0) {
    asm volatile("mma.sync.aligned.m16n8k8.row.col.f32.bf16.bf16.f32 {%0,%1,%2,%3}, {%4,%5}, {%6}, {%0,%1,%2,%3};"
                 : "+f"(c[0]), "+f"(c[1]), "+f"(c[2]), "+f"(c[3]) : "r"(a0), "r"(a1), "r"(b0));
}
__device__ __forceinline__ float ex2(float x) { float y; asm("ex2.approx.ftz.f32 %0, %1;" : "=f"(y) : "f"(x)); return y; }
__device__ __forceinline__ float rcp(float x) { float y; asm("rcp.approx.ftz.f32 %0, %1;" : "=f"(y) : "f"(x)); return y; }
__device__ __forceinline__ float sigmoidf(float z) { return rcp(1.0f + ex2(z * -1.4426950408889634f)); }
__device__ __forceinline__ float u2f(uint32_t u) { return __uint_as_float(u); }
__device__ __forceinline__ uint32_t f2u(float f) { return __float_as_uint(f); }

__device__ __forceinline__ void wgmma_main(float (&d)[96], uint32_t a, uint32_t b, int scale_d) {
    asm volatile("{\n.reg .pred p;\n.reg .b64 da, db;\nsetp.ne.b32 p, %98, 0;\n"
        "mov.b64 da, {%96, 0x40000040};\nmov.b64 db, {%97, 0x40000040};\n"
        "wgmma.mma_async.sync.aligned.m64n192k16.f32.bf16.bf16 "
        "{%0, %1, %2, %3, %4, %5, %6, %7, %8, %9, %10, %11, %12, %13, %14, %15, "
        "%16, %17, %18, %19, %20, %21, %22, %23, %24, %25, %26, %27, %28, %29, %30, %31, "
        "%32, %33, %34, %35, %36, %37, %38, %39, %40, %41, %42, %43, %44, %45, %46, %47, "
        "%48, %49, %50, %51, %52, %53, %54, %55, %56, %57, %58, %59, %60, %61, %62, %63, "
        "%64, %65, %66, %67, %68, %69, %70, %71, %72, %73, %74, %75, %76, %77, %78, %79, "
        "%80, %81, %82, %83, %84, %85, %86, %87, %88, %89, %90, %91, %92, %93, %94, %95}, "
        "da, db, p, 1, 1, 0, 1;\n}\n"
        : "+f"(d[0]), "+f"(d[1]), "+f"(d[2]), "+f"(d[3]), "+f"(d[4]), "+f"(d[5]), "+f"(d[6]), "+f"(d[7]),
          "+f"(d[8]), "+f"(d[9]), "+f"(d[10]), "+f"(d[11]), "+f"(d[12]), "+f"(d[13]), "+f"(d[14]), "+f"(d[15]),
          "+f"(d[16]), "+f"(d[17]), "+f"(d[18]), "+f"(d[19]), "+f"(d[20]), "+f"(d[21]), "+f"(d[22]), "+f"(d[23]),
          "+f"(d[24]), "+f"(d[25]), "+f"(d[26]), "+f"(d[27]), "+f"(d[28]), "+f"(d[29]), "+f"(d[30]), "+f"(d[31]),
          "+f"(d[32]), "+f"(d[33]), "+f"(d[34]), "+f"(d[35]), "+f"(d[36]), "+f"(d[37]), "+f"(d[38]), "+f"(d[39]),
          "+f"(d[40]), "+f"(d[41]), "+f"(d[42]), "+f"(d[43]), "+f"(d[44]), "+f"(d[45]), "+f"(d[46]), "+f"(d[47]),
          "+f"(d[48]), "+f"(d[49]), "+f"(d[50]), "+f"(d[51]), "+f"(d[52]), "+f"(d[53]), "+f"(d[54]), "+f"(d[55]),
          "+f"(d[56]), "+f"(d[57]), "+f"(d[58]), "+f"(d[59]), "+f"(d[60]), "+f"(d[61]), "+f"(d[62]), "+f"(d[63]),
          "+f"(d[64]), "+f"(d[65]), "+f"(d[66]), "+f"(d[67]), "+f"(d[68]), "+f"(d[69]), "+f"(d[70]), "+f"(d[71]),
          "+f"(d[72]), "+f"(d[73]), "+f"(d[74]), "+f"(d[75]), "+f"(d[76]), "+f"(d[77]), "+f"(d[78]), "+f"(d[79]),
          "+f"(d[80]), "+f"(d[81]), "+f"(d[82]), "+f"(d[83]), "+f"(d[84]), "+f"(d[85]), "+f"(d[86]), "+f"(d[87]),
          "+f"(d[88]), "+f"(d[89]), "+f"(d[90]), "+f"(d[91]), "+f"(d[92]), "+f"(d[93]), "+f"(d[94]), "+f"(d[95])
        : "r"(a), "r"(b), "r"(scale_d));
}

__device__ __forceinline__ void wgmma_rem(float (&d)[24], uint32_t a, uint32_t b, int scale_d) {
    asm volatile("{\n.reg .pred p;\n.reg .b64 da, db;\nsetp.ne.b32 p, %26, 0;\n"
        "mov.b64 da, {%24, 0x40000040};\nmov.b64 db, {%25, 0xC0000010};\n"
        "wgmma.mma_async.sync.aligned.m64n48k16.f32.bf16.bf16 "
        "{%0, %1, %2, %3, %4, %5, %6, %7, %8, %9, %10, %11, %12, %13, %14, %15, "
        "%16, %17, %18, %19, %20, %21, %22, %23}, "
        "da, db, p, 1, 1, 0, 1;\n}\n"
        : "+f"(d[0]), "+f"(d[1]), "+f"(d[2]), "+f"(d[3]), "+f"(d[4]), "+f"(d[5]), "+f"(d[6]), "+f"(d[7]),
          "+f"(d[8]), "+f"(d[9]), "+f"(d[10]), "+f"(d[11]), "+f"(d[12]), "+f"(d[13]), "+f"(d[14]), "+f"(d[15]),
          "+f"(d[16]), "+f"(d[17]), "+f"(d[18]), "+f"(d[19]), "+f"(d[20]), "+f"(d[21]), "+f"(d[22]), "+f"(d[23])
        : "r"(a), "r"(b), "r"(scale_d));
}

__device__ __forceinline__ void wgmma_out(float (&d)[80], uint32_t a, uint32_t b, int scale_d) {
    asm volatile("{\n.reg .pred p;\n.reg .b64 da, db;\nsetp.ne.b32 p, %82, 0;\n"
        "mov.b64 da, {%80, 0x50};\nmov.b64 db, {%81, 0x40000040};\n"
        "wgmma.mma_async.sync.aligned.m64n160k16.f32.bf16.bf16 "
        "{%0, %1, %2, %3, %4, %5, %6, %7, %8, %9, %10, %11, %12, %13, %14, %15, "
        "%16, %17, %18, %19, %20, %21, %22, %23, %24, %25, %26, %27, %28, %29, %30, %31, "
        "%32, %33, %34, %35, %36, %37, %38, %39, %40, %41, %42, %43, %44, %45, %46, %47, "
        "%48, %49, %50, %51, %52, %53, %54, %55, %56, %57, %58, %59, %60, %61, %62, %63, "
        "%64, %65, %66, %67, %68, %69, %70, %71, %72, %73, %74, %75, %76, %77, %78, %79}, "
        "da, db, p, 1, 1, 0, 1;\n}\n"
        : "+f"(d[0]), "+f"(d[1]), "+f"(d[2]), "+f"(d[3]), "+f"(d[4]), "+f"(d[5]), "+f"(d[6]), "+f"(d[7]),
          "+f"(d[8]), "+f"(d[9]), "+f"(d[10]), "+f"(d[11]), "+f"(d[12]), "+f"(d[13]), "+f"(d[14]), "+f"(d[15]),
          "+f"(d[16]), "+f"(d[17]), "+f"(d[18]), "+f"(d[19]), "+f"(d[20]), "+f"(d[21]), "+f"(d[22]), "+f"(d[23]),
          "+f"(d[24]), "+f"(d[25]), "+f"(d[26]), "+f"(d[27]), "+f"(d[28]), "+f"(d[29]), "+f"(d[30]), "+f"(d[31]),
          "+f"(d[32]), "+f"(d[33]), "+f"(d[34]), "+f"(d[35]), "+f"(d[36]), "+f"(d[37]), "+f"(d[38]), "+f"(d[39]),
          "+f"(d[40]), "+f"(d[41]), "+f"(d[42]), "+f"(d[43]), "+f"(d[44]), "+f"(d[45]), "+f"(d[46]), "+f"(d[47]),
          "+f"(d[48]), "+f"(d[49]), "+f"(d[50]), "+f"(d[51]), "+f"(d[52]), "+f"(d[53]), "+f"(d[54]), "+f"(d[55]),
          "+f"(d[56]), "+f"(d[57]), "+f"(d[58]), "+f"(d[59]), "+f"(d[60]), "+f"(d[61]), "+f"(d[62]), "+f"(d[63]),
          "+f"(d[64]), "+f"(d[65]), "+f"(d[66]), "+f"(d[67]), "+f"(d[68]), "+f"(d[69]), "+f"(d[70]), "+f"(d[71]),
          "+f"(d[72]), "+f"(d[73]), "+f"(d[74]), "+f"(d[75]), "+f"(d[76]), "+f"(d[77]), "+f"(d[78]), "+f"(d[79])
        : "r"(a), "r"(b), "r"(scale_d));
}

__device__ __forceinline__ void wgmma_own(float (&d)[80], uint32_t a0, uint32_t a1, uint32_t a2, uint32_t a3, uint32_t b, int scale_d) {
    asm volatile("{\n.reg .pred p;\n.reg .b64 db;\nsetp.ne.b32 p, %85, 0;\nmov.b64 db, {%84, 0x40000040};\n"
        "wgmma.mma_async.sync.aligned.m64n160k16.f32.bf16.bf16 "
        "{%0, %1, %2, %3, %4, %5, %6, %7, %8, %9, %10, %11, %12, %13, %14, %15, "
        "%16, %17, %18, %19, %20, %21, %22, %23, %24, %25, %26, %27, %28, %29, %30, %31, "
        "%32, %33, %34, %35, %36, %37, %38, %39, %40, %41, %42, %43, %44, %45, %46, %47, "
        "%48, %49, %50, %51, %52, %53, %54, %55, %56, %57, %58, %59, %60, %61, %62, %63, "
        "%64, %65, %66, %67, %68, %69, %70, %71, %72, %73, %74, %75, %76, %77, %78, %79}, "
        "{%80, %81, %82, %83}, db, p, 1, 1, 1;\n}\n"
        : "+f"(d[0]), "+f"(d[1]), "+f"(d[2]), "+f"(d[3]), "+f"(d[4]), "+f"(d[5]), "+f"(d[6]), "+f"(d[7]),
          "+f"(d[8]), "+f"(d[9]), "+f"(d[10]), "+f"(d[11]), "+f"(d[12]), "+f"(d[13]), "+f"(d[14]), "+f"(d[15]),
          "+f"(d[16]), "+f"(d[17]), "+f"(d[18]), "+f"(d[19]), "+f"(d[20]), "+f"(d[21]), "+f"(d[22]), "+f"(d[23]),
          "+f"(d[24]), "+f"(d[25]), "+f"(d[26]), "+f"(d[27]), "+f"(d[28]), "+f"(d[29]), "+f"(d[30]), "+f"(d[31]),
          "+f"(d[32]), "+f"(d[33]), "+f"(d[34]), "+f"(d[35]), "+f"(d[36]), "+f"(d[37]), "+f"(d[38]), "+f"(d[39]),
          "+f"(d[40]), "+f"(d[41]), "+f"(d[42]), "+f"(d[43]), "+f"(d[44]), "+f"(d[45]), "+f"(d[46]), "+f"(d[47]),
          "+f"(d[48]), "+f"(d[49]), "+f"(d[50]), "+f"(d[51]), "+f"(d[52]), "+f"(d[53]), "+f"(d[54]), "+f"(d[55]),
          "+f"(d[56]), "+f"(d[57]), "+f"(d[58]), "+f"(d[59]), "+f"(d[60]), "+f"(d[61]), "+f"(d[62]), "+f"(d[63]),
          "+f"(d[64]), "+f"(d[65]), "+f"(d[66]), "+f"(d[67]), "+f"(d[68]), "+f"(d[69]), "+f"(d[70]), "+f"(d[71]),
          "+f"(d[72]), "+f"(d[73]), "+f"(d[74]), "+f"(d[75]), "+f"(d[76]), "+f"(d[77]), "+f"(d[78]), "+f"(d[79])
        : "r"(a0), "r"(a1), "r"(a2), "r"(a3), "r"(b), "r"(scale_d));
}

__device__ __forceinline__ void wgmma_vec(float (&d)[8], uint32_t a, uint32_t b, int scale_d) {
    asm volatile("{\n.reg .pred p;\n.reg .b64 da, db;\nsetp.ne.b32 p, %10, 0;\n"
        "mov.b64 da, {%8, 0x40000040};\nmov.b64 db, {%9, 0x14};\n"
        "wgmma.mma_async.sync.aligned.m64n16k16.f32.bf16.bf16 {%0, %1, %2, %3, %4, %5, %6, %7}, da, db, p, 1, 1, 1, 0;\n}\n"
        : "+f"(d[0]), "+f"(d[1]), "+f"(d[2]), "+f"(d[3]), "+f"(d[4]), "+f"(d[5]), "+f"(d[6]), "+f"(d[7])
        : "r"(a), "r"(b), "r"(scale_d));
}

#define TSA(i) do { } while (0)
#define MAP_TILE(b) ((((b) >> 1) & 14) | ((b) & 1))
#define MAP_HG(b) (((b) >> 4 & 14) | ((b) >> 1 & 1))
#define HALF (int)(bid >> 1 & 1)
#define GM 0x78A0
#define SKEW 4
#define W_S0 2
#define EPF_N 15
#define EPF_M 15
#define RG_ORDER 0x24130
#define RS_N 10
#define DN_R 5
#define P2W 4
#define EPF_T 900
#define PACE_A 250
#define PACE_B 450
#define PACE_W0 (-700)
#define PACE 500
#define X_OFF 350
#define RW1_T 0
#define RG1_T0 1700
#define RG1_DT 200
#define DN_T0 500
#define DN_DT 68
#define DN_T1 100000
#define DN_D1 45
#define GU_T0 3600
#define GU_DT 750
#define GU_DS (GU_DT * 7 / 11)
#define GU_ST 90
#define CAND_T 9000
#define RS_T0 8750
#define RS_DT 120
#define C0_T 11100
#define C5_D 0
#define C6_D 100
#define HALO_D 650
#define HALO_T 0
#define H_T 13200
#define H_C 1000
#define HS_T 13200
#define L0_T 14450
#define L1_T 14050
#define LS_T 14450
#define F0_T 14650
#define F1_T 14300
#define F0_D 200
#define F1_D 0
#define O_DT 300
#define Y_T 15500
#define Y2_T 17000

__device__ __forceinline__ uint32_t keep(uint32_t v) { return __shfl_xor_sync(0xffffffffu, v, 0); }
__device__ __forceinline__ uint32_t ukeep(uint32_t v) { return __shfl_sync(0xffffffffu, v, 0); }
__device__ __forceinline__ void ldsm2(uint32_t* d, uint32_t a) {
    asm volatile("ldmatrix.sync.aligned.m8n8.x4.shared.b16 {%0,%1,%2,%3}, [%8];\nldmatrix.sync.aligned.m8n8.x4.shared.b16 {%4,%5,%6,%7}, [%9];"
                 : "=r"(d[0]), "=r"(d[1]), "=r"(d[2]), "=r"(d[3]), "=r"(d[4]), "=r"(d[5]), "=r"(d[6]), "=r"(d[7])
                 : "r"(a), "r"(a ^ 32) : "memory");
}
__device__ __forceinline__ void ldsm_t(uint32_t (&d)[4], uint32_t a) {
    asm volatile("ldmatrix.sync.aligned.m8n8.x4.trans.shared.b16 {%0,%1,%2,%3}, [%4];"
                 : "=r"(d[0]), "=r"(d[1]), "=r"(d[2]), "=r"(d[3]) : "r"(a) : "memory");
}
template <bool SWP, int SEG, int E>
__device__ __forceinline__ void pack_blocks(uint32_t (&d)[10], const float (&am)[96], const float (&ar)[24]) {
#pragma unroll
    for (int t = 0; t < 10; t++) {
        const float* p = (SWP ? t < 2 : t >= 8) ? ar + (SEG * 2 + (t & 1)) * 4 + E : am + (SEG * 8 + t - (SWP ? 2 : 0)) * 4 + E;
        d[t] = pack2v(p[0], p[1]);
    }
}
__device__ __forceinline__ int src_of(int i, int hg) {
    return i == 0 ? hg : (0x75316240u >> (i - (i <= (hg >> 2 | hg & 2))) * 4 & 7) ^ (hg & 1);
}

__device__ __forceinline__ uint32_t o_buf(int i) { return __byte_perm(0xD199ADA3u, 0xC7BDu, i - 2 | 0x7770) << 10; }
__device__ constexpr uint32_t wo_buf(int i) { return SM_W + ((0x10342103u >> i * 4) & 7) * 30720; }

template <int N>
__device__ __forceinline__ void poll(uint4 (&a)[N], const uint4* p, int stride) {
    bool bad;
    do {
        bad = false;
#pragma unroll
        for (int s = 0; s < N; s++) a[s] = ld_relaxed16(p + s * stride);
#pragma unroll
        for (int s = 0; s < N; s++) bad |= a[s].w == SENT;
    } while (__any_sync(0xffffffffu, bad));
}
__device__ __forceinline__ void pace(unsigned t0, int t) {
    asm volatile("{\n.reg .pred p;\n.reg .s32 d;\nAGAIN:\nmov.u32 d, %%clock;\nsub.s32 d, d, %0;\nsetp.lt.s32 p, d, 0;\n"
                 "@p nanosleep.u32 20;\n@p bra AGAIN;\n}" ::"r"(t0 + t) : "memory");
}
__device__ __forceinline__ void l2_prefetch(const void* p) { asm volatile("prefetch.global.L2 [%0];" ::"l"(p) : "memory"); }

template <int N>
__device__ __forceinline__ bool landed(const uint4* w, int lane) {
    uint32_t a = 0;
#pragma unroll
    for (int i = 0; i < N; i++) a ^= w[i].w;
    return __ballot_sync(0xffffffffu, lane == 0 || a == 0) && lane == 0;
}
__device__ __forceinline__ void swiglu(const uint4 (&a)[4], uint32_t dst, uint32_t stride) {
    const float g0 = bf_round((u2f(a[0].x) + u2f(a[1].x)) + (u2f(a[2].x) + u2f(a[3].x)));
    const float g1 = bf_round((u2f(a[0].y) + u2f(a[1].y)) + (u2f(a[2].y) + u2f(a[3].y)));
    const float u0 = bf_round((u2f(a[0].z) + u2f(a[1].z)) + (u2f(a[2].z) + u2f(a[3].z)));
    const float u1 = bf_round((u2f(a[0].w) + u2f(a[1].w)) + (u2f(a[2].w) + u2f(a[3].w)));
    const uint32_t h = pack2(bf_round(g0 * sigmoidf(g0)) * u0, bf_round(g1 * sigmoidf(g1)) * u1);
    asm volatile("st.shared.u16 [%0], %2;\nst.shared.u16 [%1], %3;" ::"r"(dst), "r"(dst + stride), "h"((uint16_t)h), "h"((uint16_t)(h >> 16)) : "memory");
}
template <int N>
__device__ __forceinline__ float4 vec_mma(const uint4 (&w)[N], const uint32_t* x, uint32_t sel) {
    float c[4][4] = {};
    const uint32_t s[4] = {sel, sel >> 16, sel + ((sel & 0x10101010u) >> 3) * 17, (sel + ((sel & 0x10101010u) >> 3) * 17) >> 16};
#pragma unroll
    for (int i = 0; i < N; i++)
        mma16(c[i & 3], w[i].x, w[i].y, w[i].z, w[i].w, prmt(x[i >> 1], s[(i & 1) * 2]), prmt(x[i >> 1], s[(i & 1) * 2 + 1]));
    return make_float4((c[0][0] + c[1][0]) + (c[2][0] + c[3][0]), (c[0][1] + c[1][1]) + (c[2][1] + c[3][1]),
                       (c[0][2] + c[1][2]) + (c[2][2] + c[3][2]), (c[0][3] + c[1][3]) + (c[2][3] + c[3][3]));
}

__global__ void __launch_bounds__(512, 1) fused_kernel(const __grid_constant__ Params P) {
    extern __shared__ __align__(1024) uint8_t smem_raw[];
    const unsigned t_start = clock();
    const int tid = threadIdx.x, lane = tid & 31;
    unsigned sm, bid;
    asm("mov.u32 %0, %%smid;" : "=r"(sm));
    const CUtensorMap* mx = &P.x;
    asm volatile("" : "+l"(mx));
    if ((unsigned)(tid - 480) < EPF_N) l2_prefetch(P.wp + (tid * 132 + sm) * 64 - 480 * 132 * 64);
    const int warp = __shfl_sync(0xffffffffu, threadIdx.x >> 5, 0);
    asm("{\n.reg .pred p;\n.reg .b32 t, u;\nshr.u32 t, %1, 1;\nmad.lo.s32 u, t, 14, -928;\nmad.lo.s32 t, t, 37, -925;\nmax.s32 t, t, 0;\n"
        "shr.u32 t, t, 7;\nand.b32 t, t, 14;\nsetp.ge.u32 p, %1, 124;\nselp.b32 t, u, t, p;\nadd.s32 %0, %1, t;\n}" : "=r"(bid) : "r"(sm));
    bid ^= GM >> (bid & 14) & 6;
    const int hg = MAP_HG(bid), par = bid & 1, p0 = (MAP_TILE(bid) >> 1) * 128;
    const bool swp = (hg & 3) == 3;
    const int wcm = hg * 80 + (swp ? 16 : 0), wcr = hg * 80 + (swp ? 0 : 64);
    if (warp == 0) {
        if (elect_one()) {
#pragma unroll
            for (int i = 0; i < 4; i++) mbar_init(SM_BAR + i * 8, 1);
            asm volatile("fence.mbarrier_init.release.cluster;" ::: "memory");
            if (bid < NCTA) {
                mbar_expect_tx(B_FULL, 15360 + 8192);
                tma_3d(SM_X + 8192, mx, B_FULL, 0, par, p0 + 64);
                tma_3d(SM_W, mx + 2, B_FULL, wcm, 0, 0);
                tma_3d(SM_W + 12288, mx + 3, B_FULL, wcr, 0, 0);
                TS(40);
                mbar_expect_tx(B_XL0, 8192);
                tma_3d(SM_X, mx, B_XL0, 0, par, p0);
                mbar_expect_tx(B_FULL + 8, 15360);
                tma_3d(SM_W + 15360, mx + 2, B_FULL + 8, wcm, 32, 0);
                tma_3d(SM_W + 15360 + 12288, mx + 3, B_FULL + 8, wcr, 32, 0);
            }
        }
    }
    if ((unsigned)(warp - 1) < 6 && elect_one()) {
#pragma unroll
        for (int i = 0; i < 4; i++) mbar_init(SM_BAR + warp * 32 + i * 8, warp < 4 ? 1 : warp < 6 ? 2 : 4);
        asm volatile("fence.mbarrier_init.release.cluster;" ::: "memory");
    }
    asm volatile("" : "+r"(bid));
    const int role = bid >= NCTA ? -1 : warp, e = sm & 3;
    const int tile = MAP_TILE(bid), cid = tile * 8 + hg;
    uint4* const sc = g_sc + cid * SC_SIZE;
    __syncthreads();

    if (role < 0) {
        const int half = warp >> 3;
        if (!NFFN) {
            if (tid == 0) red_inc<NCTA / NEXTRA>(g_cnt, 0);
            return;
        }
        uint32_t wf[DN_R][5][4], la[5];
        auto rows = [&](uint32_t l) {
#pragma unroll
            for (int i = 0; i < 5; i++) {
                const uint32_t c = (warp & 7) * 10 + 2 * i + (l >> 3 & 1);
                la[i] = SB + half * 20480 + (c >> 3) * 2048 + (l & 7) * 128 + (l >> 4) * 1024 + (((c ^ l) & 7) << 4);
            }
        };
        rows(lane);
        auto fetch = [&](int j, int n, uint32_t bar) {
#pragma unroll 1
            for (int h = 0; h < n; h++) {
                pace(t_start, min(DN_T0 + (j * 20 + h * 10 + warp) * DN_DT, DN_T1 + (j * 20 + h * 10 + warp) * DN_D1));
                tma_2d(SB + (j % 5) * 40960 + h * 20480 + warp * 2048, &P.down, bar, warp * 64, e * 272 + (j + h * 9) * 16);
            }
        };
        if (warp < 10 && elect_one()) {
            if (warp <= DN_R) mbar_expect_tx(B_FULL + warp * 8, warp < DN_R ? 40960 : (17 - 2 * DN_R) * 20480);
#pragma unroll 1
            for (int j = 0; j < 5; j++) fetch(j, 2, B_FULL + j * 8);
        }
        const uint32_t tag = (ukeep(ld_relaxed4(g_cnt)) * 8 + 2048) & 0xF800u;
#pragma unroll
        for (int j = 0; j < DN_R; j++) {
            uint32_t any = 0;
            mbar_wait(B_FULL + j * 8, 0);
#pragma unroll
            for (int i = 0; i < 5; i++) {
                ldsm_t(wf[j][i], la[i] + j * 40960);
                any ^= wf[j][i][3];
            }
            if (j < 4) {
                if (__syncthreads_count(any == 0) == 1000) fault();
                if (warp < 10 && elect_one()) fetch(j + 5, j < 3 ? 2 : 1, B_FULL + DN_R * 8);
                if (j == 0 && tid == 0) red_inc<NCTA / NEXTRA>(g_cnt, tag);
            }
            TSX(warp == 0 && j == 0 ? 0 : warp == 0 && j == 3 ? 1 : 63);
        }
        if (warp < 9) {
            pace(t_start, H_T - H_C);
            uint4 a[4];
            do {
                a[0] = ld_relaxed16(g_cand + lane * 2);
                a[1] = ld_relaxed16(g_cand + lane * 2 + 64);
            } while (__any_sync(0xffffffffu, ((a[0].x ^ tag) | (a[0].z ^ tag) | (a[1].x ^ tag) | (a[1].z ^ tag)) & 0xF800u));
            const int u = min(tid, 271), f = e * 272 + u;
            pace(t_start, H_T);
            TSX(warp == 0 ? 3 : 63);
            poll<4>(a, g_sc + (f >> 6) * 4 * SC_SIZE + SC_GU + (f & 63), SC_SIZE);
            TSX(warp == 0 ? 4 : warp == 8 ? 5 : 63);
            swiglu(a, SM_RED + (u >> 4) * 64 + (u & 6) * 4 + (u & 8) / 2 + (u & 1) * 2, 32);
        }
        rows(keep(lane));
        mbar_wait(B_FULL + DN_R * 8, 0);
        TSX(warp == 15 ? 2 : 63);
        __syncthreads();
        float c[5][4] = {};
#pragma unroll
        for (int j = 0; j < 9; j++) {
            if (j == 8 && half) break;
            const float2 b = lds8f(SM_RED + half * 576 + j * 64 + (lane & 7) * 8);
            if (j == 1) TSX(warp == 0 ? 6 : 63);
#pragma unroll
            for (int i = 0; i < 5; i++) {
                if (j >= DN_R) ldsm_t(wf[j % DN_R][i], la[i] + (j % 5) * 40960);
                mma16(c[i], wf[j % DN_R][i][0], wf[j % DN_R][i][1], wf[j % DN_R][i][2], wf[j % DN_R][i][3], f2u(b.x), f2u(b.y));
            }
        }
        const uint32_t ra = SB + 7 * 20480 + half * 5248 + (lane & 1) * 2624 + (warp & 7) * 320 + (lane & 2) * 16 + (lane >> 2) * 4;
#pragma unroll
        for (int i = 0; i < 5; i++) sts4(ra + i * 64, f2u((lane & 2) ? ((lane & 1) ? c[i][3] : c[i][2]) : ((lane & 1) ? c[i][1] : c[i][0])));
        TSX(warp == 0 ? 7 : 63);
        __syncthreads();
        if (warp < 10) {
            const uint32_t ya = SB + 7 * 20480 + (warp & 1) * 2624 + (warp >> 1) * 512 + lane * 16;
            const uint4 y0 = lds16(ya), y1 = lds16(ya + 5248);
            st_relaxed16(g_sc + (e * 5 + (warp >> 1)) * SC_SIZE + SC_Y + (tid & 63), f2u(u2f(y0.x) + u2f(y1.x)), f2u(u2f(y0.y) + u2f(y1.y)),
                         f2u(u2f(y0.z) + u2f(y1.z)), f2u(u2f(y0.w) + u2f(y1.w)));
        }
    } else if (role < 8) {
        asm volatile("setmaxnreg.inc.sync.aligned.u32 192;");
        const int wg = warp >> 2;
        const bool leader = (tid & 127) == 0;
        float am[96], ar[24];
        if (wg == 0) mbar_wait(B_XL0, 0);
        bool rel = false;
        uint32_t nb[40];
        const int odd = (hg >> 1) & 1, kba = ukeep(wg != HALF ? 99 : ((hg >> 1) * 5 + 1) >> 1), kbr = ukeep(kba + 2 - odd * 3);
        const int kbs = wg ? -1 : (20 - SKEW) / 2;
        const uint32_t xrow = keep(SM_X + (warp * 16 + (lane & 15)) * 128 + (((lane >> 4) ^ (lane & 7)) << 4));
#pragma unroll 1
        for (int kb = 0; kb < 10; kb++) {
            const uint32_t fb = B_FULL + (kb & 3) * 16, wo = (kb & 3) * 1920, ph = (kb >> 2) & 1;
            const uint32_t xo = desc_lo(SM_X, 16) + wg * 512 + (kb & 3) * 1024;
#pragma unroll
            for (int h = 0; h < 2; h++) {
                mbar_wait(fb + h * 8, ph);
                if (kb == 0 && h == 0) TS(warp == 0 ? 0 : warp == 4 ? 16 : 63);
                TS2(warp == P2W ? kb * 2 + h : 63);
                {
                    const uint32_t xa = (xrow ^ h * 64) + (kb & 3) * 16384;
                    if (kb == kba) ldsm2(nb + h * 8, xa);
                    if (kb == kba + 1) ldsm2(nb + 16 + h * 8, xa);
                    if (h == 0 && kb == kbr) ldsm2(nb + 32, xa ^ (odd * 64));
                }
                wg_wait<1>();
                if (rel && (h == 0 || kb != kbs)) mbar_arrive(B_EMPTY + ((kb * 16 - 16) & 48) + h * 8);
                if (h == 0 && kb == kbs) {
                    wg_wait<0>();
                    if (rel) mbar_arrive(B_EMPTY + ((19 - SKEW) & 7) * 8);
                    bar_sync(5, 256);
                }
                wg_fence();
                wgmma_main(am, xo + h * 4, desc_lo(SM_W + h * 15360, 4096) + wo, h || kb);
                wgmma_rem(ar, xo + h * 4, desc_lo(SM_W + h * 15360 + 12288, 1024) + wo, h || kb);
                wgmma_main(am, xo + h * 4 + 2, desc_lo(SM_W + h * 15360 + 2048, 4096) + wo, 1);
                wgmma_rem(ar, xo + h * 4 + 2, desc_lo(SM_W + h * 15360 + 12288 + 512, 1024) + wo, 1);
                wg_commit();
            }
            rel = leader;
        }
        if (wg == 1) bar_arrive(5, 256);
        mbar_wait(B_XE + 16, 0);
        mbar_wait(B_RG2, 0);
        mbar_wait(B_EMPTY + 5 * 8, 1);
        wg_wait<0>();
        if (leader) mbar_arrive(B_EMPTY + 3 * 8);
        TS(warp == 0 ? 2 : warp == 4 ? 18 : 63);
        TS2(warp == 0 ? 41 : warp == 4 ? 40 : 63);

        uint32_t kl[10], kh[10], vl[10], vh[10], ql[10], qh[10], kp[10], vp[10];
        if (swp) {
            pack_blocks<true, 1, 2>(kh, am, ar);
            pack_blocks<true, 2, 2>(vh, am, ar);
        } else {
            pack_blocks<false, 1, 2>(kh, am, ar);
            pack_blocks<false, 2, 2>(vh, am, ar);
        }
        const int w4 = warp & 3;
        const uint32_t pbuf = (wg ? SM_HALO1 : SM_HALO) + w4 * 2560 + lane * 16;
        const uint32_t hbuf = warp == 3 ? SM_HALO1 + lane * 16 : pbuf + 2560;
        {
            const uint32_t ex[20] = {kh[0], kh[1], kh[3], kh[4], kh[5], kh[6], kh[8], kh[9], kh[2], kh[7],
                                     vh[0], vh[1], vh[2], vh[3], vh[4], vh[5], vh[6], vh[7], vh[8], vh[9]};
            if (warp == 7) {
                uint4* const hp = sc + SC_HALO + lane;
#pragma unroll
                for (int s = 0; s < 5; s++) st_relaxed16(hp + s * 32, ex[4 * s], ex[4 * s + 1], ex[4 * s + 2], ex[4 * s + 3]);
                bar_arrive(12, 64);
            } else {
#pragma unroll
                for (int s = 0; s < 5; s++) sts16(hbuf + s * 512, ex[4 * s], ex[4 * s + 1], ex[4 * s + 2], ex[4 * s + 3]);
            }
        }
        TS(warp == 7 ? 22 : warp == 3 ? 23 : 63);
        if (warp == 3) bar_arrive(11, 64);
        if (swp) {
            pack_blocks<true, 2, 0>(vl, am, ar);
            pack_blocks<true, 0, 0>(ql, am, ar);
            pack_blocks<true, 0, 2>(qh, am, ar);
            pack_blocks<true, 1, 0>(kl, am, ar);
        } else {
            pack_blocks<false, 2, 0>(vl, am, ar);
            pack_blocks<false, 0, 0>(ql, am, ar);
            pack_blocks<false, 0, 2>(qh, am, ar);
            pack_blocks<false, 1, 0>(kl, am, ar);
        }
#pragma unroll
        for (int t = 0; t < 10; t++) { vl[t] = movm(vl[t]); vh[t] = movm(vh[t]); }
        mbar_wait(B_RS, 0);
        mbar_wait(B_GT, 0);
        const float g0 = bf_hi(lds4(SM_GATE + warp * 64 + (lane & 28))), g1 = bf_hi(lds4(SM_GATE + 32 + warp * 64 + (lane & 28)));

        const int r = lane >> 2, cq = lane & 3;
        const bool no_prev = warp == 0 && tile < 2, low = cq < 2;
        const bool le0 = 2 * cq <= r, le1 = 2 * cq + 1 <= r;
        const uint32_t mle = (le0 ? 0xFFFFu : 0u) | (le1 ? 0xFFFF0000u : 0u);
        const float scl = 0.22360679774997896f * 1.4426950408889634f;
        uint32_t pl[4], ph[4];
        {
            float sl[4][4], sh[4][4], sp[4][4];
            auto exchange = [&]() {
            TSA(warp == 1 ? 26 : 63);
            bar_sync(6 + wg, 128);
            if (w4 == 0) bar_sync(8 + wg * 3, 64);
            {
                const uint4 a = lds16(pbuf), b = lds16(pbuf + 512), c = lds16(pbuf + 1024), d = lds16(pbuf + 1536), e = lds16(pbuf + 2048);
                kp[0] = a.x; kp[1] = a.y; kp[3] = a.z; kp[4] = a.w; kp[5] = b.x; kp[6] = b.y; kp[8] = b.z; kp[9] = b.w;
                kp[2] = c.x; kp[7] = c.y; vp[0] = c.z; vp[1] = c.w; vp[2] = d.x; vp[3] = d.y; vp[4] = d.z; vp[5] = d.w;
                vp[6] = e.x; vp[7] = e.y; vp[8] = e.z; vp[9] = e.w;
            }
            TSA(warp == 0 ? 3 : warp == 4 ? 19 : warp == 5 ? 27 : 63);
            };
            exchange();
#pragma unroll
            for (int h = 0; h < 4; h++) {
                const int ta = (h >> 1) * 5 + (h & 1) * 3, tc = (h >> 1) * 5 + 2;
                const uint32_t ml = low != (h & 1) ? ql[tc] : 0u, mh = low != (h & 1) ? qh[tc] : 0u;
#pragma unroll
                for (int e = 0; e < 4; e++) sl[h][e] = sh[h][e] = sp[h][e] = 0.f;
                mma16(sl[h], ql[ta], qh[ta], ql[ta + 1], qh[ta + 1], kl[ta], kl[ta + 1]);
                mma16(sh[h], ql[ta], qh[ta], ql[ta + 1], qh[ta + 1], kh[ta], kh[ta + 1]);
                mma8(sl[h], ml, mh, kl[tc]);
                mma8(sh[h], ml, mh, kh[tc]);
            }
#pragma unroll
            for (int h = 0; h < 4; h++) {
                const int ta = (h >> 1) * 5 + (h & 1) * 3, tc = (h >> 1) * 5 + 2;
                mma16(sp[h], ql[ta], qh[ta], ql[ta + 1], qh[ta + 1], kp[ta], kp[ta + 1]);
                mma8(sp[h], low != (h & 1) ? ql[tc] : 0u, low != (h & 1) ? qh[tc] : 0u, kp[tc]);
            }
#pragma unroll
            for (int t = 0; t < 10; t++) vp[t] = movm(vp[t]);
#pragma unroll
            for (int h = 0; h < 4; h++) {
                if (no_prev) sp[h][0] = sp[h][1] = -1e9f / 0.22360679774997896f;
                const float a0 = le0 ? sl[h][0] : sp[h][0], a1 = le1 ? sl[h][1] : sp[h][1];
                const float b0 = le0 ? sh[h][2] : sl[h][2], b1 = le1 ? sh[h][3] : sl[h][3];
                float ma = fmaxf(a0, a1), mb = fmaxf(b0, b1);
                ma = fmaxf(ma, __shfl_xor_sync(0xffffffffu, ma, 1));
                mb = fmaxf(mb, __shfl_xor_sync(0xffffffffu, mb, 1));
                ma = fmaxf(ma, __shfl_xor_sync(0xffffffffu, ma, 2)) * -scl;
                mb = fmaxf(mb, __shfl_xor_sync(0xffffffffu, mb, 2)) * -scl;
                pl[h] = pack2(ex2(fmaf(a0, scl, ma)), ex2(fmaf(a1, scl, ma)));
                ph[h] = pack2(ex2(fmaf(b0, scl, mb)), ex2(fmaf(b1, scl, mb)));
            }
        }
        TSA(warp == 0 ? 4 : warp == 4 ? 20 : warp == 5 ? 28 : 63);
        uint32_t ol[10], oh[10];
        {
            uint32_t* const po = reinterpret_cast<uint32_t*>(sc + SC_O + warp * 160) + lane;
            const uint32_t ONES = 0x3F803F80u;
            float o[12][4];
#pragma unroll
            for (int hp = 0; hp < 2; hp++) {
#pragma unroll
                for (int h = hp * 2; h < hp * 2 + 2; h++) {
                    const int ta = (h >> 1) * 5 + (h & 1) * 3, tc = (h >> 1) * 5 + 2;
                    const bool mine = (lane < 16) != (h & 1);
                    const uint32_t a0 = pl[h] & mle, a1 = ph[h] & ~mle, a3 = ph[h] & mle, ap = pl[h] & ~mle;
#pragma unroll
                    for (int i = 0; i < 3; i++) o[h * 3 + i][0] = o[h * 3 + i][1] = o[h * 3 + i][2] = o[h * 3 + i][3] = 0.f;
                    mma16(o[h * 3 + 2], a0, a1, 0u, a3, mine ? vl[tc] : ONES, mine ? vh[tc] : ONES);
                    mma16(o[h * 3], a0, a1, 0u, a3, vl[ta], vh[ta]);
                    mma16(o[h * 3 + 1], a0, a1, 0u, a3, vl[ta + 1], vh[ta + 1]);
                    mma8(o[h * 3 + 2], ap, 0u, mine ? vp[tc] : ONES);
                    mma8(o[h * 3], ap, 0u, vp[ta]);
                    mma8(o[h * 3 + 1], ap, 0u, vp[ta + 1]);
                }
                if (hp && wg != HALF) bar_arrive(2, 256);
                const float (&oa)[4] = o[hp * 6 + 2], (&ob)[4] = o[hp * 6 + 5];
                const float hl = rcp(low ? ob[0] : oa[0]) * g0, hh = rcp(low ? ob[2] : oa[2]) * g1;
                const float gl = __shfl_xor_sync(0xffffffffu, hl, 2), gh = __shfl_xor_sync(0xffffffffu, hh, 2);
                const float ial = low ? gl : hl, iah = low ? gh : hh, ibl = low ? hl : gl, ibh = low ? hh : gh;
#pragma unroll
                for (int i = 0; i < 2; i++) {
                    ol[hp * 5 + i] = pack2(o[hp * 6 + i][0] * ial, o[hp * 6 + i][1] * ial);
                    oh[hp * 5 + i] = pack2(o[hp * 6 + i][2] * iah, o[hp * 6 + i][3] * iah);
                    ol[hp * 5 + 3 + i] = pack2(o[hp * 6 + 3 + i][0] * ibl, o[hp * 6 + 3 + i][1] * ibl);
                    oh[hp * 5 + 3 + i] = pack2(o[hp * 6 + 3 + i][2] * ibh, o[hp * 6 + 3 + i][3] * ibh);
                }
                ol[hp * 5 + 2] = pack2((low ? oa[0] : ob[0]) * gl, (low ? oa[1] : ob[1]) * gl);
                oh[hp * 5 + 2] = pack2((low ? oa[2] : ob[2]) * gh, (low ? oa[3] : ob[3]) * gh);
#pragma unroll
                for (int t = hp * 5; t < hp * 5 + 5; t++) {
                    st_relaxed4(po + t * 32, ol[t]);
                    st_relaxed4(po + 320 + t * 32, oh[t]);
                }
            }
        }
        TS(warp == 0 ? 5 : warp == 4 ? 21 : warp == 5 ? 29 : warp == 1 ? 31 : 63);
        if (lane == 0) mbar_arrive(B_PUB);
        const uint4* ow = sc + (SC_O + HALF * 640 - hg * SC_SIZE);
        mbar_wait(B_INIT, 0);
        if (wg != HALF) {
            mbar_wait(B_PUB, 0);
            const unsigned t0 = t_start + max((unsigned)clock() - t_start + (wg ? F0_D : F1_D), wg ? F0_T : F1_T);
            uint32_t ph = 0;
#pragma unroll 1
            for (int i = w4 + 2; i < 8; i += 4) {
                const uint4* src = ow + src_of(i, hg) * SC_SIZE;
                const uint32_t buf = o_buf(i), chk = buf + lane * 132;
                pace(t0, (i - 2) * O_DT);
                if (i > 5) mbar_wait(B_DF, 0);
                if (i == 2) TS(wg ? 3 : 4);
                uint32_t c;
                do {
                    if (elect_one()) {
                        mbar_expect_tx(B_OT + w4 * 8, 10240);
                        bulk_load(buf, src, 10240, B_OT + w4 * 8);
                    }
                    mbar_wait(B_OT + w4 * 8, ph);
                    if (i == 2 && !ph) TS(wg ? 19 : 20);
                    ph ^= 1;
                    c = max(max(lds4(chk), lds4(chk + 4096)), lds4(chk + 6144));
                } while (__any_sync(0xffffffffu, c == SENT));
                if (lane == 0) mbar_arrive(B_G2 + i * 8);
                TS(i == 2 ? 33 : 32 + i);
            }
            return;
        }

        float oc[80];
        uint32_t af[20];
        auto fetch = [&]() {
            const uint32_t* p = reinterpret_cast<const uint32_t*>(ow + src_of(1, hg) * SC_SIZE + w4 * 160) + lane;
#pragma unroll
            for (int t = 0; t < 20; t++) af[t] = ld_relaxed4(p + t * 32);
        };
        mbar_wait(B_XS, 0);
        const int orow = p0 + wg * 64 + w4 * 16;
        const uint32_t tk1 = ~lds4(SM_KEY + 16 * 4) & 2047, tk2 = ~lds4(SM_KEY + 17 * 4) & 2047;
        const uint32_t sel1 = (tk1 & 1) == par ? (tk1 >> 1) - orow : 99, sel2 = (tk2 & 1) == par ? (tk2 >> 1) - orow : 99;
        const uint32_t n0 = pack2(1.f - g0, 1.f - g0), n1 = pack2(1.f - g1, 1.f - g1);
        const uint32_t stg = SM_OUT + w4 * 5120;
        const uint32_t m128 = keep(stg + (lane & 15) * 128 + (((lane >> 4) ^ (lane & 7)) << 4));
        const uint32_t m64 = keep(stg + 4096 + (lane & 15) * 64 + (((lane >> 4) ^ ((lane >> 1) & 3)) << 4));
        const uint32_t l128 = keep(stg + (lane >> 3) * 128 + (((lane & 7) ^ (lane >> 3)) << 4));
        const uint32_t l64 = keep(stg + 4096 + r * 64 + ((cq ^ (lane >> 3)) << 4));
        char* const o128 = reinterpret_cast<char*>(P.op) + keep(((orow + (lane >> 3)) * 2 + par) * 1280 + kba * 128 + (lane & 7) * 16);
        char* const o64 = reinterpret_cast<char*>(P.op) + keep(((orow + r) * 2 + par) * 1280 + kbr * 128 + odd * 64 + cq * 16);
        mbar_wait(B_G2, 0);
        mbar_wait(B_G2 + 8, 0);
        const bool ff = cid < NFFN;
        if (ff) {
            pace(t_start, wg ? L1_T : L0_T);
            fetch();
        }
        bar_sync(2, 256);
        TS(w4 == 0 ? 6 : 63);
        wg_fence();
#pragma unroll
        for (int s = 0; s < 5; s++)
            wgmma_own(oc, ol[2 * s], oh[2 * s], ol[2 * s + 1], oh[2 * s + 1], desc_lo(wo_buf(0), 10240) + s * 128, s);
        wg_commit();
        if (!ff) {
            pace(t_start, LS_T);
            fetch();
        }
        TS(w4 == 0 ? 28 : 63);
        mbar_wait(B_DF, 0);
        for (;;) {
            uint32_t m = 0;
#pragma unroll
            for (int t = 0; t < 20; t++) m = max(m, af[t]);
            if (!__any_sync(0xffffffffu, m == SENT)) break;
            fetch();
        }
        TS(w4 == 0 ? 7 : 63);
        wg_fence();
#pragma unroll
        for (int s = 0; s < 5; s++)
            wgmma_own(oc, af[2 * s], af[10 + 2 * s], af[2 * s + 1], af[11 + 2 * s], desc_lo(wo_buf(1), 10240) + s * 128, 1);
        wg_commit();
        wg_wait<1>();
        if (leader) mbar_arrive(B_OE);
#pragma unroll 1
        for (int i = 2; i < 8; i++) {
            const uint32_t ao = desc_lo(0, 128) + (o_buf(i) >> 4), wo = desc_lo(0, 10240) + (wo_buf(i) >> 4);
            mbar_wait(B_G2 + i * 8, 0);
            TS(w4 == 0 ? (i < 2 ? 6 + i : i < 7 ? 9 + i : 17) : 63);
            wg_fence();
#pragma unroll
            for (int s = 0; s < 5; s++) wgmma_out(oc, ao + s * 16, wo + s * 128, 1);
            wg_commit();
            if (i < 4) {
                wg_wait<1>();
                if (i > 1 && leader) mbar_arrive(B_OE - 8 + i * 8);
            }
        }
        TS(w4 == 0 ? 8 : 63);

        if (min(sel1, sel2) < 16) {
#pragma unroll 1
            for (int j = 0; j < 2; j++) {
                const uint32_t sel = j ? sel2 : sel1;
                if (sel > 16) continue;
                mbar_wait(B_MOD, 0);
#pragma unroll
                for (int t = 0; t < 5; t++) {
                    const uint4 v = lds16(SM_U + j * 320 + cq * 80 + t * 16);
                    const uint32_t u[4] = {v.x, v.y, v.z, v.w};
#pragma unroll
                    for (int k = 0; k < 4; k++) {
                        if (sel == r) nb[8 * t + 2 * k] = hadd2(nb[8 * t + 2 * k], u[k]);
                        if (sel == r + 8) nb[8 * t + 2 * k + 1] = hadd2(nb[8 * t + 2 * k + 1], u[k]);
                    }
                }
            }
            TS(26);
        }
        wg_wait<0>();
        TS(w4 == 0 ? 9 : 63);
        const bool nan = oc[0] != oc[0] || oc[2] != oc[2];
#pragma unroll
        for (int part = 0; part < 3; part++) {
            const int s0 = part ? part * 4 - 4 : 8, ns = part ? 4 : 2;
#pragma unroll
            for (int i = 0; i < 4; i++) {
                if (i >= ns) break;
                const int s = s0 + i;
                const uint32_t y0 = hfma2(n0, nb[s * 4], pack2(oc[s * 8 + 0], oc[s * 8 + 1]));
                const uint32_t y1 = hfma2(n1, nb[s * 4 + 1], pack2(oc[s * 8 + 2], oc[s * 8 + 3]));
                const uint32_t y2 = hfma2(n0, nb[s * 4 + 2], pack2(oc[s * 8 + 4], oc[s * 8 + 5]));
                const uint32_t y3 = hfma2(n1, nb[s * 4 + 3], pack2(oc[s * 8 + 6], oc[s * 8 + 7]));
                asm volatile("stmatrix.sync.aligned.m8n8.x4.shared.b16 [%0], {%1,%2,%3,%4};"
                             ::"r"(((s < 8 ? m128 : m64) ^ ((s & 3) * 32)) + (s & 4) * 512), "r"(y0), "r"(y1), "r"(y2), "r"(y3) : "memory");
            }
            __syncwarp();
            uint4 v[4];
#pragma unroll
            for (int i = 0; i < 4; i++)
                if (i < ns) v[i] = lds16(!part ? l64 + i * 512 : (l128 ^ ((i & 1) * 64)) + i * 512 + s0 * 512);
#pragma unroll
            for (int i = 0; i < 4; i++)
                if (i < ns) *reinterpret_cast<uint4*>(!part ? o64 + i * 8 * 2560 : o128 + i * 4 * 2560 + s0 * 32) = v[i];
            if (part == 0) TS(w4 == 0 ? 1 : 63);
        }
        TS(w4 == 0 ? 10 : 63);
        TSL(w4);
        if (lane == 0) mbar_arrive(B_DONE);
        uint32_t redo;
        asm volatile("{\n.reg .pred p, q;\nsetp.ne.u32 p, %1, 0;\nbar.cta.red.or.pred q, 10, 128, p;\nselp.u32 %0, 1, 0, q;\n}"
                     : "=r"(redo) : "r"((uint32_t)nan) : "memory");
        if (redo) {
            const int cb = hg >> 1;
#pragma unroll 1
            for (int i = 0; i < 8; i++) {
                if (leader) {
                    mbar_expect_tx(B_RE, 25600);
                    tma_3d(SM_W, &P.woa, B_RE, 0, i * 80, (cb * 5 + 1) >> 1);
                    tma_2d(SM_W + 20480, &P.wob, B_RE, cb * 160 + ((cb & 1) ? 0 : 128), i * 80);
                }
#pragma unroll 1
                for (int s = 0; s < 20; s++) {
                    const int w = w4 * 640 + s * 32 + lane;
                    uint32_t v, it = 0;
                    do {
                        v = ld_relaxed4(reinterpret_cast<const uint32_t*>(ow + i * SC_SIZE) + w);
                        if (++it > (1u << 22)) fault();
                    } while ((v >> 16) == 0xFFFFu || (v & 0xFFFFu) == 0xFFFFu);
                    sts4(SM_X + w * 4, v);
                }
                fence_async_smem();
                __syncwarp();
                bar_sync(10, 128);
                mbar_wait(B_RE, i & 1);
                wg_fence();
#pragma unroll
                for (int s = 0; s < 5; s++) wgmma_out(oc, desc_lo(SM_X, 128) + s * 16, desc_lo(SM_W, 10240) + s * 128, s || i);
                wg_commit();
                wg_wait<0>();
                bar_sync(10, 128);
            }
#pragma unroll
            for (int t = 0; t < 40; t++) {
                const int col = (t < 32 ? kba * 64 + (t >> 1) * 8 : kbr * 64 + odd * 32 + ((t - 32) >> 1) * 8) + cq * 2;
                *reinterpret_cast<uint32_t*>(P.op + ((orow + r + (t & 1) * 8) * 2 + par) * 640 + col) =
                    hfma2((t & 1) ? n1 : n0, nb[t], pack2(oc[2 * t], oc[2 * t + 1]));
            }
        }
    } else if (role < 12) {
        asm volatile("setmaxnreg.dec.sync.aligned.u32 96;");
        const int t = tid - 256;
        uint32_t tag = ld_relaxed4(g_cnt);
        float gv = 0.f;
        int grow = hg * 16 + (t >> 3);
        mbar_wait(B_RG, 0);
        TS(warp == 8 ? 48 : 63);
        {
            float r0 = 0.f, r1 = 0.f, g0 = 0.f, g1 = 0.f;
            const uint32_t sw = (t >> 4) * 128 + (((t ^ (t >> 4)) & 7) << 4), hi = (t >> 3) & 1;
            mbar_wait(B_XL0, 0);
            tag = (tag * 8 + 2048) & 0xF800u;
            sts4(SM_KEY + 20 * 4, tag);
#pragma unroll 1
            for (int i = 0; i < 5; i++) {
                const int p = (RG_ORDER >> (i * 4)) & 7, kb = 2 * p + hi;
                mbar_wait(p < 3 ? B_FULL + (p & 1) * 32 : B_RG2, p == 2);
                if (p < 2) mbar_wait(B_FULL + p * 32 + 16, 0);
                const uint32_t xa = sw + (kb < 5 ? SM_X + (kb & 3) * 16384 + hg * 2048 : SM_HALO - 5 * 2048 + kb * 2048);
                const uint4 a = lds16(xa), b = lds16(xa + 1024);
                const uint4 w = lds16(SM_RED + p * 256 + (t & 15) * 16), v = lds16(SM_RED + 1280 + p * 256 + (t & 15) * 16);
                if (__ballot_sync(0xffffffffu, lane == 0 || a.w == b.w) && lane == 0 && p < 3) mbar_arrive(B_XE + p * 8);
                TS5(warp == 8 ? 51 + i : 63);
                const uint32_t as[4] = {a.x, a.y, a.z, a.w}, bs[4] = {b.x, b.y, b.z, b.w};
                const uint32_t ws[4] = {w.x, w.y, w.z, w.w}, vs[4] = {v.x, v.y, v.z, v.w};
#pragma unroll
                for (int e = 0; e < 4; e++) {
                    r0 = fmaf(bf_lo(as[e]), bf_lo(ws[e]), r0);
                    r1 = fmaf(bf_lo(bs[e]), bf_lo(ws[e]), r1);
                    g0 = fmaf(bf_lo(as[e]), bf_lo(vs[e]), g0);
                    g1 = fmaf(bf_lo(bs[e]), bf_lo(vs[e]), g1);
                    r0 = fmaf(bf_hi(as[e]), bf_hi(ws[e]), r0);
                    r1 = fmaf(bf_hi(bs[e]), bf_hi(ws[e]), r1);
                    g0 = fmaf(bf_hi(as[e]), bf_hi(vs[e]), g0);
                    g1 = fmaf(bf_hi(bs[e]), bf_hi(vs[e]), g1);
                }
            }
            const bool up = lane & 4;
            r0 = (hi ? r1 : r0) + __shfl_xor_sync(0xffffffffu, hi ? r0 : r1, 8);
            g0 = (hi ? g1 : g0) + __shfl_xor_sync(0xffffffffu, hi ? g0 : g1, 8);
            float r = (up ? g0 : r0) + __shfl_xor_sync(0xffffffffu, up ? r0 : g0, 4);
            r += __shfl_xor_sync(0xffffffffu, r, 2);
            r = bf_round(r + __shfl_xor_sync(0xffffffffu, r, 1));
            const int row = hg * 16 + (t >> 4) + hi * 8;
            const uint32_t u = f2u(r);
            if (!up) sts4(SM_KEY + (t >> 3) * 4, (((int)u < 0 ? ~u : u | 0x80000000u) & 0xFFFF0000u) | (2047 - (p0 + row) * 2 - par));
            gv = r;
            grow = row;
        }
        TS(warp == 8 ? 63 : 63);
        mbar_wait(B_RG2, 0);
        bar_sync(4, 128);
        if (warp == 8) {
            const uint32_t key = lds4(SM_KEY + (lane & 15) * 4);
            uint32_t k1 = __reduce_max_sync(0xffffffffu, key);
            uint32_t k2 = __reduce_max_sync(0xffffffffu, key == k1 ? 0u : key);
            if (elect_one()) {
                st_relaxed8(g_cand + cid, k1 | tag, k2 | tag);
                red_inc<1>(g_cnt, tag);
            }
            TS(49);
        }
        if ((lane & 7) == 4) st_relaxed4(g_gate + tile * 128 + grow, f2u(bf_round(sigmoidf(gv))) | tag);
        const int cq = lane & 3, w4 = warp & 3;
        const uint32_t la = keep(cq * 256 + (((lane >> 2) ^ cq * 2) << 4));
        const uint32_t sel = keep(0x44444444u ^ (0x54u << (lane >> 2 & 1) * 8 + (lane & 16)));
        if (NFFN) {
            float4 d;
            uint4* dst;
            if (cid < NFFN) {
                float dg[8], du[8];
                mbar_wait(B_GU, 0);
                mbar_wait(B_XS, 0);
                TS(warp == 8 ? 50 : 63);
                wg_fence();
#pragma unroll
                for (int i = 0; i < 10; i++) wgmma_vec(dg, desc_lo(SM_F + i * 2048, 16), desc_lo(SM_XS + i * 32, 16), i);
                wg_commit();
                mbar_wait(B_UP, 0);
                TS(warp == 10 ? 58 : 63);
                wg_fence();
#pragma unroll
                for (int i = 0; i < 10; i++) wgmma_vec(du, desc_lo(SM_UP + i * 2048, 16), desc_lo(SM_XS + i * 32, 16), i);
                wg_commit();
                wg_wait<0>();
                if (lane == 0) mbar_arrive(B_GUD), mbar_arrive(B_DF);
                TS(warp == 8 ? 54 : warp == 10 ? 59 : 63);
                if (cq == 0) {
                    st_relaxed16(sc + SC_GU + w4 * 16 + (lane >> 2), f2u(dg[0]), f2u(dg[4]), f2u(du[0]), f2u(du[4]));
                    st_relaxed16(sc + SC_GU + w4 * 16 + 8 + (lane >> 2), f2u(dg[2]), f2u(dg[6]), f2u(du[2]), f2u(du[6]));
                }
            } else {
                uint4 wv[2][8], wr[4];
                mbar_wait(B_UP, 0);
                TS(warp == 10 ? 58 : 63);
                mbar_wait(B_EMPTY + 3 * 8, 0);
#pragma unroll
                for (int i = 0; i < 8; i++) wv[i >> 2][4 + (i & 3)] = lds16((la ^ (i & 1) * 144) + SM_UP + w4 * 4096 + (i >> 1) * 1024);
                if (landed<4>(wv[0] + 4, lane) & landed<4>(wv[1] + 4, lane)) mbar_arrive(B_GUD);
                TS(warp == 8 ? 54 : 63);
                mbar_wait(B_GU, 0);
#pragma unroll
                for (int i = 0; i < 4; i++) wr[i] = lds16((la ^ (i & 1) * 144) + SM_F + 12288 + w4 * 2048 + (i >> 1) * 1024);
                mbar_wait(B_XS, 0);
                if (w4 == 0) {
                    uint4 pq[4];
                    pace(t_start, HS_T);
                    poll<4>(pq, g_sc + ((cid >> 1) * 4 - 148) * SC_SIZE + SC_GU + (cid & 1) * 32 + lane, SC_SIZE);
                    TS(warp == 8 ? 55 : 63);
                    swiglu(pq, SM_H + (lane & 6) * 8 + (lane >> 3) * 4 + (lane & 1) * 2, 64);
                }
                bar_sync(4, 128);
                TS(warp == 8 ? 57 : 63);
                const uint4 h = lds16(SM_H + (lane & 8) * 8 + cq * 16);
                const uint32_t hv[4] = {h.x, h.y, h.z, h.w}, hr[2] = {(w4 & 1) ? h.z : h.x, (w4 & 1) ? h.w : h.y};
                d = vec_mma<4>(wr, hr, sel);
                dst = g_sc + (cid * 5 - 520 + w4) * SC_SIZE + SC_Y + (lane & 1) * 32 + (lane >> 1);
                float c[2][2][4] = {};
                const uint32_t s2 = sel + ((sel & 0x10101010u) >> 3) * 17;
#pragma unroll
                for (int i = 7; i >= 0; i--) {
                    const uint32_t x0 = prmt(hv[i >> 1], (i & 1) ? s2 : sel), x1 = prmt(hv[i >> 1], ((i & 1) ? s2 : sel) >> 16);
#pragma unroll
                    for (int n = 0; n < 2; n++) {
                        if (i >= 4) wv[n][i - 4] = lds16((la ^ (i & 1) * 144) + SM_F - 6144 + w4 * 4096 + n * 2048 + (i >> 1) * 1024);
                        mma16(c[n][i & 1], wv[n][i].x, wv[n][i].y, wv[n][i].z, wv[n][i].w, x0, x1);
                    }
                }
#pragma unroll
                for (int n = 0; n < 2; n++)
                    st_relaxed16(dst + n * 16, f2u(c[n][0][0] + c[n][1][0]), f2u(c[n][0][1] + c[n][1][1]), f2u(c[n][0][2] + c[n][1][2]),
                                 f2u(c[n][0][3] + c[n][1][3]));
                dst += (4 - w4) * SC_SIZE + w4 * 8;
                TS(warp == 8 ? 30 : 63);
                if (lane == 0 && f2u(d.x) != SENT) mbar_arrive(B_DF);
                if (w4 & 1) {
                    sts16(SM_RED + 512 + (w4 & 2) * 256 + lane * 16, f2u(d.x), f2u(d.y), f2u(d.z), f2u(d.w));
                    bar_arrive(13 + (w4 >> 1), 64);
                } else {
                    bar_sync(13 + (w4 >> 1), 64);
                    const uint4 o = lds16(SM_RED + 512 + (w4 & 2) * 256 + lane * 16);
                    st_relaxed16(dst, f2u(d.x + u2f(o.x)), f2u(d.y + u2f(o.y)), f2u(d.z + u2f(o.z)), f2u(d.w + u2f(o.w)));
                }
            }
        } else {
            if (t < 4) mbar_arrive(B_GUD);
            if (t < 4) mbar_arrive(B_DF);
            mbar_wait(B_XS, 0);
        }
        TS(warp == 8 ? 51 : 63);
        const uint32_t k1 = lds4(SM_KEY + 16 * 4), k2 = lds4(SM_KEY + 17 * 4);
        const uint32_t mine = (tile >> 1) * 256 + HALF * 128 + par;
        const bool own1 = (~k1 & 0x781) == mine, own2 = (~k2 & 0x781) == mine;
        if ((own1 || own2) && NFFN) {
            const int rg = min(t / 40, 2), un = (hg >> 1) * 40 + t % 40;
            mbar_wait(B_RS, 0);
            pace(t_start, Y_T);
            TS(warp == 8 ? 60 : 63);
#pragma unroll 1
            for (int j = !own1; j <= own2; j++) {
                const uint4* p = g_sc + (rg * 5 + 20 + (un >> 5)) * SC_SIZE + SC_Y + j * 32 + (un & 31);
                float y[4];
                bool bad;
                do {
                    uint4 yp[7];
#pragma unroll
                    for (int i = 0; i < 7; i++) yp[i] = i < 6 || rg < 2 ? ld_relaxed16(p + i * 15 * SC_SIZE) : make_uint4(0, 0, 0, 0);
                    y[0] = y[1] = y[2] = y[3] = 0.f;
                    bad = false;
#pragma unroll
                    for (int i = 0; i < 7; i++) {
                        y[0] += u2f(yp[i].x); y[1] += u2f(yp[i].y); y[2] += u2f(yp[i].z); y[3] += u2f(yp[i].w);
                        bad |= yp[i].w == SENT;
                    }
                } while (__any_sync(0xffffffffu, bad));
                TS(warp == 8 ? 53 : 63);
                sts16(SM_SENT + j * 2048 + t * 16, f2u(y[0]), f2u(y[1]), f2u(y[2]), f2u(y[3]));
            }
            bar_sync(4, 128);
            const int j = w4 >> 1;
            if (j ? own2 : own1) {
                const uint32_t key = j ? k2 : k1, u = min(t & 63, 39), ya = SM_SENT + j * 2048 + u * 16, uq = (hg >> 1) * 40 + u;
                const float rs = bf_round(sigmoidf(u2f(((int)key < 0 ? key & 0x7FFFFFFFu : ~key) & 0xFFFF0000u)));
                const uint4 y0 = lds16(ya), y1 = lds16(ya + 640), y2 = lds16(ya + 1280);
                const uint4* q = g_sc + (uq >> 5) * SC_SIZE + SC_Y + j * 32 + (uq & 31);
                const float sx = u2f(y0.x) + u2f(y1.x) + u2f(y2.x), sy = u2f(y0.y) + u2f(y1.y) + u2f(y2.y);
                const float sz = u2f(y0.z) + u2f(y1.z) + u2f(y2.z), sw = u2f(y0.w) + u2f(y1.w) + u2f(y2.w);
                const uint32_t ua = SM_U + j * 320 + (u & 1) * 160 + ((u >> 1) + (hg & 2) * 8) % 20 * 4;
                uint4 z[4];
                pace(t_start, Y2_T);
                do {
#pragma unroll
                    for (int i = 0; i < 4; i++) z[i] = ld_relaxed16(q + i * 5 * SC_SIZE);
                } while (__any_sync(0xffffffffu, max(max(z[0].w, z[1].w), max(z[2].w, z[3].w)) == SENT));
                TS(warp == 8 ? 62 : 63);
                if ((t & 63) < 40) {
                    sts4(ua, pack2(bf_round(sx + (u2f(z[0].x) + u2f(z[1].x)) + (u2f(z[2].x) + u2f(z[3].x))) * rs,
                                   bf_round(sy + (u2f(z[0].y) + u2f(z[1].y)) + (u2f(z[2].y) + u2f(z[3].y))) * rs));
                    sts4(ua + 80, pack2(bf_round(sz + (u2f(z[0].z) + u2f(z[1].z)) + (u2f(z[2].z) + u2f(z[3].z))) * rs,
                                        bf_round(sw + (u2f(z[0].w) + u2f(z[1].w)) + (u2f(z[2].w) + u2f(z[3].w))) * rs));
                }
            }
        }
        __syncwarp();
        if (lane == 0) mbar_arrive(B_MOD);
        TS(warp == 8 ? 52 : 63);
    } else {
        asm volatile("setmaxnreg.dec.sync.aligned.u32 32;");
        if (warp == 15) {
            pace(t_start, EPF_T);
            if (lane < EPF_M) l2_prefetch(P.wp + (EPF_N * 132 + lane * 128 + bid) * 64);
            if (elect_one()) {
#pragma unroll 1
                for (int i = 0; i < (!NFFN ? 0 : cid < NFFN ? 8 : 12); i++) {
                    pace(t_start, GU_T0 + i * (cid < NFFN ? GU_DT : GU_DS) + (cid & 7) * GU_ST);
                    if (cid < NFFN) tma_2d(SM_F + i * 2560, &P.gate, B_GU, (cid >> 2) * 64, (cid & 3) * 160 + i * 20);
                    else tma_2d(SM_F - 4096 + i * 2048, &P.down, B_GU, min(i, 4 + (i >> 1)) * 64, cid * 32 - 2368 + (i > 8 ? (i & 1) * 16 : 0));
                }
            }
            __syncwarp();
            int it = (smem_u32(smem_raw) & 0xFFFFFF) == SB ? 0 : 1 << 20;
            while (!mbar_try(B_DONE, 0) || !mbar_try(B_MOD, 0))
                if (++it > (1 << 20)) fault();
        } else if (warp == 13) {
#pragma unroll 1
            for (int i = 0; i < 10; i++) sts16(SM_SENT + i * 512 + lane * 16, SENT, SENT, SENT, SENT);
            fence_async_smem();
            __syncwarp();
            if (elect_one()) {
                mbar_expect_tx(B_RG, 2560);
                mbar_expect_tx(B_GU, cid < NFFN ? 20480 : 24576);
                asm volatile("mbarrier.expect_tx.relaxed.cta.shared::cta.b64 [%0], 10240;" ::"r"(B_RG2) : "memory");
                pace(t_start, RW1_T);
                bulk_load(SM_RED, P.w_r, 1280, B_RG);
                bulk_load(SM_RED + 1280, P.gate_w, 1280, B_RG);
#pragma unroll 1
                for (int i = 0; i < 5; i++) {
                    pace(t_start, RG1_T0 + i * RG1_DT);
                    tma_3d(SM_HALO + i * 2048, &P.xg, B_RG2, 320 + i * 64, par, p0 + hg * 16);
                }
#pragma unroll
                for (int i = 0; i < 23; i++) mbar_init(B_GUD + i * 8, i == 10 ? 8 : i == 22 || i == 9 || !i ? 4 : i < 16 ? 1 : 2);
                bulk_store(sc + SC_HALO, SM_SENT, 5120);
                asm volatile("cp.async.bulk.commit_group;\ncp.async.bulk.wait_group 0;" ::: "memory");
                mbar_arrive(B_RG2);
                TS(43);
                const unsigned goal = (ld_relaxed4(g_cnt + 32) | (NCTA - 1)) + 1;
#pragma unroll 1
                for (int i = 0; i < RS_N; i++) {
                    pace(t_start, RS_T0 + i * RS_DT);
                    bulk_store(sc + i * (1280 / RS_N), SM_SENT, 20480 / RS_N);
                }
                asm volatile("cp.async.bulk.commit_group;\ncp.async.bulk.wait_group 0;" ::: "memory");
                red_inc(g_cnt + 32, goal);
                mbar_arrive(B_RS);
                TS(44);
                while (ld_relaxed4(g_cnt + 32) - goal > 0x80000000u) {}
                mbar_arrive(B_INIT);
                TS(45);
            }
        } else if (warp == 14) {
            if (elect_one()) {
#pragma unroll 1
                for (int kb = 1; kb < 10; kb++) {
                    const uint32_t fb = B_FULL + (kb & 3) * 16, dst = SM_X + (kb & 3) * 16384;
                    mbar_wait(fb + (B_EMPTY - B_FULL + 8), ~(kb >> 2) & 1);
                    if (kb >= 4) mbar_wait(B_XE + (kb - 4 >> 1) * 8, 0);
                    pace(t_start, max(PACE_A - PACE_B / 2 + 2 * kb * PACE_B, PACE_W0 - X_OFF + (2 * kb + 1) * PACE));
                    tma_3d(dst, &P.x2, fb, kb * 64, par, p0);
                    TS5(41 + kb);
                }
            }
            __syncwarp();
            pace(t_start, CAND_T);
            {
                const uint32_t tag = lds4(SM_KEY + 20 * 4);
                uint4 c[2], v;
                do {
                    c[0] = ld_relaxed16(g_cand + lane * 2);
                    c[1] = ld_relaxed16(g_cand + lane * 2 + 64);
                    v = ld_relaxed16(g_gate + tile * 128 + lane * 4);
                } while (__any_sync(0xffffffffu, ((c[0].x ^ tag) | (c[0].z ^ tag) | (c[1].x ^ tag) | (c[1].z ^ tag) | (v.x ^ tag) |
                                                  (v.y ^ tag) | (v.z ^ tag) | (v.w ^ tag)) & 0xF800u));
                const uint32_t a1 = max(c[0].x, c[0].z), b1 = max(c[1].x, c[1].z), l1 = max(a1, b1);
                const uint32_t l2 = max(max(max(c[0].y, c[0].w), max(c[1].y, c[1].w)),
                                        max(max(min(c[0].x, c[0].z), min(c[1].x, c[1].z)), min(a1, b1)));
                const uint32_t k1 = __reduce_max_sync(0xffffffffu, l1);
                const uint32_t k2 = __reduce_max_sync(0xffffffffu, l1 == k1 ? l2 : l1);
                sts16(SM_GATE + lane * 16, v.x, v.y, v.z, v.w);
                __syncwarp();
                if (elect_one()) {
                    bulk_load(SM_XS, P.xp + (~k1 & 2047) * 640 + (cid & 3) * 160, 320, B_XS);
                    bulk_load(SM_XS + 320, P.xp + (~k2 & 2047) * 640 + (cid & 3) * 160, 320, B_XS);
                    sts16(SM_KEY + 16 * 4, k1, k2, 0, 0);
                    mbar_expect_tx(B_XS, 640);
                    mbar_arrive(B_GT);
                    TS(56);
                }
            }
            bar_sync(12, 64);
            pace(t_start, 0);
            pace(clock(), HALO_D);
            if (HALO_T) pace(t_start, HALO_T);
            TS(24);
            uint4 hv[5];
            poll<5>(hv, sc + (SC_HALO - (tile < 2 ? 0 : 16 * SC_SIZE) + lane), 32);
#pragma unroll
            for (int s = 0; s < 5; s++) sts16(SM_HALO + s * 512 + lane * 16, hv[s].x, hv[s].y, hv[s].z, hv[s].w);
            bar_arrive(8, 64);
            TS(25);
        } else {
            if (elect_one()) {
#pragma unroll 1
                for (int s = W_S0; s < 20; s++) {
                    const uint32_t fb = B_FULL + (s & 7) * 8, dst = SM_W + (s & 7) * 15360;
                    mbar_wait(fb + (B_EMPTY - B_FULL), ~(s >> 3) & 1);
                    pace(t_start, max(PACE_A + s * PACE_B, PACE_W0 + s * PACE));
                    mbar_expect_tx(fb, (s & 1) ? 15360 : 15360 + 16384);
                    tma_3d(dst, &P.w, fb, wcm, s * 32, 0);
                    tma_3d(dst + 12288, &P.wr, fb, wcr, s * 32, 0);
                    TS2(20 + s);
                    if (s == W_S0) TS(41);
                }
                mbar_wait(B_RG2, 0);
                if (NFFN) {
                    mbar_wait(B_EMPTY + 5 * 8, 1);
                    mbar_expect_tx(B_UP, cid < NFFN ? 20480 : 16384);
                    TS(46);
                    if (cid < NFFN) tma_2d(SM_UP, &P.up, B_UP, (cid >> 2) * 64, (cid & 3) * 160);
                    else
#pragma unroll 1
                        for (int i = 0; i < 8; i++) tma_2d(SM_UP + i * 2048, &P.down, B_UP, i * 64, cid * 32 - 2352);
                }
                const int cb = hg >> 1, ca = (cb * 5 + 1) >> 1, cr = cb * 160 + ((cb & 1) ? 0 : 128);
                pace(t_start, C0_T);
#pragma unroll 1
                for (int j = 0; j < 8; j++) {
                    const int i = j ^ (j == 3 || j == 4 ? 7 : 0);
                    if (j != 3) mbar_wait(j < 3 ? B_EMPTY + ((2 * j + 7) & 7) * 8 : B_GUD + (j - 4) * 8, j == 0);
                    if (j >= 5) pace(clock(), j == 5 ? C5_D : C6_D);
                    const uint32_t dst = wo_buf(i), gb = B_G2 + i * 8;
                    mbar_expect_tx(gb, 25600);
                    tma_3d(dst, &P.woa, gb, 0, src_of(i, hg) * 80, ca);
                    tma_2d(dst + 20480, &P.wob, gb, cr, src_of(i, hg) * 80);
                }
            }
        }
    }
}

typedef CUresult (*EncodeFn)(CUtensorMap*, CUtensorMapDataType, cuuint32_t, void*, const cuuint64_t*, const cuuint64_t*,
                             const cuuint32_t*, const cuuint32_t*, CUtensorMapInterleave, CUtensorMapSwizzle,
                             CUtensorMapL2promotion, CUtensorMapFloatOOBfill);

void encode(EncodeFn fn, CUtensorMap* m, const void* ptr, int rank, const cuuint64_t* dims, const cuuint64_t* strides,
            const cuuint32_t* box, CUtensorMapSwizzle swz) {
    const cuuint32_t es[4] = {1, 1, 1, 1};
    fn(m, CU_TENSOR_MAP_DATA_TYPE_BFLOAT16, rank, const_cast<void*>(ptr), dims, strides, box, es,
       CU_TENSOR_MAP_INTERLEAVE_NONE, swz, CU_TENSOR_MAP_L2_PROMOTION_L2_128B, CU_TENSOR_MAP_FLOAT_OOB_FILL_NONE);
}

}

extern "C" void kernel_launch(void* const* d_in, const int* in_sizes, int n_in, void* d_out, int out_size) {
    (void)in_sizes; (void)n_in; (void)out_size;
    Params P;
    P.xp = (const __nv_bfloat16*)d_in[0];
    P.wp = (const __nv_bfloat16*)d_in[1];
    P.op = (__nv_bfloat16*)d_out;
    P.w_r = (const __nv_bfloat16*)d_in[4];
    P.gate_w = (const __nv_bfloat16*)d_in[8];

    void* fp = nullptr;
    cudaDriverEntryPointQueryResult st;
    cudaGetDriverEntryPoint("cuTensorMapEncodeTiled", &fp, cudaEnableDefault, &st);
    EncodeFn fn = (EncodeFn)fp;
    const cuuint64_t xd[3] = {640, 2, 1024}, xs[2] = {1280, 2560};
    const cuuint32_t bx[3] = {64, 1, 64}, bx2[3] = {64, 1, 128};
    encode(fn, &P.x2, d_in[0], 3, xd, xs, bx2, CU_TENSOR_MAP_SWIZZLE_128B);
    encode(fn, &P.x, d_in[0], 3, xd, xs, bx, CU_TENSOR_MAP_SWIZZLE_128B);
    const cuuint64_t wd[3] = {640, 640, 3}, ws[2] = {3840, 1280};
    const cuuint32_t bw[3] = {64, 32, 3}, bwr[3] = {16, 32, 3};
    encode(fn, &P.w, d_in[1], 3, wd, ws, bw, CU_TENSOR_MAP_SWIZZLE_128B);
    encode(fn, &P.wr, d_in[1], 3, wd, ws, bwr, CU_TENSOR_MAP_SWIZZLE_32B);
    const cuuint64_t ad[3] = {64, 640, 10}, as[2] = {1280, 128}, bd[2] = {640, 640};
    const cuuint32_t ba[3] = {64, 80, 2}, bb[2] = {32, 80};
    encode(fn, &P.woa, d_in[2], 3, ad, as, ba, CU_TENSOR_MAP_SWIZZLE_128B);
    encode(fn, &P.wob, d_in[2], 2, bd, as, bb, CU_TENSOR_MAP_SWIZZLE_128B);
    const cuuint64_t gd[2] = {1728, 640}, gs[1] = {3456}, dd[2] = {640, 1728};
    const cuuint32_t bg[2] = {64, 20}, bu[2] = {64, 160}, bdn[2] = {64, 16}, bxg[3] = {64, 1, 16};
    encode(fn, &P.xg, d_in[0], 3, xd, xs, bxg, CU_TENSOR_MAP_SWIZZLE_128B);
    encode(fn, &P.gate, d_in[5], 2, gd, gs, bg, CU_TENSOR_MAP_SWIZZLE_128B);
    encode(fn, &P.up, d_in[6], 2, gd, gs, bu, CU_TENSOR_MAP_SWIZZLE_128B);
    encode(fn, &P.down, d_in[7], 2, dd, as, bdn, CU_TENSOR_MAP_SWIZZLE_128B);

    cudaFuncSetAttribute(fused_kernel, cudaFuncAttributeMaxDynamicSharedMemorySize, SM_TOTAL);
    fused_kernel<<<NCTA + NEXTRA, 512, SM_TOTAL, cudaStreamPerThread>>>(P);
}
```

```cpp
#include <cuda_runtime.h>
#include <cuda_bf16.h>
#include <cuda.h>
#include <stdint.h>

namespace {

constexpr int NCTA = 128, NEXTRA = 4;
constexpr int NFFN = 108;
constexpr uint32_t SENT = 0xFFFFFFFFu;

constexpr uint32_t SB = 1024;
constexpr uint32_t SM_W = SB;
constexpr uint32_t SM_X = SB + 122880;
constexpr uint32_t SM_F = SB + 192512;
constexpr uint32_t SM_HALO = SB + 212992;
constexpr uint32_t SM_BAR = SB + 223232;
constexpr uint32_t SM_PROF = SB + 223744;
constexpr uint32_t SM_KEY = SB + 224000;
constexpr uint32_t SM_RED = SB + 224128;
constexpr uint32_t SM_XS = SB + 226688;
constexpr uint32_t SM_SENT = SB + 227328;
constexpr uint32_t SM_U = SM_RED + 1920;
constexpr uint32_t SM_H = SM_RED + 1536;
constexpr uint32_t SM_GATE = SM_RED;
constexpr uint32_t SM_TOTAL = 232448;
constexpr uint32_t SM_HALO1 = SM_X + 32768;
constexpr uint32_t SM_UP = SM_W + 61440;
constexpr uint32_t SM_OUT = SM_W + 61440;

constexpr uint32_t B_XL0 = SM_BAR, B_FULL = SM_BAR + 8, B_GT = SM_BAR + 72, B_RG = SM_BAR + 80, B_RG2 = SM_BAR + 88,
                   B_XS = SM_BAR + 96, B_EMPTY = SM_BAR + 128, B_DONE = SM_BAR + 192, B_XE = SM_BAR + 200,
                   B_GUD = SM_BAR + 224, B_OE = SM_BAR + 232, B_OT = SM_BAR + 264, B_MOD = SM_BAR + 296,
                   B_GU = SM_BAR + 104, B_UP = SM_BAR + 112, B_RS = SM_BAR + 312, B_INIT = SM_BAR + 320,
                   B_RE = SM_BAR + 328, B_PUB = SM_BAR + 304, B_G2 = SM_BAR + 336, B_DF = SM_BAR + 400;

struct Params {
    CUtensorMap x, x2, w, wr, woa, wob, xg, gate, up, down;
    __nv_bfloat16* op;
    const __nv_bfloat16 *xp, *wp, *w_r, *gate_w;
};

constexpr int SC_O = 0;
constexpr int SC_HALO = 1280;
constexpr int SC_GU = 1440;
constexpr int SC_Y = 1504;
constexpr int SC_SIZE = 1600;
__device__ __align__(128) uint4 g_sc[NCTA * SC_SIZE];
__device__ __align__(128) uint2 g_cand[NCTA];
__device__ __align__(16) uint32_t g_gate[2048];
__device__ __align__(128) unsigned g_cnt[64];
#define TS(i) do { } while (0)
#define TS2(i) do { } while (0)
#define TSX(i) do { } while (0)

#define TSL(i) do { } while (0)
#define TS5(i) do { } while (0)
__device__ __forceinline__ uint32_t smem_u32(const void* p) { return (uint32_t)__cvta_generic_to_shared(p); }
__device__ __forceinline__ void fault() { asm volatile("st.shared.u32 [%0], %0;" ::"r"(0x100001) : "memory"); }
__device__ __forceinline__ void mbar_init(uint32_t bar, uint32_t cnt) {
    asm volatile("mbarrier.init.shared::cta.b64 [%0], %1;" ::"r"(bar), "r"(cnt) : "memory");
}
__device__ __forceinline__ void mbar_expect_tx(uint32_t bar, uint32_t bytes) {
    asm volatile("mbarrier.arrive.expect_tx.shared::cta.b64 _, [%0], %1;" ::"r"(bar), "r"(bytes) : "memory");
}
__device__ __forceinline__ void mbar_arrive(uint32_t bar) {
    asm volatile("mbarrier.arrive.shared::cta.b64 _, [%0];" ::"r"(bar) : "memory");
}
__device__ __forceinline__ bool mbar_try(uint32_t bar, uint32_t parity) {
    uint32_t ok;
    asm volatile("{\n.reg .pred p;\nmbarrier.try_wait.parity.shared::cta.b64 p, [%1], %2;\nselp.u32 %0, 1, 0, p;\n}"
                 : "=r"(ok) : "r"(bar), "r"(parity) : "memory");
    return ok;
}
__device__ __forceinline__ void mbar_wait(uint32_t bar, uint32_t parity) {
    asm volatile("{\n.reg .pred p;\nAGAIN:\nmbarrier.try_wait.parity.shared::cta.b64 p, [%0], %1;\n@!p bra AGAIN;\n}"
                 ::"r"(bar), "r"(parity) : "memory");
}
__device__ __forceinline__ void tma_2d(uint32_t dst, const CUtensorMap* m, uint32_t bar, int c0, int c1) {
    asm volatile("cp.async.bulk.tensor.2d.shared::cluster.global.mbarrier::complete_tx::bytes [%0], [%1, {%3, %4}], [%2];"
                 ::"r"(dst), "l"(m), "r"(bar), "r"(c0), "r"(c1) : "memory");
}
__device__ __forceinline__ void bulk_load(uint32_t dst, const void* src, uint32_t bytes, uint32_t bar) {
    asm volatile("cp.async.bulk.shared::cluster.global.mbarrier::complete_tx::bytes [%0], [%1], %2, [%3];"
                 ::"r"(dst), "l"(src), "r"(bytes), "r"(bar) : "memory");
}
__device__ __forceinline__ void bulk_store(void* dst, uint32_t src, uint32_t bytes) {
    asm volatile("cp.async.bulk.global.shared::cta.bulk_group [%0], [%1], %2;" ::"l"(dst), "r"(src), "r"(bytes) : "memory");
}
__device__ __forceinline__ void tma_3d(uint32_t dst, const CUtensorMap* m, uint32_t bar, int c0, int c1, int c2) {
    asm volatile("cp.async.bulk.tensor.3d.shared::cluster.global.mbarrier::complete_tx::bytes [%0], [%1, {%3, %4, %5}], [%2];"
                 ::"r"(dst), "l"(m), "r"(bar), "r"(c0), "r"(c1), "r"(c2) : "memory");
}
__device__ __forceinline__ void fence_async_smem() { asm volatile("fence.proxy.async.shared::cta;" ::: "memory"); }
__device__ __forceinline__ void wg_fence() { asm volatile("wgmma.fence.sync.aligned;" ::: "memory"); }
__device__ __forceinline__ void wg_commit() { asm volatile("wgmma.commit_group.sync.aligned;" ::: "memory"); }
template <int N> __device__ __forceinline__ void wg_wait() { asm volatile("wgmma.wait_group.sync.aligned %0;" ::"n"(N) : "memory"); }
__device__ __forceinline__ void bar_sync(int id, int n) { asm volatile("bar.cta.sync %0, %1;" ::"r"(id), "r"(n) : "memory"); }
__device__ __forceinline__ void bar_arrive(int id, int n) { asm volatile("bar.cta.arrive %0, %1;" ::"r"(id), "r"(n) : "memory"); }

__device__ constexpr uint32_t desc_lo(uint32_t addr, uint32_t lbo) { return (addr >> 4) | ((lbo >> 4) << 16); }
__device__ __forceinline__ bool elect_one() {
    uint32_t p;
    asm volatile("{\n.reg .pred p;\nelect.sync _|p, 0xffffffff;\nselp.u32 %0, 1, 0, p;\n}" : "=r"(p));
    return p;
}
__device__ __forceinline__ uint32_t ld_relaxed4(const void* p) {
    uint32_t v;
    asm volatile("ld.relaxed.gpu.global.u32 %0, [%1];" : "=r"(v) : "l"(p) : "memory");
    return v;
}
__device__ __forceinline__ void st_relaxed4(void* p, uint32_t v) {
    asm volatile("st.relaxed.gpu.global.u32 [%0], %1;" ::"l"(p), "r"(v) : "memory");
}
template <int N = 1>
__device__ __forceinline__ void red_inc(unsigned* p, unsigned after) {
    asm volatile("red.relaxed.gpu.global.add.u32 [%0], %2;" ::"l"(p), "r"(after), "n"(N) : "memory");
}
__device__ __forceinline__ uint32_t lds4(uint32_t a) {
    uint32_t v;
    asm volatile("ld.shared.u32 %0, [%1];" : "=r"(v) : "r"(a) : "memory");
    return v;
}
__device__ __forceinline__ float2 lds8f(uint32_t a) {
    float2 v;
    asm volatile("ld.shared.v2.f32 {%0, %1}, [%2];" : "=f"(v.x), "=f"(v.y) : "r"(a) : "memory");
    return v;
}
__device__ __forceinline__ void sts4(uint32_t a, uint32_t v) { asm volatile("st.shared.u32 [%0], %1;" ::"r"(a), "r"(v) : "memory"); }
__device__ __forceinline__ uint32_t hadd2(uint32_t a, uint32_t b) {
    uint32_t d;
    asm("add.rn.bf16x2 %0, %1, %2;" : "=r"(d) : "r"(a), "r"(b));
    return d;
}
__device__ __forceinline__ uint32_t hfma2(uint32_t a, uint32_t b, uint32_t c) {
    uint32_t d;
    asm("fma.rn.bf16x2 %0, %1, %2, %3;" : "=r"(d) : "r"(a), "r"(b), "r"(c));
    return d;
}
__device__ __forceinline__ uint4 ld_relaxed16(const void* p) {
    uint4 v;
    asm volatile("{\n.reg .b128 t;\n.reg .b64 lo, hi;\nld.relaxed.gpu.global.b128 t, [%4];\nmov.b128 {lo, hi}, t;\n"
                 "mov.b64 {%0, %1}, lo;\nmov.b64 {%2, %3}, hi;\n}" : "=r"(v.x), "=r"(v.y), "=r"(v.z), "=r"(v.w) : "l"(p) : "memory");
    return v;
}
__device__ __forceinline__ void st_relaxed16(void* p, uint32_t a, uint32_t b, uint32_t c, uint32_t d) {
    uint64_t lo = (uint64_t)a | ((uint64_t)b << 32), hi = (uint64_t)c | ((uint64_t)d << 32);
    asm volatile("{\n.reg .b128 t;\nmov.b128 t, {%1, %2};\nst.relaxed.gpu.global.b128 [%0], t;\n}" ::"l"(p), "l"(lo), "l"(hi) : "memory");
}
__device__ __forceinline__ void st_relaxed8(void* p, uint32_t a, uint32_t b) {
    asm volatile("{\n.reg .b64 t;\nmov.b64 t, {%1, %2};\nst.relaxed.gpu.global.b64 [%0], t;\n}" ::"l"(p), "r"(a), "r"(b) : "memory");
}
__device__ __forceinline__ uint4 lds16(uint32_t a) {
    uint4 v;
    asm volatile("ld.shared.v4.u32 {%0, %1, %2, %3}, [%4];" : "=r"(v.x), "=r"(v.y), "=r"(v.z), "=r"(v.w) : "r"(a) : "memory");
    return v;
}
__device__ __forceinline__ void sts16(uint32_t a, uint32_t x, uint32_t y, uint32_t z, uint32_t w) {
    asm volatile("st.shared.v4.u32 [%0], {%1, %2, %3, %4};" ::"r"(a), "r"(x), "r"(y), "r"(z), "r"(w) : "memory");
}
__device__ __forceinline__ uint32_t pack2(float lo, float hi) {
    uint32_t r;
    asm("cvt.rn.bf16x2.f32 %0, %1, %2;" : "=r"(r) : "f"(hi), "f"(lo));
    return r;
}
__device__ __forceinline__ uint32_t pack2v(float lo, float hi) {
    uint32_t r;
    asm volatile("cvt.rn.bf16x2.f32 %0, %1, %2;" : "=r"(r) : "f"(hi), "f"(lo));
    return r;
}
__device__ __forceinline__ float bf_lo(uint32_t u) { return __uint_as_float(u << 16); }
__device__ __forceinline__ float bf_hi(uint32_t u) { return __uint_as_float(u & 0xFFFF0000u); }
__device__ __forceinline__ float bf_round(float f) { return __bfloat162float(__float2bfloat16_rn(f)); }
__device__ __forceinline__ uint32_t prmt(uint32_t a, uint32_t sel) {
    uint32_t d;
    asm("prmt.b32 %0, %1, 0, %2;" : "=r"(d) : "r"(a), "r"(sel));
    return d;
}
__device__ __forceinline__ uint32_t movm(uint32_t a) {
    uint32_t d;
    asm volatile("movmatrix.sync.aligned.m8n8.trans.b16 %0, %1;" : "=r"(d) : "r"(a));
    return d;
}
__device__ __forceinline__ void mma16(float (&c)[4], uint32_t a0, uint32_t a1, uint32_t a2, uint32_t a3, uint32_t b0, uint32_t b1) {
    asm volatile("mma.sync.aligned.m16n8k16.row.col.f32.bf16.bf16.f32 {%0,%1,%2,%3}, {%4,%5,%6,%7}, {%8,%9}, {%0,%1,%2,%3};"
                 : "+f"(c[0]), "+f"(c[1]), "+f"(c[2]), "+f"(c[3]) : "r"(a0), "r"(a1), "r"(a2), "r"(a3), "r"(b0), "r"(b1));
}
__device__ __forceinline__ void mma8(float (&c)[4], uint32_t a0, uint32_t a1, uint32_t b0) {
    asm volatile("mma.sync.aligned.m16n8k8.row.col.f32.bf16.bf16.f32 {%0,%1,%2,%3}, {%4,%5}, {%6}, {%0,%1,%2,%3};"
                 : "+f"(c[0]), "+f"(c[1]), "+f"(c[2]), "+f"(c[3]) : "r"(a0), "r"(a1), "r"(b0));
}
__device__ __forceinline__ float ex2(float x) { float y; asm("ex2.approx.ftz.f32 %0, %1;" : "=f"(y) : "f"(x)); return y; }
__device__ __forceinline__ float rcp(float x) { float y; asm("rcp.approx.ftz.f32 %0, %1;" : "=f"(y) : "f"(x)); return y; }
__device__ __forceinline__ float sigmoidf(float z) { return rcp(1.0f + ex2(z * -1.4426950408889634f)); }
__device__ __forceinline__ float u2f(uint32_t u) { return __uint_as_float(u); }
__device__ __forceinline__ uint32_t f2u(float f) { return __float_as_uint(f); }

__device__ __forceinline__ void wgmma_main(float (&d)[96], uint32_t a, uint32_t b, int scale_d) {
    asm volatile("{\n.reg .pred p;\n.reg .b64 da, db;\nsetp.ne.b32 p, %98, 0;\n"
        "mov.b64 da, {%96, 0x40000040};\nmov.b64 db, {%97, 0x40000040};\n"
        "wgmma.mma_async.sync.aligned.m64n192k16.f32.bf16.bf16 "
        "{%0, %1, %2, %3, %4, %5, %6, %7, %8, %9, %10, %11, %12, %13, %14, %15, "
        "%16, %17, %18, %19, %20, %21, %22, %23, %24, %25, %26, %27, %28, %29, %30, %31, "
        "%32, %33, %34, %35, %36, %37, %38, %39, %40, %41, %42, %43, %44, %45, %46, %47, "
        "%48, %49, %50, %51, %52, %53, %54, %55, %56, %57, %58, %59, %60, %61, %62, %63, "
        "%64, %65, %66, %67, %68, %69, %70, %71, %72, %73, %74, %75, %76, %77, %78, %79, "
        "%80, %81, %82, %83, %84, %85, %86, %87, %88, %89, %90, %91, %92, %93, %94, %95}, "
        "da, db, p, 1, 1, 0, 1;\n}\n"
        : "+f"(d[0]), "+f"(d[1]), "+f"(d[2]), "+f"(d[3]), "+f"(d[4]), "+f"(d[5]), "+f"(d[6]), "+f"(d[7]),
          "+f"(d[8]), "+f"(d[9]), "+f"(d[10]), "+f"(d[11]), "+f"(d[12]), "+f"(d[13]), "+f"(d[14]), "+f"(d[15]),
          "+f"(d[16]), "+f"(d[17]), "+f"(d[18]), "+f"(d[19]), "+f"(d[20]), "+f"(d[21]), "+f"(d[22]), "+f"(d[23]),
          "+f"(d[24]), "+f"(d[25]), "+f"(d[26]), "+f"(d[27]), "+f"(d[28]), "+f"(d[29]), "+f"(d[30]), "+f"(d[31]),
          "+f"(d[32]), "+f"(d[33]), "+f"(d[34]), "+f"(d[35]), "+f"(d[36]), "+f"(d[37]), "+f"(d[38]), "+f"(d[39]),
          "+f"(d[40]), "+f"(d[41]), "+f"(d[42]), "+f"(d[43]), "+f"(d[44]), "+f"(d[45]), "+f"(d[46]), "+f"(d[47]),
          "+f"(d[48]), "+f"(d[49]), "+f"(d[50]), "+f"(d[51]), "+f"(d[52]), "+f"(d[53]), "+f"(d[54]), "+f"(d[55]),
          "+f"(d[56]), "+f"(d[57]), "+f"(d[58]), "+f"(d[59]), "+f"(d[60]), "+f"(d[61]), "+f"(d[62]), "+f"(d[63]),
          "+f"(d[64]), "+f"(d[65]), "+f"(d[66]), "+f"(d[67]), "+f"(d[68]), "+f"(d[69]), "+f"(d[70]), "+f"(d[71]),
          "+f"(d[72]), "+f"(d[73]), "+f"(d[74]), "+f"(d[75]), "+f"(d[76]), "+f"(d[77]), "+f"(d[78]), "+f"(d[79]),
          "+f"(d[80]), "+f"(d[81]), "+f"(d[82]), "+f"(d[83]), "+f"(d[84]), "+f"(d[85]), "+f"(d[86]), "+f"(d[87]),
          "+f"(d[88]), "+f"(d[89]), "+f"(d[90]), "+f"(d[91]), "+f"(d[92]), "+f"(d[93]), "+f"(d[94]), "+f"(d[95])
        : "r"(a), "r"(b), "r"(scale_d));
}

__device__ __forceinline__ void wgmma_rem(float (&d)[24], uint32_t a, uint32_t b, int scale_d) {
    asm volatile("{\n.reg .pred p;\n.reg .b64 da, db;\nsetp.ne.b32 p, %26, 0;\n"
        "mov.b64 da, {%24, 0x40000040};\nmov.b64 db, {%25, 0xC0000010};\n"
        "wgmma.mma_async.sync.aligned.m64n48k16.f32.bf16.bf16 "
        "{%0, %1, %2, %3, %4, %5, %6, %7, %8, %9, %10, %11, %12, %13, %14, %15, "
        "%16, %17, %18, %19, %20, %21, %22, %23}, "
        "da, db, p, 1, 1, 0, 1;\n}\n"
        : "+f"(d[0]), "+f"(d[1]), "+f"(d[2]), "+f"(d[3]), "+f"(d[4]), "+f"(d[5]), "+f"(d[6]), "+f"(d[7]),
          "+f"(d[8]), "+f"(d[9]), "+f"(d[10]), "+f"(d[11]), "+f"(d[12]), "+f"(d[13]), "+f"(d[14]), "+f"(d[15]),
          "+f"(d[16]), "+f"(d[17]), "+f"(d[18]), "+f"(d[19]), "+f"(d[20]), "+f"(d[21]), "+f"(d[22]), "+f"(d[23])
        : "r"(a), "r"(b), "r"(scale_d));
}

__device__ __forceinline__ void wgmma_out(float (&d)[80], uint32_t a, uint32_t b, int scale_d) {
    asm volatile("{\n.reg .pred p;\n.reg .b64 da, db;\nsetp.ne.b32 p, %82, 0;\n"
        "mov.b64 da, {%80, 0x50};\nmov.b64 db, {%81, 0x40000040};\n"
        "wgmma.mma_async.sync.aligned.m64n160k16.f32.bf16.bf16 "
        "{%0, %1, %2, %3, %4, %5, %6, %7, %8, %9, %10, %11, %12, %13, %14, %15, "
        "%16, %17, %18, %19, %20, %21, %22, %23, %24, %25, %26, %27, %28, %29, %30, %31, "
        "%32, %33, %34, %35, %36, %37, %38, %39, %40, %41, %42, %43, %44, %45, %46, %47, "
        "%48, %49, %50, %51, %52, %53, %54, %55, %56, %57, %58, %59, %60, %61, %62, %63, "
        "%64, %65, %66, %67, %68, %69, %70, %71, %72, %73, %74, %75, %76, %77, %78, %79}, "
        "da, db, p, 1, 1, 0, 1;\n}\n"
        : "+f"(d[0]), "+f"(d[1]), "+f"(d[2]), "+f"(d[3]), "+f"(d[4]), "+f"(d[5]), "+f"(d[6]), "+f"(d[7]),
          "+f"(d[8]), "+f"(d[9]), "+f"(d[10]), "+f"(d[11]), "+f"(d[12]), "+f"(d[13]), "+f"(d[14]), "+f"(d[15]),
          "+f"(d[16]), "+f"(d[17]), "+f"(d[18]), "+f"(d[19]), "+f"(d[20]), "+f"(d[21]), "+f"(d[22]), "+f"(d[23]),
          "+f"(d[24]), "+f"(d[25]), "+f"(d[26]), "+f"(d[27]), "+f"(d[28]), "+f"(d[29]), "+f"(d[30]), "+f"(d[31]),
          "+f"(d[32]), "+f"(d[33]), "+f"(d[34]), "+f"(d[35]), "+f"(d[36]), "+f"(d[37]), "+f"(d[38]), "+f"(d[39]),
          "+f"(d[40]), "+f"(d[41]), "+f"(d[42]), "+f"(d[43]), "+f"(d[44]), "+f"(d[45]), "+f"(d[46]), "+f"(d[47]),
          "+f"(d[48]), "+f"(d[49]), "+f"(d[50]), "+f"(d[51]), "+f"(d[52]), "+f"(d[53]), "+f"(d[54]), "+f"(d[55]),
          "+f"(d[56]), "+f"(d[57]), "+f"(d[58]), "+f"(d[59]), "+f"(d[60]), "+f"(d[61]), "+f"(d[62]), "+f"(d[63]),
          "+f"(d[64]), "+f"(d[65]), "+f"(d[66]), "+f"(d[67]), "+f"(d[68]), "+f"(d[69]), "+f"(d[70]), "+f"(d[71]),
          "+f"(d[72]), "+f"(d[73]), "+f"(d[74]), "+f"(d[75]), "+f"(d[76]), "+f"(d[77]), "+f"(d[78]), "+f"(d[79])
        : "r"(a), "r"(b), "r"(scale_d));
}

__device__ __forceinline__ void wgmma_own(float (&d)[80], uint32_t a0, uint32_t a1, uint32_t a2, uint32_t a3, uint32_t b, int scale_d) {
    asm volatile("{\n.reg .pred p;\n.reg .b64 db;\nsetp.ne.b32 p, %85, 0;\nmov.b64 db, {%84, 0x40000040};\n"
        "wgmma.mma_async.sync.aligned.m64n160k16.f32.bf16.bf16 "
        "{%0, %1, %2, %3, %4, %5, %6, %7, %8, %9, %10, %11, %12, %13, %14, %15, "
        "%16, %17, %18, %19, %20, %21, %22, %23, %24, %25, %26, %27, %28, %29, %30, %31, "
        "%32, %33, %34, %35, %36, %37, %38, %39, %40, %41, %42, %43, %44, %45, %46, %47, "
        "%48, %49, %50, %51, %52, %53, %54, %55, %56, %57, %58, %59, %60, %61, %62, %63, "
        "%64, %65, %66, %67, %68, %69, %70, %71, %72, %73, %74, %75, %76, %77, %78, %79}, "
        "{%80, %81, %82, %83}, db, p, 1, 1, 1;\n}\n"
        : "+f"(d[0]), "+f"(d[1]), "+f"(d[2]), "+f"(d[3]), "+f"(d[4]), "+f"(d[5]), "+f"(d[6]), "+f"(d[7]),
          "+f"(d[8]), "+f"(d[9]), "+f"(d[10]), "+f"(d[11]), "+f"(d[12]), "+f"(d[13]), "+f"(d[14]), "+f"(d[15]),
          "+f"(d[16]), "+f"(d[17]), "+f"(d[18]), "+f"(d[19]), "+f"(d[20]), "+f"(d[21]), "+f"(d[22]), "+f"(d[23]),
          "+f"(d[24]), "+f"(d[25]), "+f"(d[26]), "+f"(d[27]), "+f"(d[28]), "+f"(d[29]), "+f"(d[30]), "+f"(d[31]),
          "+f"(d[32]), "+f"(d[33]), "+f"(d[34]), "+f"(d[35]), "+f"(d[36]), "+f"(d[37]), "+f"(d[38]), "+f"(d[39]),
          "+f"(d[40]), "+f"(d[41]), "+f"(d[42]), "+f"(d[43]), "+f"(d[44]), "+f"(d[45]), "+f"(d[46]), "+f"(d[47]),
          "+f"(d[48]), "+f"(d[49]), "+f"(d[50]), "+f"(d[51]), "+f"(d[52]), "+f"(d[53]), "+f"(d[54]), "+f"(d[55]),
          "+f"(d[56]), "+f"(d[57]), "+f"(d[58]), "+f"(d[59]), "+f"(d[60]), "+f"(d[61]), "+f"(d[62]), "+f"(d[63]),
          "+f"(d[64]), "+f"(d[65]), "+f"(d[66]), "+f"(d[67]), "+f"(d[68]), "+f"(d[69]), "+f"(d[70]), "+f"(d[71]),
          "+f"(d[72]), "+f"(d[73]), "+f"(d[74]), "+f"(d[75]), "+f"(d[76]), "+f"(d[77]), "+f"(d[78]), "+f"(d[79])
        : "r"(a0), "r"(a1), "r"(a2), "r"(a3), "r"(b), "r"(scale_d));
}

__device__ __forceinline__ void wgmma_vec(float (&d)[8], uint32_t a, uint32_t b, int scale_d) {
    asm volatile("{\n.reg .pred p;\n.reg .b64 da, db;\nsetp.ne.b32 p, %10, 0;\n"
        "mov.b64 da, {%8, 0x40000040};\nmov.b64 db, {%9, 0x14};\n"
        "wgmma.mma_async.sync.aligned.m64n16k16.f32.bf16.bf16 {%0, %1, %2, %3, %4, %5, %6, %7}, da, db, p, 1, 1, 1, 0;\n}\n"
        : "+f"(d[0]), "+f"(d[1]), "+f"(d[2]), "+f"(d[3]), "+f"(d[4]), "+f"(d[5]), "+f"(d[6]), "+f"(d[7])
        : "r"(a), "r"(b), "r"(scale_d));
}

#define TSA(i) do { } while (0)
#define MAP_TILE(b) ((((b) >> 1) & 14) | ((b) & 1))
#define MAP_HG(b) (((b) >> 4 & 14) | ((b) >> 1 & 1))
#define HALF (int)(bid >> 1 & 1)
#define GM 0x78A0
#define SKEW 4
#define W_S0 2
#define EPF_N 15
#define EPF_M 15
#define RG_ORDER 0x24130
#define RS_N 10
#define DN_R 5
#define P2W 4
#define EPF_T 900
#define PACE_A 250
#define PACE_B 450
#define PACE_W0 (-700)
#define PACE 500
#define X_OFF 350
#define RW1_T 0
#define RG1_T0 1900
#define RG1_DT 200
#define DN_T0 800
#define DN_DT 62
#define DN_T1 100000
#define DN_D1 45
#define GU_T0 3600
#define GU_DT 750
#define GU_DS (GU_DT * 7 / 11)
#define GU_ST 60
#define CAND_T 9000
#define RS_T0 8850
#define RS_DT 100
#define C0_T 11100
#define C5_D 0
#define C6_D 100
#define HALO_D 550
#define HALO_T 12050
#define H_T 13150
#define H_C 1000
#define HS_T 13150
#define L0_T 14450
#define L1_T 14050
#define LS_T 14450
#define F0_T 14600
#define F1_T 14400
#define F0_D 200
#define F1_D 0
#define O_DT 285
#define Y_T 15500
#define Y2_T 16850

__device__ __forceinline__ uint32_t keep(uint32_t v) { return __shfl_xor_sync(0xffffffffu, v, 0); }
__device__ __forceinline__ uint32_t ukeep(uint32_t v) { return __shfl_sync(0xffffffffu, v, 0); }
__device__ __forceinline__ void ldsm2(uint32_t* d, uint32_t a) {
    asm volatile("ldmatrix.sync.aligned.m8n8.x4.shared.b16 {%0,%1,%2,%3}, [%8];\nldmatrix.sync.aligned.m8n8.x4.shared.b16 {%4,%5,%6,%7}, [%9];"
                 : "=r"(d[0]), "=r"(d[1]), "=r"(d[2]), "=r"(d[3]), "=r"(d[4]), "=r"(d[5]), "=r"(d[6]), "=r"(d[7])
                 : "r"(a), "r"(a ^ 32) : "memory");
}
__device__ __forceinline__ void ldsm_t(uint32_t (&d)[4], uint32_t a) {
    asm volatile("ldmatrix.sync.aligned.m8n8.x4.trans.shared.b16 {%0,%1,%2,%3}, [%4];"
                 : "=r"(d[0]), "=r"(d[1]), "=r"(d[2]), "=r"(d[3]) : "r"(a) : "memory");
}
template <bool SWP, int SEG, int E>
__device__ __forceinline__ void pack_blocks(uint32_t (&d)[10], const float (&am)[96], const float (&ar)[24]) {
#pragma unroll
    for (int t = 0; t < 10; t++) {
        const float* p = (SWP ? t < 2 : t >= 8) ? ar + (SEG * 2 + (t & 1)) * 4 + E : am + (SEG * 8 + t - (SWP ? 2 : 0)) * 4 + E;
        d[t] = pack2v(p[0], p[1]);
    }
}
__device__ __forceinline__ int src_of(int i, int hg) {
    return i == 0 ? hg : (0x75316240u >> (i - (i <= (hg >> 2 | hg & 2))) * 4 & 7) ^ (hg & 1);
}

__device__ __forceinline__ uint32_t o_buf(int i) { return __byte_perm(0xD199ADA3u, 0xC7BDu, i - 2 | 0x7770) << 10; }
__device__ constexpr uint32_t wo_buf(int i) { return SM_W + ((0x10342103u >> i * 4) & 7) * 30720; }

template <int N>
__device__ __forceinline__ void poll(uint4 (&a)[N], const uint4* p, int stride) {
    bool bad;
    do {
        bad = false;
#pragma unroll
        for (int s = 0; s < N; s++) a[s] = ld_relaxed16(p + s * stride);
#pragma unroll
        for (int s = 0; s < N; s++) bad |= a[s].w == SENT;
    } while (__any_sync(0xffffffffu, bad));
}
__device__ __forceinline__ void pace(unsigned t0, int t) {
    asm volatile("{\n.reg .pred p;\n.reg .s32 d;\nAGAIN:\nmov.u32 d, %%clock;\nsub.s32 d, d, %0;\nsetp.lt.s32 p, d, 0;\n"
                 "@p nanosleep.u32 20;\n@p bra AGAIN;\n}" ::"r"(t0 + t) : "memory");
}
__device__ __forceinline__ void l2_prefetch(const void* p) { asm volatile("prefetch.global.L2 [%0];" ::"l"(p) : "memory"); }

template <int N>
__device__ __forceinline__ bool landed(const uint4* w, int lane) {
    uint32_t a = 0;
#pragma unroll
    for (int i = 0; i < N; i++) a ^= w[i].w;
    return __ballot_sync(0xffffffffu, lane == 0 || a == 0) && lane == 0;
}
__device__ __forceinline__ void swiglu(const uint4 (&a)[4], uint32_t dst, uint32_t stride) {
    const float g0 = bf_round((u2f(a[0].x) + u2f(a[1].x)) + (u2f(a[2].x) + u2f(a[3].x)));
    const float g1 = bf_round((u2f(a[0].y) + u2f(a[1].y)) + (u2f(a[2].y) + u2f(a[3].y)));
    const float u0 = bf_round((u2f(a[0].z) + u2f(a[1].z)) + (u2f(a[2].z) + u2f(a[3].z)));
    const float u1 = bf_round((u2f(a[0].w) + u2f(a[1].w)) + (u2f(a[2].w) + u2f(a[3].w)));
    const uint32_t h = pack2(bf_round(g0 * sigmoidf(g0)) * u0, bf_round(g1 * sigmoidf(g1)) * u1);
    asm volatile("st.shared.u16 [%0], %2;\nst.shared.u16 [%1], %3;" ::"r"(dst), "r"(dst + stride), "h"((uint16_t)h), "h"((uint16_t)(h >> 16)) : "memory");
}
template <int N>
__device__ __forceinline__ float4 vec_mma(const uint4 (&w)[N], const uint32_t* x, uint32_t sel) {
    float c[4][4] = {};
    const uint32_t s[4] = {sel, sel >> 16, sel + ((sel & 0x10101010u) >> 3) * 17, (sel + ((sel & 0x10101010u) >> 3) * 17) >> 16};
#pragma unroll
    for (int i = 0; i < N; i++)
        mma16(c[i & 3], w[i].x, w[i].y, w[i].z, w[i].w, prmt(x[i >> 1], s[(i & 1) * 2]), prmt(x[i >> 1], s[(i & 1) * 2 + 1]));
    return make_float4((c[0][0] + c[1][0]) + (c[2][0] + c[3][0]), (c[0][1] + c[1][1]) + (c[2][1] + c[3][1]),
                       (c[0][2] + c[1][2]) + (c[2][2] + c[3][2]), (c[0][3] + c[1][3]) + (c[2][3] + c[3][3]));
}

__global__ void __launch_bounds__(512, 1) fused_kernel(const __grid_constant__ Params P) {
    extern __shared__ __align__(1024) uint8_t smem_raw[];
    const unsigned t_start = clock();
    const int tid = threadIdx.x, lane = tid & 31;
    unsigned sm, bid;
    asm("mov.u32 %0, %%smid;" : "=r"(sm));
    const CUtensorMap* mx = &P.x;
    asm volatile("" : "+l"(mx));
    if ((unsigned)(tid - 480) < EPF_N) l2_prefetch(P.wp + (tid * 132 + sm) * 64 - 480 * 132 * 64);
    const int warp = __shfl_sync(0xffffffffu, threadIdx.x >> 5, 0);
    asm("{\n.reg .pred p;\n.reg .b32 t, u;\nshr.u32 t, %1, 1;\nmad.lo.s32 u, t, 14, -928;\nmad.lo.s32 t, t, 37, -925;\nmax.s32 t, t, 0;\n"
        "shr.u32 t, t, 7;\nand.b32 t, t, 14;\nsetp.ge.u32 p, %1, 124;\nselp.b32 t, u, t, p;\nadd.s32 %0, %1, t;\n}" : "=r"(bid) : "r"(sm));
    bid ^= GM >> (bid & 14) & 6;
    const int hg = MAP_HG(bid), par = bid & 1, p0 = (MAP_TILE(bid) >> 1) * 128;
    const bool swp = (hg & 3) == 3;
    const int wcm = hg * 80 + (swp ? 16 : 0), wcr = hg * 80 + (swp ? 0 : 64);
    if (warp == 0) {
        if (elect_one()) {
#pragma unroll
            for (int i = 0; i < 4; i++) mbar_init(SM_BAR + i * 8, 1);
            asm volatile("fence.mbarrier_init.release.cluster;" ::: "memory");
            if (bid < NCTA) {
                mbar_expect_tx(B_FULL, 15360 + 8192);
                tma_3d(SM_X + 8192, mx, B_FULL, 0, par, p0 + 64);
                tma_3d(SM_W, mx + 2, B_FULL, wcm, 0, 0);
                tma_3d(SM_W + 12288, mx + 3, B_FULL, wcr, 0, 0);
                TS(40);
                mbar_expect_tx(B_XL0, 8192);
                tma_3d(SM_X, mx, B_XL0, 0, par, p0);
                mbar_expect_tx(B_FULL + 8, 15360);
                tma_3d(SM_W + 15360, mx + 2, B_FULL + 8, wcm, 32, 0);
                tma_3d(SM_W + 15360 + 12288, mx + 3, B_FULL + 8, wcr, 32, 0);
            }
        }
    }
    if ((unsigned)(warp - 1) < 6 && elect_one()) {
#pragma unroll
        for (int i = 0; i < 4; i++) mbar_init(SM_BAR + warp * 32 + i * 8, warp < 4 ? 1 : warp < 6 ? 2 : 4);
        asm volatile("fence.mbarrier_init.release.cluster;" ::: "memory");
    }
    asm volatile("" : "+r"(bid));
    const int role = bid >= NCTA ? -1 : warp, e = sm & 3;
    const int tile = MAP_TILE(bid), cid = tile * 8 + hg;
    uint4* const sc = g_sc + cid * SC_SIZE;
    __syncthreads();

    if (role < 0) {
        const int half = warp >> 3;
        if (!NFFN) {
            if (tid == 0) red_inc<NCTA / NEXTRA>(g_cnt, 0);
            return;
        }
        uint32_t wf[DN_R][5][4], la[5];
        auto rows = [&](uint32_t l) {
#pragma unroll
            for (int i = 0; i < 5; i++) {
                const uint32_t c = (warp & 7) * 10 + 2 * i + (l >> 3 & 1);
                la[i] = SB + half * 20480 + (c >> 3) * 2048 + (l & 7) * 128 + (l >> 4) * 1024 + (((c ^ l) & 7) << 4);
            }
        };
        rows(lane);
        auto fetch = [&](int j, int n, uint32_t bar) {
#pragma unroll 1
            for (int h = 0; h < n; h++) {
                pace(t_start, min(DN_T0 + (j * 20 + h * 10 + warp) * DN_DT, DN_T1 + (j * 20 + h * 10 + warp) * DN_D1));
                tma_2d(SB + (j % 5) * 40960 + h * 20480 + warp * 2048, &P.down, bar, warp * 64, e * 272 + (j + h * 9) * 16);
            }
        };
        if (warp < 10 && elect_one()) {
            if (warp <= DN_R) mbar_expect_tx(B_FULL + warp * 8, warp < DN_R ? 40960 : (17 - 2 * DN_R) * 20480);
#pragma unroll 1
            for (int j = 0; j < 5; j++) fetch(j, 2, B_FULL + j * 8);
        }
        const uint32_t tag = (ukeep(ld_relaxed4(g_cnt)) * 8 + 2048) & 0xF800u;
#pragma unroll
        for (int j = 0; j < DN_R; j++) {
            uint32_t any = 0;
            mbar_wait(B_FULL + j * 8, 0);
#pragma unroll
            for (int i = 0; i < 5; i++) {
                ldsm_t(wf[j][i], la[i] + j * 40960);
                any ^= wf[j][i][3];
            }
            if (j < 4) {
                if (__syncthreads_count(any == 0) == 1000) fault();
                if (warp < 10 && elect_one()) fetch(j + 5, j < 3 ? 2 : 1, B_FULL + DN_R * 8);
                if (j == 0 && tid == 0) red_inc<NCTA / NEXTRA>(g_cnt, tag);
            }
            TSX(warp == 0 && j == 0 ? 0 : warp == 0 && j == 3 ? 1 : 63);
        }
        if (warp < 9) {
            pace(t_start, H_T - H_C);
            uint4 a[4];
            do {
                a[0] = ld_relaxed16(g_cand + lane * 2);
                a[1] = ld_relaxed16(g_cand + lane * 2 + 64);
            } while (__any_sync(0xffffffffu, ((a[0].x ^ tag) | (a[0].z ^ tag) | (a[1].x ^ tag) | (a[1].z ^ tag)) & 0xF800u));
            const int u = min(tid, 271), f = e * 272 + u;
            pace(t_start, H_T);
            TSX(warp == 0 ? 3 : 63);
            poll<4>(a, g_sc + (f >> 6) * 4 * SC_SIZE + SC_GU + (f & 63), SC_SIZE);
            TSX(warp == 0 ? 4 : warp == 8 ? 5 : 63);
            swiglu(a, SM_RED + (u >> 4) * 64 + (u & 6) * 4 + (u & 8) / 2 + (u & 1) * 2, 32);
        }
        rows(keep(lane));
        mbar_wait(B_FULL + DN_R * 8, 0);
        TSX(warp == 15 ? 2 : 63);
        __syncthreads();
        float c[5][4] = {};
#pragma unroll
        for (int j = 0; j < 9; j++) {
            if (j == 8 && half) break;
            const float2 b = lds8f(SM_RED + half * 576 + j * 64 + (lane & 7) * 8);
            if (j == 1) TSX(warp == 0 ? 6 : 63);
#pragma unroll
            for (int i = 0; i < 5; i++) {
                if (j >= DN_R) ldsm_t(wf[j % DN_R][i], la[i] + (j % 5) * 40960);
                mma16(c[i], wf[j % DN_R][i][0], wf[j % DN_R][i][1], wf[j % DN_R][i][2], wf[j % DN_R][i][3], f2u(b.x), f2u(b.y));
            }
        }
        const uint32_t ra = SB + 7 * 20480 + half * 5248 + (lane & 1) * 2624 + (warp & 7) * 320 + (lane & 2) * 16 + (lane >> 2) * 4;
#pragma unroll
        for (int i = 0; i < 5; i++) sts4(ra + i * 64, f2u((lane & 2) ? ((lane & 1) ? c[i][3] : c[i][2]) : ((lane & 1) ? c[i][1] : c[i][0])));
        TSX(warp == 0 ? 7 : 63);
        __syncthreads();
        if (warp < 10) {
            const uint32_t ya = SB + 7 * 20480 + (warp & 1) * 2624 + (warp >> 1) * 512 + lane * 16;
            const uint4 y0 = lds16(ya), y1 = lds16(ya + 5248);
            st_relaxed16(g_sc + (e * 5 + (warp >> 1)) * SC_SIZE + SC_Y + (tid & 63), f2u(u2f(y0.x) + u2f(y1.x)), f2u(u2f(y0.y) + u2f(y1.y)),
                         f2u(u2f(y0.z) + u2f(y1.z)), f2u(u2f(y0.w) + u2f(y1.w)));
        }
    } else if (role < 8) {
        asm volatile("setmaxnreg.inc.sync.aligned.u32 192;");
        const int wg = warp >> 2;
        const bool leader = (tid & 127) == 0;
        float am[96], ar[24];
        if (wg == 0) mbar_wait(B_XL0, 0);
        bool rel = false;
        uint32_t nb[40];
        const int odd = (hg >> 1) & 1, kba = ukeep(wg != HALF ? 99 : ((hg >> 1) * 5 + 1) >> 1), kbr = ukeep(kba + 2 - odd * 3);
        const int kbs = wg ? -1 : (20 - SKEW) / 2;
        const uint32_t xrow = keep(SM_X + (warp * 16 + (lane & 15)) * 128 + (((lane >> 4) ^ (lane & 7)) << 4));
#pragma unroll 1
        for (int kb = 0; kb < 10; kb++) {
            const uint32_t fb = B_FULL + (kb & 3) * 16, wo = (kb & 3) * 1920, ph = (kb >> 2) & 1;
            const uint32_t xo = desc_lo(SM_X, 16) + wg * 512 + (kb & 3) * 1024;
#pragma unroll
            for (int h = 0; h < 2; h++) {
                mbar_wait(fb + h * 8, ph);
                if (kb == 0 && h == 0) TS(warp == 0 ? 0 : warp == 4 ? 16 : 63);
                TS2(warp == P2W ? kb * 2 + h : 63);
                {
                    const uint32_t xa = (xrow ^ h * 64) + (kb & 3) * 16384;
                    if (kb == kba) ldsm2(nb + h * 8, xa);
                    if (kb == kba + 1) ldsm2(nb + 16 + h * 8, xa);
                    if (h == 0 && kb == kbr) ldsm2(nb + 32, xa ^ (odd * 64));
                }
                wg_wait<1>();
                if (rel && (h == 0 || kb != kbs)) mbar_arrive(B_EMPTY + ((kb * 16 - 16) & 48) + h * 8);
                if (h == 0 && kb == kbs) {
                    wg_wait<0>();
                    if (rel) mbar_arrive(B_EMPTY + ((19 - SKEW) & 7) * 8);
                    bar_sync(5, 256);
                }
                wg_fence();
                wgmma_main(am, xo + h * 4, desc_lo(SM_W + h * 15360, 4096) + wo, h || kb);
                wgmma_rem(ar, xo + h * 4, desc_lo(SM_W + h * 15360 + 12288, 1024) + wo, h || kb);
                wgmma_main(am, xo + h * 4 + 2, desc_lo(SM_W + h * 15360 + 2048, 4096) + wo, 1);
                wgmma_rem(ar, xo + h * 4 + 2, desc_lo(SM_W + h * 15360 + 12288 + 512, 1024) + wo, 1);
                wg_commit();
            }
            rel = leader;
        }
        if (wg == 1) bar_arrive(5, 256);
        mbar_wait(B_XE + 16, 0);
        mbar_wait(B_RG2, 0);
        mbar_wait(B_EMPTY + 5 * 8, 1);
        wg_wait<0>();
        if (leader) mbar_arrive(B_EMPTY + 3 * 8);
        TS(warp == 0 ? 2 : warp == 4 ? 18 : 63);
        TS2(warp == 0 ? 41 : warp == 4 ? 40 : 63);

        uint32_t kl[10], kh[10], vl[10], vh[10], ql[10], qh[10], kp[10], vp[10];
        if (swp) {
            pack_blocks<true, 1, 2>(kh, am, ar);
            pack_blocks<true, 2, 2>(vh, am, ar);
        } else {
            pack_blocks<false, 1, 2>(kh, am, ar);
            pack_blocks<false, 2, 2>(vh, am, ar);
        }
        const int w4 = warp & 3;
        const uint32_t pbuf = (wg ? SM_HALO1 : SM_HALO) + w4 * 2560 + lane * 16;
        const uint32_t hbuf = warp == 3 ? SM_HALO1 + lane * 16 : pbuf + 2560;
        {
            const uint32_t ex[20] = {kh[0], kh[1], kh[3], kh[4], kh[5], kh[6], kh[8], kh[9], kh[2], kh[7],
                                     vh[0], vh[1], vh[2], vh[3], vh[4], vh[5], vh[6], vh[7], vh[8], vh[9]};
            if (warp == 7) {
                uint4* const hp = sc + SC_HALO + lane;
#pragma unroll
                for (int s = 0; s < 5; s++) st_relaxed16(hp + s * 32, ex[4 * s], ex[4 * s + 1], ex[4 * s + 2], ex[4 * s + 3]);
                bar_arrive(12, 64);
            } else {
#pragma unroll
                for (int s = 0; s < 5; s++) sts16(hbuf + s * 512, ex[4 * s], ex[4 * s + 1], ex[4 * s + 2], ex[4 * s + 3]);
            }
        }
        TS(warp == 7 ? 22 : warp == 3 ? 23 : 63);
        if (warp == 3) bar_arrive(11, 64);
        if (swp) {
            pack_blocks<true, 2, 0>(vl, am, ar);
            pack_blocks<true, 0, 0>(ql, am, ar);
            pack_blocks<true, 0, 2>(qh, am, ar);
            pack_blocks<true, 1, 0>(kl, am, ar);
        } else {
            pack_blocks<false, 2, 0>(vl, am, ar);
            pack_blocks<false, 0, 0>(ql, am, ar);
            pack_blocks<false, 0, 2>(qh, am, ar);
            pack_blocks<false, 1, 0>(kl, am, ar);
        }
#pragma unroll
        for (int t = 0; t < 10; t++) { vl[t] = movm(vl[t]); vh[t] = movm(vh[t]); }
        mbar_wait(B_RS, 0);
        mbar_wait(B_GT, 0);
        const float g0 = bf_hi(lds4(SM_GATE + warp * 64 + (lane & 28))), g1 = bf_hi(lds4(SM_GATE + 32 + warp * 64 + (lane & 28)));

        const int r = lane >> 2, cq = lane & 3;
        const bool no_prev = warp == 0 && tile < 2, low = cq < 2;
        const bool le0 = 2 * cq <= r, le1 = 2 * cq + 1 <= r;
        const uint32_t mle = (le0 ? 0xFFFFu : 0u) | (le1 ? 0xFFFF0000u : 0u);
        const float scl = 0.22360679774997896f * 1.4426950408889634f;
        uint32_t pl[4], ph[4];
        {
            float sl[4][4], sh[4][4], sp[4][4];
            auto exchange = [&]() {
            TSA(warp == 1 ? 26 : 63);
            bar_sync(6 + wg, 128);
            if (w4 == 0) bar_sync(8 + wg * 3, 64);
            {
                const uint4 a = lds16(pbuf), b = lds16(pbuf + 512), c = lds16(pbuf + 1024), d = lds16(pbuf + 1536), e = lds16(pbuf + 2048);
                kp[0] = a.x; kp[1] = a.y; kp[3] = a.z; kp[4] = a.w; kp[5] = b.x; kp[6] = b.y; kp[8] = b.z; kp[9] = b.w;
                kp[2] = c.x; kp[7] = c.y; vp[0] = c.z; vp[1] = c.w; vp[2] = d.x; vp[3] = d.y; vp[4] = d.z; vp[5] = d.w;
                vp[6] = e.x; vp[7] = e.y; vp[8] = e.z; vp[9] = e.w;
            }
            TSA(warp == 0 ? 3 : warp == 4 ? 19 : warp == 5 ? 27 : 63);
            };
            exchange();
#pragma unroll
            for (int h = 0; h < 4; h++) {
                const int ta = (h >> 1) * 5 + (h & 1) * 3, tc = (h >> 1) * 5 + 2;
                const uint32_t ml = low != (h & 1) ? ql[tc] : 0u, mh = low != (h & 1) ? qh[tc] : 0u;
#pragma unroll
                for (int e = 0; e < 4; e++) sl[h][e] = sh[h][e] = sp[h][e] = 0.f;
                mma16(sl[h], ql[ta], qh[ta], ql[ta + 1], qh[ta + 1], kl[ta], kl[ta + 1]);
                mma16(sh[h], ql[ta], qh[ta], ql[ta + 1], qh[ta + 1], kh[ta], kh[ta + 1]);
                mma8(sl[h], ml, mh, kl[tc]);
                mma8(sh[h], ml, mh, kh[tc]);
            }
#pragma unroll
            for (int h = 0; h < 4; h++) {
                const int ta = (h >> 1) * 5 + (h & 1) * 3, tc = (h >> 1) * 5 + 2;
                mma16(sp[h], ql[ta], qh[ta], ql[ta + 1], qh[ta + 1], kp[ta], kp[ta + 1]);
                mma8(sp[h], low != (h & 1) ? ql[tc] : 0u, low != (h & 1) ? qh[tc] : 0u, kp[tc]);
            }
#pragma unroll
            for (int t = 0; t < 10; t++) vp[t] = movm(vp[t]);
#pragma unroll
            for (int h = 0; h < 4; h++) {
                if (no_prev) sp[h][0] = sp[h][1] = -1e9f / 0.22360679774997896f;
                const float a0 = le0 ? sl[h][0] : sp[h][0], a1 = le1 ? sl[h][1] : sp[h][1];
                const float b0 = le0 ? sh[h][2] : sl[h][2], b1 = le1 ? sh[h][3] : sl[h][3];
                float ma = fmaxf(a0, a1), mb = fmaxf(b0, b1);
                ma = fmaxf(ma, __shfl_xor_sync(0xffffffffu, ma, 1));
                mb = fmaxf(mb, __shfl_xor_sync(0xffffffffu, mb, 1));
                ma = fmaxf(ma, __shfl_xor_sync(0xffffffffu, ma, 2)) * -scl;
                mb = fmaxf(mb, __shfl_xor_sync(0xffffffffu, mb, 2)) * -scl;
                pl[h] = pack2(ex2(fmaf(a0, scl, ma)), ex2(fmaf(a1, scl, ma)));
                ph[h] = pack2(ex2(fmaf(b0, scl, mb)), ex2(fmaf(b1, scl, mb)));
            }
        }
        TSA(warp == 0 ? 4 : warp == 4 ? 20 : warp == 5 ? 28 : 63);
        uint32_t ol[10], oh[10];
        {
            uint32_t* const po = reinterpret_cast<uint32_t*>(sc + SC_O + warp * 160) + lane;
            const uint32_t ONES = 0x3F803F80u;
            float o[12][4];
#pragma unroll
            for (int hp = 0; hp < 2; hp++) {
#pragma unroll
                for (int h = hp * 2; h < hp * 2 + 2; h++) {
                    const int ta = (h >> 1) * 5 + (h & 1) * 3, tc = (h >> 1) * 5 + 2;
                    const bool mine = (lane < 16) != (h & 1);
                    const uint32_t a0 = pl[h] & mle, a1 = ph[h] & ~mle, a3 = ph[h] & mle, ap = pl[h] & ~mle;
#pragma unroll
                    for (int i = 0; i < 3; i++) o[h * 3 + i][0] = o[h * 3 + i][1] = o[h * 3 + i][2] = o[h * 3 + i][3] = 0.f;
                    mma16(o[h * 3 + 2], a0, a1, 0u, a3, mine ? vl[tc] : ONES, mine ? vh[tc] : ONES);
                    mma16(o[h * 3], a0, a1, 0u, a3, vl[ta], vh[ta]);
                    mma16(o[h * 3 + 1], a0, a1, 0u, a3, vl[ta + 1], vh[ta + 1]);
                    mma8(o[h * 3 + 2], ap, 0u, mine ? vp[tc] : ONES);
                    mma8(o[h * 3], ap, 0u, vp[ta]);
                    mma8(o[h * 3 + 1], ap, 0u, vp[ta + 1]);
                }
                if (hp && wg != HALF) bar_arrive(2, 256);
                const float (&oa)[4] = o[hp * 6 + 2], (&ob)[4] = o[hp * 6 + 5];
                const float hl = rcp(low ? ob[0] : oa[0]) * g0, hh = rcp(low ? ob[2] : oa[2]) * g1;
                const float gl = __shfl_xor_sync(0xffffffffu, hl, 2), gh = __shfl_xor_sync(0xffffffffu, hh, 2);
                const float ial = low ? gl : hl, iah = low ? gh : hh, ibl = low ? hl : gl, ibh = low ? hh : gh;
#pragma unroll
                for (int i = 0; i < 2; i++) {
                    ol[hp * 5 + i] = pack2(o[hp * 6 + i][0] * ial, o[hp * 6 + i][1] * ial);
                    oh[hp * 5 + i] = pack2(o[hp * 6 + i][2] * iah, o[hp * 6 + i][3] * iah);
                    ol[hp * 5 + 3 + i] = pack2(o[hp * 6 + 3 + i][0] * ibl, o[hp * 6 + 3 + i][1] * ibl);
                    oh[hp * 5 + 3 + i] = pack2(o[hp * 6 + 3 + i][2] * ibh, o[hp * 6 + 3 + i][3] * ibh);
                }
                ol[hp * 5 + 2] = pack2((low ? oa[0] : ob[0]) * gl, (low ? oa[1] : ob[1]) * gl);
                oh[hp * 5 + 2] = pack2((low ? oa[2] : ob[2]) * gh, (low ? oa[3] : ob[3]) * gh);
#pragma unroll
                for (int t = hp * 5; t < hp * 5 + 5; t++) {
                    st_relaxed4(po + t * 32, ol[t]);
                    st_relaxed4(po + 320 + t * 32, oh[t]);
                }
            }
        }
        TS(warp == 0 ? 5 : warp == 4 ? 21 : warp == 5 ? 29 : warp == 1 ? 31 : 63);
        if (lane == 0) mbar_arrive(B_PUB);
        const uint4* ow = sc + (SC_O + HALF * 640 - hg * SC_SIZE);
        mbar_wait(B_INIT, 0);
        if (wg != HALF) {
            mbar_wait(B_PUB, 0);
            const unsigned t0 = t_start + max((unsigned)clock() - t_start + (wg ? F0_D : F1_D), wg ? F0_T : F1_T);
            uint32_t ph = 0;
#pragma unroll 1
            for (int i = w4 + 2; i < 8; i += 4) {
                const uint4* src = ow + src_of(i, hg) * SC_SIZE;
                const uint32_t buf = o_buf(i), chk = buf + lane * 132;
                pace(t0, (i - 2) * O_DT);
                if (i > 5) mbar_wait(B_DF, 0);
                if (i == 2) TS(wg ? 3 : 4);
                uint32_t c;
                do {
                    if (elect_one()) {
                        mbar_expect_tx(B_OT + w4 * 8, 10240);
                        bulk_load(buf, src, 10240, B_OT + w4 * 8);
                    }
                    mbar_wait(B_OT + w4 * 8, ph);
                    if (i == 2 && !ph) TS(wg ? 19 : 20);
                    ph ^= 1;
                    c = max(max(lds4(chk), lds4(chk + 4096)), lds4(chk + 6144));
                } while (__any_sync(0xffffffffu, c == SENT));
                if (lane == 0) mbar_arrive(B_G2 + i * 8);
                TS(i == 2 ? 33 : 32 + i);
            }
            return;
        }

        float oc[80];
        uint32_t af[20];
        auto fetch = [&]() {
            const uint32_t* p = reinterpret_cast<const uint32_t*>(ow + src_of(1, hg) * SC_SIZE + w4 * 160) + lane;
#pragma unroll
            for (int t = 0; t < 20; t++) af[t] = ld_relaxed4(p + t * 32);
        };
        mbar_wait(B_XS, 0);
        const int orow = p0 + wg * 64 + w4 * 16;
        const uint32_t tk1 = ~lds4(SM_KEY + 16 * 4) & 2047, tk2 = ~lds4(SM_KEY + 17 * 4) & 2047;
        const uint32_t sel1 = (tk1 & 1) == par ? (tk1 >> 1) - orow : 99, sel2 = (tk2 & 1) == par ? (tk2 >> 1) - orow : 99;
        const uint32_t n0 = pack2(1.f - g0, 1.f - g0), n1 = pack2(1.f - g1, 1.f - g1);
        const uint32_t stg = SM_OUT + w4 * 5120;
        const uint32_t m128 = keep(stg + (lane & 15) * 128 + (((lane >> 4) ^ (lane & 7)) << 4));
        const uint32_t m64 = keep(stg + 4096 + (lane & 15) * 64 + (((lane >> 4) ^ ((lane >> 1) & 3)) << 4));
        const uint32_t l128 = keep(stg + (lane >> 3) * 128 + (((lane & 7) ^ (lane >> 3)) << 4));
        const uint32_t l64 = keep(stg + 4096 + r * 64 + ((cq ^ (lane >> 3)) << 4));
        char* const o128 = reinterpret_cast<char*>(P.op) + keep(((orow + (lane >> 3)) * 2 + par) * 1280 + kba * 128 + (lane & 7) * 16);
        char* const o64 = reinterpret_cast<char*>(P.op) + keep(((orow + r) * 2 + par) * 1280 + kbr * 128 + odd * 64 + cq * 16);
        mbar_wait(B_G2, 0);
        mbar_wait(B_G2 + 8, 0);
        const bool ff = cid < NFFN;
        if (ff) {
            pace(t_start, wg ? L1_T : L0_T);
            fetch();
        }
        bar_sync(2, 256);
        TS(w4 == 0 ? 6 : 63);
        wg_fence();
#pragma unroll
        for (int s = 0; s < 5; s++)
            wgmma_own(oc, ol[2 * s], oh[2 * s], ol[2 * s + 1], oh[2 * s + 1], desc_lo(wo_buf(0), 10240) + s * 128, s);
        wg_commit();
        if (!ff) {
            pace(t_start, LS_T);
            fetch();
        }
        TS(w4 == 0 ? 28 : 63);
        mbar_wait(B_DF, 0);
        for (;;) {
            uint32_t m = 0;
#pragma unroll
            for (int t = 0; t < 20; t++) m = max(m, af[t]);
            if (!__any_sync(0xffffffffu, m == SENT)) break;
            fetch();
        }
        TS(w4 == 0 ? 7 : 63);
        wg_fence();
#pragma unroll
        for (int s = 0; s < 5; s++)
            wgmma_own(oc, af[2 * s], af[10 + 2 * s], af[2 * s + 1], af[11 + 2 * s], desc_lo(wo_buf(1), 10240) + s * 128, 1);
        wg_commit();
        wg_wait<1>();
        if (leader) mbar_arrive(B_OE);
#pragma unroll 1
        for (int i = 2; i < 8; i++) {
            const uint32_t ao = desc_lo(0, 128) + (o_buf(i) >> 4), wo = desc_lo(0, 10240) + (wo_buf(i) >> 4);
            mbar_wait(B_G2 + i * 8, 0);
            TS(w4 == 0 ? (i < 2 ? 6 + i : i < 7 ? 9 + i : 17) : 63);
            wg_fence();
#pragma unroll
            for (int s = 0; s < 5; s++) wgmma_out(oc, ao + s * 16, wo + s * 128, 1);
            wg_commit();
            if (i < 4) {
                wg_wait<1>();
                if (i > 1 && leader) mbar_arrive(B_OE - 8 + i * 8);
            }
        }
        TS(w4 == 0 ? 8 : 63);

        if (min(sel1, sel2) < 16) {
#pragma unroll 1
            for (int j = 0; j < 2; j++) {
                const uint32_t sel = j ? sel2 : sel1;
                if (sel > 16) continue;
                mbar_wait(B_MOD, 0);
#pragma unroll
                for (int t = 0; t < 5; t++) {
                    const uint4 v = lds16(SM_U + j * 320 + cq * 80 + t * 16);
                    const uint32_t u[4] = {v.x, v.y, v.z, v.w};
#pragma unroll
                    for (int k = 0; k < 4; k++) {
                        if (sel == r) nb[8 * t + 2 * k] = hadd2(nb[8 * t + 2 * k], u[k]);
                        if (sel == r + 8) nb[8 * t + 2 * k + 1] = hadd2(nb[8 * t + 2 * k + 1], u[k]);
                    }
                }
            }
            TS(26);
        }
        wg_wait<0>();
        TS(w4 == 0 ? 9 : 63);
        const bool nan = oc[0] != oc[0] || oc[2] != oc[2];
#pragma unroll
        for (int part = 0; part < 3; part++) {
            const int s0 = part ? part * 4 - 4 : 8, ns = part ? 4 : 2;
#pragma unroll
            for (int i = 0; i < 4; i++) {
                if (i >= ns) break;
                const int s = s0 + i;
                const uint32_t y0 = hfma2(n0, nb[s * 4], pack2(oc[s * 8 + 0], oc[s * 8 + 1]));
                const uint32_t y1 = hfma2(n1, nb[s * 4 + 1], pack2(oc[s * 8 + 2], oc[s * 8 + 3]));
                const uint32_t y2 = hfma2(n0, nb[s * 4 + 2], pack2(oc[s * 8 + 4], oc[s * 8 + 5]));
                const uint32_t y3 = hfma2(n1, nb[s * 4 + 3], pack2(oc[s * 8 + 6], oc[s * 8 + 7]));
                asm volatile("stmatrix.sync.aligned.m8n8.x4.shared.b16 [%0], {%1,%2,%3,%4};"
                             ::"r"(((s < 8 ? m128 : m64) ^ ((s & 3) * 32)) + (s & 4) * 512), "r"(y0), "r"(y1), "r"(y2), "r"(y3) : "memory");
            }
            __syncwarp();
            uint4 v[4];
#pragma unroll
            for (int i = 0; i < 4; i++)
                if (i < ns) v[i] = lds16(!part ? l64 + i * 512 : (l128 ^ ((i & 1) * 64)) + i * 512 + s0 * 512);
#pragma unroll
            for (int i = 0; i < 4; i++)
                if (i < ns) *reinterpret_cast<uint4*>(!part ? o64 + i * 8 * 2560 : o128 + i * 4 * 2560 + s0 * 32) = v[i];
            if (part == 0) TS(w4 == 0 ? 1 : 63);
        }
        TS(w4 == 0 ? 10 : 63);
        TSL(w4);
        if (lane == 0) mbar_arrive(B_DONE);
        uint32_t redo;
        asm volatile("{\n.reg .pred p, q;\nsetp.ne.u32 p, %1, 0;\nbar.cta.red.or.pred q, 10, 128, p;\nselp.u32 %0, 1, 0, q;\n}"
                     : "=r"(redo) : "r"((uint32_t)nan) : "memory");
        if (redo) {
            const int cb = hg >> 1;
#pragma unroll 1
            for (int i = 0; i < 8; i++) {
                if (leader) {
                    mbar_expect_tx(B_RE, 25600);
                    tma_3d(SM_W, &P.woa, B_RE, 0, i * 80, (cb * 5 + 1) >> 1);
                    tma_2d(SM_W + 20480, &P.wob, B_RE, cb * 160 + ((cb & 1) ? 0 : 128), i * 80);
                }
#pragma unroll 1
                for (int s = 0; s < 20; s++) {
                    const int w = w4 * 640 + s * 32 + lane;
                    uint32_t v, it = 0;
                    do {
                        v = ld_relaxed4(reinterpret_cast<const uint32_t*>(ow + i * SC_SIZE) + w);
                        if (++it > (1u << 22)) fault();
                    } while ((v >> 16) == 0xFFFFu || (v & 0xFFFFu) == 0xFFFFu);
                    sts4(SM_X + w * 4, v);
                }
                fence_async_smem();
                __syncwarp();
                bar_sync(10, 128);
                mbar_wait(B_RE, i & 1);
                wg_fence();
#pragma unroll
                for (int s = 0; s < 5; s++) wgmma_out(oc, desc_lo(SM_X, 128) + s * 16, desc_lo(SM_W, 10240) + s * 128, s || i);
                wg_commit();
                wg_wait<0>();
                bar_sync(10, 128);
            }
#pragma unroll
            for (int t = 0; t < 40; t++) {
                const int col = (t < 32 ? kba * 64 + (t >> 1) * 8 : kbr * 64 + odd * 32 + ((t - 32) >> 1) * 8) + cq * 2;
                *reinterpret_cast<uint32_t*>(P.op + ((orow + r + (t & 1) * 8) * 2 + par) * 640 + col) =
                    hfma2((t & 1) ? n1 : n0, nb[t], pack2(oc[2 * t], oc[2 * t + 1]));
            }
        }
    } else if (role < 12) {
        asm volatile("setmaxnreg.dec.sync.aligned.u32 96;");
        const int t = tid - 256;
        uint32_t tag = ld_relaxed4(g_cnt);
        float gv = 0.f;
        int grow = hg * 16 + (t >> 3);
        mbar_wait(B_RG, 0);
        TS(warp == 8 ? 48 : 63);
        {
            float r0 = 0.f, r1 = 0.f, g0 = 0.f, g1 = 0.f;
            const uint32_t sw = (t >> 4) * 128 + (((t ^ (t >> 4)) & 7) << 4), hi = (t >> 3) & 1;
            mbar_wait(B_XL0, 0);
            tag = (tag * 8 + 2048) & 0xF800u;
            sts4(SM_KEY + 20 * 4, tag);
#pragma unroll 1
            for (int i = 0; i < 5; i++) {
                const int p = (RG_ORDER >> (i * 4)) & 7, kb = 2 * p + hi;
                mbar_wait(p < 3 ? B_FULL + (p & 1) * 32 : B_RG2, p == 2);
                if (p < 2) mbar_wait(B_FULL + p * 32 + 16, 0);
                const uint32_t xa = sw + (kb < 5 ? SM_X + (kb & 3) * 16384 + hg * 2048 : SM_HALO - 5 * 2048 + kb * 2048);
                const uint4 a = lds16(xa), b = lds16(xa + 1024);
                const uint4 w = lds16(SM_RED + p * 256 + (t & 15) * 16), v = lds16(SM_RED + 1280 + p * 256 + (t & 15) * 16);
                if (__ballot_sync(0xffffffffu, lane == 0 || a.w == b.w) && lane == 0 && p < 3) mbar_arrive(B_XE + p * 8);
                TS5(warp == 8 ? 51 + i : 63);
                const uint32_t as[4] = {a.x, a.y, a.z, a.w}, bs[4] = {b.x, b.y, b.z, b.w};
                const uint32_t ws[4] = {w.x, w.y, w.z, w.w}, vs[4] = {v.x, v.y, v.z, v.w};
#pragma unroll
                for (int e = 0; e < 4; e++) {
                    r0 = fmaf(bf_lo(as[e]), bf_lo(ws[e]), r0);
                    r1 = fmaf(bf_lo(bs[e]), bf_lo(ws[e]), r1);
                    g0 = fmaf(bf_lo(as[e]), bf_lo(vs[e]), g0);
                    g1 = fmaf(bf_lo(bs[e]), bf_lo(vs[e]), g1);
                    r0 = fmaf(bf_hi(as[e]), bf_hi(ws[e]), r0);
                    r1 = fmaf(bf_hi(bs[e]), bf_hi(ws[e]), r1);
                    g0 = fmaf(bf_hi(as[e]), bf_hi(vs[e]), g0);
                    g1 = fmaf(bf_hi(bs[e]), bf_hi(vs[e]), g1);
                }
            }
            const bool up = lane & 4;
            r0 = (hi ? r1 : r0) + __shfl_xor_sync(0xffffffffu, hi ? r0 : r1, 8);
            g0 = (hi ? g1 : g0) + __shfl_xor_sync(0xffffffffu, hi ? g0 : g1, 8);
            float r = (up ? g0 : r0) + __shfl_xor_sync(0xffffffffu, up ? r0 : g0, 4);
            r += __shfl_xor_sync(0xffffffffu, r, 2);
            r = bf_round(r + __shfl_xor_sync(0xffffffffu, r, 1));
            const int row = hg * 16 + (t >> 4) + hi * 8;
            const uint32_t u = f2u(r);
            if (!up) sts4(SM_KEY + (t >> 3) * 4, (((int)u < 0 ? ~u : u | 0x80000000u) & 0xFFFF0000u) | (2047 - (p0 + row) * 2 - par));
            gv = r;
            grow = row;
        }
        TS(warp == 8 ? 63 : 63);
        mbar_wait(B_RG2, 0);
        bar_sync(4, 128);
        if (warp == 8) {
            const uint32_t key = lds4(SM_KEY + (lane & 15) * 4);
            uint32_t k1 = __reduce_max_sync(0xffffffffu, key);
            uint32_t k2 = __reduce_max_sync(0xffffffffu, key == k1 ? 0u : key);
            if (elect_one()) {
                st_relaxed8(g_cand + cid, k1 | tag, k2 | tag);
                red_inc<1>(g_cnt, tag);
            }
            TS(49);
        }
        if ((lane & 7) == 4) st_relaxed4(g_gate + tile * 128 + grow, f2u(bf_round(sigmoidf(gv))) | tag);
        const int cq = lane & 3, w4 = warp & 3;
        const uint32_t la = keep(cq * 256 + (((lane >> 2) ^ cq * 2) << 4));
        const uint32_t sel = keep(0x44444444u ^ (0x54u << (lane >> 2 & 1) * 8 + (lane & 16)));
        if (NFFN) {
            float4 d;
            uint4* dst;
            if (cid < NFFN) {
                float dg[8], du[8];
                mbar_wait(B_GU, 0);
                mbar_wait(B_XS, 0);
                TS(warp == 8 ? 50 : 63);
                wg_fence();
#pragma unroll
                for (int i = 0; i < 10; i++) wgmma_vec(dg, desc_lo(SM_F + i * 2048, 16), desc_lo(SM_XS + i * 32, 16), i);
                wg_commit();
                mbar_wait(B_UP, 0);
                TS(warp == 10 ? 58 : 63);
                wg_fence();
#pragma unroll
                for (int i = 0; i < 10; i++) wgmma_vec(du, desc_lo(SM_UP + i * 2048, 16), desc_lo(SM_XS + i * 32, 16), i);
                wg_commit();
                wg_wait<0>();
                if (lane == 0) mbar_arrive(B_GUD), mbar_arrive(B_DF);
                TS(warp == 8 ? 54 : warp == 10 ? 59 : 63);
                if (cq == 0) {
                    st_relaxed16(sc + SC_GU + w4 * 16 + (lane >> 2), f2u(dg[0]), f2u(dg[4]), f2u(du[0]), f2u(du[4]));
                    st_relaxed16(sc + SC_GU + w4 * 16 + 8 + (lane >> 2), f2u(dg[2]), f2u(dg[6]), f2u(du[2]), f2u(du[6]));
                }
            } else {
                uint4 wv[2][8], wr[4];
                mbar_wait(B_UP, 0);
                TS(warp == 10 ? 58 : 63);
                mbar_wait(B_EMPTY + 3 * 8, 0);
#pragma unroll
                for (int i = 0; i < 8; i++) wv[i >> 2][4 + (i & 3)] = lds16((la ^ (i & 1) * 144) + SM_UP + w4 * 4096 + (i >> 1) * 1024);
                if (landed<4>(wv[0] + 4, lane) & landed<4>(wv[1] + 4, lane)) mbar_arrive(B_GUD);
                TS(warp == 8 ? 54 : 63);
                mbar_wait(B_GU, 0);
#pragma unroll
                for (int i = 0; i < 4; i++) wr[i] = lds16((la ^ (i & 1) * 144) + SM_F + 12288 + w4 * 2048 + (i >> 1) * 1024);
                mbar_wait(B_XS, 0);
                if (w4 == 0) {
                    uint4 pq[4];
                    pace(t_start, HS_T);
                    poll<4>(pq, g_sc + ((cid >> 1) * 4 - 148) * SC_SIZE + SC_GU + (cid & 1) * 32 + lane, SC_SIZE);
                    TS(warp == 8 ? 55 : 63);
                    swiglu(pq, SM_H + (lane & 6) * 8 + (lane >> 3) * 4 + (lane & 1) * 2, 64);
                }
                bar_sync(4, 128);
                TS(warp == 8 ? 57 : 63);
                const uint4 h = lds16(SM_H + (lane & 8) * 8 + cq * 16);
                const uint32_t hv[4] = {h.x, h.y, h.z, h.w}, hr[2] = {(w4 & 1) ? h.z : h.x, (w4 & 1) ? h.w : h.y};
                d = vec_mma<4>(wr, hr, sel);
                dst = g_sc + (cid * 5 - 520 + w4) * SC_SIZE + SC_Y + (lane & 1) * 32 + (lane >> 1);
                float c[2][2][4] = {};
                const uint32_t s2 = sel + ((sel & 0x10101010u) >> 3) * 17;
#pragma unroll
                for (int i = 7; i >= 0; i--) {
                    const uint32_t x0 = prmt(hv[i >> 1], (i & 1) ? s2 : sel), x1 = prmt(hv[i >> 1], ((i & 1) ? s2 : sel) >> 16);
#pragma unroll
                    for (int n = 0; n < 2; n++) {
                        if (i >= 4) wv[n][i - 4] = lds16((la ^ (i & 1) * 144) + SM_F - 6144 + w4 * 4096 + n * 2048 + (i >> 1) * 1024);
                        mma16(c[n][i & 1], wv[n][i].x, wv[n][i].y, wv[n][i].z, wv[n][i].w, x0, x1);
                    }
                }
#pragma unroll
                for (int n = 0; n < 2; n++)
                    st_relaxed16(dst + n * 16, f2u(c[n][0][0] + c[n][1][0]), f2u(c[n][0][1] + c[n][1][1]), f2u(c[n][0][2] + c[n][1][2]),
                                 f2u(c[n][0][3] + c[n][1][3]));
                dst += (4 - w4) * SC_SIZE + w4 * 8;
                TS(warp == 8 ? 30 : 63);
                if (lane == 0 && f2u(d.x) != SENT) mbar_arrive(B_DF);
                if (w4 & 1) {
                    sts16(SM_RED + 512 + (w4 & 2) * 256 + lane * 16, f2u(d.x), f2u(d.y), f2u(d.z), f2u(d.w));
                    bar_arrive(13 + (w4 >> 1), 64);
                } else {
                    bar_sync(13 + (w4 >> 1), 64);
                    const uint4 o = lds16(SM_RED + 512 + (w4 & 2) * 256 + lane * 16);
                    st_relaxed16(dst, f2u(d.x + u2f(o.x)), f2u(d.y + u2f(o.y)), f2u(d.z + u2f(o.z)), f2u(d.w + u2f(o.w)));
                }
            }
        } else {
            if (t < 4) mbar_arrive(B_GUD);
            if (t < 4) mbar_arrive(B_DF);
            mbar_wait(B_XS, 0);
        }
        TS(warp == 8 ? 51 : 63);
        const uint32_t k1 = lds4(SM_KEY + 16 * 4), k2 = lds4(SM_KEY + 17 * 4);
        const uint32_t mine = (tile >> 1) * 256 + HALF * 128 + par;
        const bool own1 = (~k1 & 0x781) == mine, own2 = (~k2 & 0x781) == mine;
        if ((own1 || own2) && NFFN) {
            const int rg = min(t / 40, 2), un = (hg >> 1) * 40 + t % 40;
            mbar_wait(B_RS, 0);
            pace(t_start, Y_T);
            TS(warp == 8 ? 60 : 63);
#pragma unroll 1
            for (int j = !own1; j <= own2; j++) {
                const uint4* p = g_sc + (rg * 5 + 20 + (un >> 5)) * SC_SIZE + SC_Y + j * 32 + (un & 31);
                float y[4];
                bool bad;
                do {
                    uint4 yp[7];
#pragma unroll
                    for (int i = 0; i < 7; i++) yp[i] = i < 6 || rg < 2 ? ld_relaxed16(p + i * 15 * SC_SIZE) : make_uint4(0, 0, 0, 0);
                    y[0] = y[1] = y[2] = y[3] = 0.f;
                    bad = false;
#pragma unroll
                    for (int i = 0; i < 7; i++) {
                        y[0] += u2f(yp[i].x); y[1] += u2f(yp[i].y); y[2] += u2f(yp[i].z); y[3] += u2f(yp[i].w);
                        bad |= yp[i].w == SENT;
                    }
                } while (__any_sync(0xffffffffu, bad));
                TS(warp == 8 ? 53 : 63);
                sts16(SM_SENT + j * 2048 + t * 16, f2u(y[0]), f2u(y[1]), f2u(y[2]), f2u(y[3]));
            }
            bar_sync(4, 128);
            const int j = w4 >> 1;
            if (j ? own2 : own1) {
                const uint32_t key = j ? k2 : k1, u = min(t & 63, 39), ya = SM_SENT + j * 2048 + u * 16, uq = (hg >> 1) * 40 + u;
                const float rs = bf_round(sigmoidf(u2f(((int)key < 0 ? key & 0x7FFFFFFFu : ~key) & 0xFFFF0000u)));
                const uint4 y0 = lds16(ya), y1 = lds16(ya + 640), y2 = lds16(ya + 1280);
                const uint4* q = g_sc + (uq >> 5) * SC_SIZE + SC_Y + j * 32 + (uq & 31);
                const float sx = u2f(y0.x) + u2f(y1.x) + u2f(y2.x), sy = u2f(y0.y) + u2f(y1.y) + u2f(y2.y);
                const float sz = u2f(y0.z) + u2f(y1.z) + u2f(y2.z), sw = u2f(y0.w) + u2f(y1.w) + u2f(y2.w);
                const uint32_t ua = SM_U + j * 320 + (u & 1) * 160 + ((u >> 1) + (hg & 2) * 8) % 20 * 4;
                uint4 z[4];
                pace(t_start, Y2_T);
                do {
#pragma unroll
                    for (int i = 0; i < 4; i++) z[i] = ld_relaxed16(q + i * 5 * SC_SIZE);
                } while (__any_sync(0xffffffffu, max(max(z[0].w, z[1].w), max(z[2].w, z[3].w)) == SENT));
                TS(warp == 8 ? 62 : 63);
                if ((t & 63) < 40) {
                    sts4(ua, pack2(bf_round(sx + (u2f(z[0].x) + u2f(z[1].x)) + (u2f(z[2].x) + u2f(z[3].x))) * rs,
                                   bf_round(sy + (u2f(z[0].y) + u2f(z[1].y)) + (u2f(z[2].y) + u2f(z[3].y))) * rs));
                    sts4(ua + 80, pack2(bf_round(sz + (u2f(z[0].z) + u2f(z[1].z)) + (u2f(z[2].z) + u2f(z[3].z))) * rs,
                                        bf_round(sw + (u2f(z[0].w) + u2f(z[1].w)) + (u2f(z[2].w) + u2f(z[3].w))) * rs));
                }
            }
        }
        __syncwarp();
        if (lane == 0) mbar_arrive(B_MOD);
        TS(warp == 8 ? 52 : 63);
    } else {
        asm volatile("setmaxnreg.dec.sync.aligned.u32 32;");
        if (warp == 15) {
            pace(t_start, EPF_T);
            if (lane < EPF_M) l2_prefetch(P.wp + (EPF_N * 132 + lane * 128 + bid) * 64);
            if (elect_one()) {
#pragma unroll 1
                for (int i = 0; i < (!NFFN ? 0 : cid < NFFN ? 8 : 12); i++) {
                    pace(t_start, GU_T0 + i * (cid < NFFN ? GU_DT : GU_DS) + (cid & 7) * GU_ST);
                    if (cid < NFFN) tma_2d(SM_F + i * 2560, &P.gate, B_GU, (cid >> 2) * 64, (cid & 3) * 160 + i * 20);
                    else tma_2d(SM_F - 4096 + i * 2048, &P.down, B_GU, min(i, 4 + (i >> 1)) * 64, cid * 32 - 2368 + (i > 8 ? (i & 1) * 16 : 0));
                }
            }
            __syncwarp();
            int it = (smem_u32(smem_raw) & 0xFFFFFF) == SB ? 0 : 1 << 20;
            while (!mbar_try(B_DONE, 0) || !mbar_try(B_MOD, 0))
                if (++it > (1 << 20)) fault();
        } else if (warp == 13) {
#pragma unroll 1
            for (int i = 0; i < 10; i++) sts16(SM_SENT + i * 512 + lane * 16, SENT, SENT, SENT, SENT);
            fence_async_smem();
            __syncwarp();
            if (elect_one()) {
                mbar_expect_tx(B_RG, 2560);
                mbar_expect_tx(B_GU, cid < NFFN ? 20480 : 24576);
                asm volatile("mbarrier.expect_tx.relaxed.cta.shared::cta.b64 [%0], 10240;" ::"r"(B_RG2) : "memory");
                pace(t_start, RW1_T);
                bulk_load(SM_RED, P.w_r, 1280, B_RG);
                bulk_load(SM_RED + 1280, P.gate_w, 1280, B_RG);
#pragma unroll 1
                for (int i = 0; i < 5; i++) {
                    pace(t_start, RG1_T0 + i * RG1_DT);
                    tma_3d(SM_HALO + i * 2048, &P.xg, B_RG2, 320 + i * 64, par, p0 + hg * 16);
                }
#pragma unroll
                for (int i = 0; i < 23; i++) mbar_init(B_GUD + i * 8, i == 10 ? 8 : i == 22 || i == 9 || !i ? 4 : i < 16 ? 1 : 2);
                bulk_store(sc + SC_HALO, SM_SENT, 5120);
                asm volatile("cp.async.bulk.commit_group;\ncp.async.bulk.wait_group 0;" ::: "memory");
                mbar_arrive(B_RG2);
                TS(43);
                const unsigned goal = (ld_relaxed4(g_cnt + 32) | (NCTA - 1)) + 1;
#pragma unroll 1
                for (int i = 0; i < RS_N; i++) {
                    pace(t_start, RS_T0 + i * RS_DT);
                    bulk_store(sc + i * (1280 / RS_N), SM_SENT, 20480 / RS_N);
                }
                asm volatile("cp.async.bulk.commit_group;\ncp.async.bulk.wait_group 0;" ::: "memory");
                red_inc(g_cnt + 32, goal);
                mbar_arrive(B_RS);
                TS(44);
                while (ld_relaxed4(g_cnt + 32) - goal > 0x80000000u) {}
                mbar_arrive(B_INIT);
                TS(45);
            }
        } else if (warp == 14) {
            if (elect_one()) {
#pragma unroll 1
                for (int kb = 1; kb < 10; kb++) {
                    const uint32_t fb = B_FULL + (kb & 3) * 16, dst = SM_X + (kb & 3) * 16384;
                    mbar_wait(fb + (B_EMPTY - B_FULL + 8), ~(kb >> 2) & 1);
                    if (kb >= 4) mbar_wait(B_XE + (kb - 4 >> 1) * 8, 0);
                    pace(t_start, max(PACE_A - PACE_B / 2 + 2 * kb * PACE_B, PACE_W0 - X_OFF + (2 * kb + 1) * PACE));
                    tma_3d(dst, &P.x2, fb, kb * 64, par, p0);
                    TS5(41 + kb);
                }
            }
            __syncwarp();
            pace(t_start, CAND_T);
            {
                const uint32_t tag = lds4(SM_KEY + 20 * 4);
                uint4 c[2], v;
                do {
                    c[0] = ld_relaxed16(g_cand + lane * 2);
                    c[1] = ld_relaxed16(g_cand + lane * 2 + 64);
                    v = ld_relaxed16(g_gate + tile * 128 + lane * 4);
                } while (__any_sync(0xffffffffu, ((c[0].x ^ tag) | (c[0].z ^ tag) | (c[1].x ^ tag) | (c[1].z ^ tag) | (v.x ^ tag) |
                                                  (v.y ^ tag) | (v.z ^ tag) | (v.w ^ tag)) & 0xF800u));
                const uint32_t a1 = max(c[0].x, c[0].z), b1 = max(c[1].x, c[1].z), l1 = max(a1, b1);
                const uint32_t l2 = max(max(max(c[0].y, c[0].w), max(c[1].y, c[1].w)),
                                        max(max(min(c[0].x, c[0].z), min(c[1].x, c[1].z)), min(a1, b1)));
                const uint32_t k1 = __reduce_max_sync(0xffffffffu, l1);
                const uint32_t k2 = __reduce_max_sync(0xffffffffu, l1 == k1 ? l2 : l1);
                sts16(SM_GATE + lane * 16, v.x, v.y, v.z, v.w);
                __syncwarp();
                if (elect_one()) {
                    bulk_load(SM_XS, P.xp + (~k1 & 2047) * 640 + (cid & 3) * 160, 320, B_XS);
                    bulk_load(SM_XS + 320, P.xp + (~k2 & 2047) * 640 + (cid & 3) * 160, 320, B_XS);
                    sts16(SM_KEY + 16 * 4, k1, k2, 0, 0);
                    mbar_expect_tx(B_XS, 640);
                    mbar_arrive(B_GT);
                    TS(56);
                }
            }
            bar_sync(12, 64);
            pace(t_start, 0);
            pace(clock(), HALO_D);
            pace(t_start, HALO_T);
            TS(24);
            uint4 hv[5];
            poll<5>(hv, sc + (SC_HALO - (tile < 2 ? 0 : 16 * SC_SIZE) + lane), 32);
#pragma unroll
            for (int s = 0; s < 5; s++) sts16(SM_HALO + s * 512 + lane * 16, hv[s].x, hv[s].y, hv[s].z, hv[s].w);
            bar_arrive(8, 64);
            TS(25);
        } else {
            if (elect_one()) {
#pragma unroll 1
                for (int s = W_S0; s < 20; s++) {
                    const uint32_t fb = B_FULL + (s & 7) * 8, dst = SM_W + (s & 7) * 15360;
                    mbar_wait(fb + (B_EMPTY - B_FULL), ~(s >> 3) & 1);
                    pace(t_start, max(PACE_A + s * PACE_B, PACE_W0 + s * PACE));
                    mbar_expect_tx(fb, (s & 1) ? 15360 : 15360 + 16384);
                    tma_3d(dst, &P.w, fb, wcm, s * 32, 0);
                    tma_3d(dst + 12288, &P.wr, fb, wcr, s * 32, 0);
                    TS2(20 + s);
                    if (s == W_S0) TS(41);
                }
                mbar_wait(B_RG2, 0);
                if (NFFN) {
                    mbar_wait(B_EMPTY + 5 * 8, 1);
                    mbar_expect_tx(B_UP, cid < NFFN ? 20480 : 16384);
                    TS(46);
                    if (cid < NFFN) tma_2d(SM_UP, &P.up, B_UP, (cid >> 2) * 64, (cid & 3) * 160);
                    else
#pragma unroll 1
                        for (int i = 0; i < 8; i++) tma_2d(SM_UP + i * 2048, &P.down, B_UP, i * 64, cid * 32 - 2352);
                }
                const int cb = hg >> 1, ca = (cb * 5 + 1) >> 1, cr = cb * 160 + ((cb & 1) ? 0 : 128);
                pace(t_start, C0_T);
#pragma unroll 1
                for (int j = 0; j < 8; j++) {
                    const int i = j ^ (j == 3 || j == 4 ? 7 : 0);
                    if (j != 3) mbar_wait(j < 3 ? B_EMPTY + ((2 * j + 7) & 7) * 8 : B_GUD + (j - 4) * 8, j == 0);
                    if (j >= 5) pace(clock(), j == 5 ? C5_D : C6_D);
                    const uint32_t dst = wo_buf(i), gb = B_G2 + i * 8;
                    mbar_expect_tx(gb, 25600);
                    tma_3d(dst, &P.woa, gb, 0, src_of(i, hg) * 80, ca);
                    tma_2d(dst + 20480, &P.wob, gb, cr, src_of(i, hg) * 80);
                }
            }
        }
    }
}

typedef CUresult (*EncodeFn)(CUtensorMap*, CUtensorMapDataType, cuuint32_t, void*, const cuuint64_t*, const cuuint64_t*,
                             const cuuint32_t*, const cuuint32_t*, CUtensorMapInterleave, CUtensorMapSwizzle,
                             CUtensorMapL2promotion, CUtensorMapFloatOOBfill);

void encode(EncodeFn fn, CUtensorMap* m, const void* ptr, int rank, const cuuint64_t* dims, const cuuint64_t* strides,
            const cuuint32_t* box, CUtensorMapSwizzle swz) {
    const cuuint32_t es[4] = {1, 1, 1, 1};
    fn(m, CU_TENSOR_MAP_DATA_TYPE_BFLOAT16, rank, const_cast<void*>(ptr), dims, strides, box, es,
       CU_TENSOR_MAP_INTERLEAVE_NONE, swz, CU_TENSOR_MAP_L2_PROMOTION_L2_128B, CU_TENSOR_MAP_FLOAT_OOB_FILL_NONE);
}

}

extern "C" void kernel_launch(void* const* d_in, const int* in_sizes, int n_in, void* d_out, int out_size) {
    (void)in_sizes; (void)n_in; (void)out_size;
    Params P;
    P.xp = (const __nv_bfloat16*)d_in[0];
    P.wp = (const __nv_bfloat16*)d_in[1];
    P.op = (__nv_bfloat16*)d_out;
    P.w_r = (const __nv_bfloat16*)d_in[4];
    P.gate_w = (const __nv_bfloat16*)d_in[8];

    void* fp = nullptr;
    cudaDriverEntryPointQueryResult st;
    cudaGetDriverEntryPoint("cuTensorMapEncodeTiled", &fp, cudaEnableDefault, &st);
    EncodeFn fn = (EncodeFn)fp;
    const cuuint64_t xd[3] = {640, 2, 1024}, xs[2] = {1280, 2560};
    const cuuint32_t bx[3] = {64, 1, 64}, bx2[3] = {64, 1, 128};
    encode(fn, &P.x2, d_in[0], 3, xd, xs, bx2, CU_TENSOR_MAP_SWIZZLE_128B);
    encode(fn, &P.x, d_in[0], 3, xd, xs, bx, CU_TENSOR_MAP_SWIZZLE_128B);
    const cuuint64_t wd[3] = {640, 640, 3}, ws[2] = {3840, 1280};
    const cuuint32_t bw[3] = {64, 32, 3}, bwr[3] = {16, 32, 3};
    encode(fn, &P.w, d_in[1], 3, wd, ws, bw, CU_TENSOR_MAP_SWIZZLE_128B);
    encode(fn, &P.wr, d_in[1], 3, wd, ws, bwr, CU_TENSOR_MAP_SWIZZLE_32B);
    const cuuint64_t ad[3] = {64, 640, 10}, as[2] = {1280, 128}, bd[2] = {640, 640};
    const cuuint32_t ba[3] = {64, 80, 2}, bb[2] = {32, 80};
    encode(fn, &P.woa, d_in[2], 3, ad, as, ba, CU_TENSOR_MAP_SWIZZLE_128B);
    encode(fn, &P.wob, d_in[2], 2, bd, as, bb, CU_TENSOR_MAP_SWIZZLE_128B);
    const cuuint64_t gd[2] = {1728, 640}, gs[1] = {3456}, dd[2] = {640, 1728};
    const cuuint32_t bg[2] = {64, 20}, bu[2] = {64, 160}, bdn[2] = {64, 16}, bxg[3] = {64, 1, 16};
    encode(fn, &P.xg, d_in[0], 3, xd, xs, bxg, CU_TENSOR_MAP_SWIZZLE_128B);
    encode(fn, &P.gate, d_in[5], 2, gd, gs, bg, CU_TENSOR_MAP_SWIZZLE_128B);
    encode(fn, &P.up, d_in[6], 2, gd, gs, bu, CU_TENSOR_MAP_SWIZZLE_128B);
    encode(fn, &P.down, d_in[7], 2, dd, as, bdn, CU_TENSOR_MAP_SWIZZLE_128B);

    cudaFuncSetAttribute(fused_kernel, cudaFuncAttributeMaxDynamicSharedMemorySize, SM_TOTAL);
    fused_kernel<<<NCTA + NEXTRA, 512, SM_TOTAL, cudaStreamPerThread>>>(P);
}
```
